```python
import torch

def _softmax(x, axis=-1):
    return torch.softmax(x, dim=axis)
def _gelu(x):
    return torch.nn.functional.gelu(x, approximate="tanh")
def _silu(x):
    return torch.nn.functional.silu(x)
def _sigmoid(x):
    return torch.sigmoid(x)
def _layernorm(x, axis=-1, eps=1e-5):
    m = x.mean(dim=axis, keepdim=True)
    v = x.var(dim=axis, keepdim=True, unbiased=False)
    return (x - m) / torch.sqrt(v + eps)
def _scatter_add(tgt, idx, src, axis=0):
    return tgt.clone().index_add_(axis, idx, src)
def _segment_sum(src, seg, n):
    out = torch.zeros((n,) + src.shape[1:], dtype=src.dtype)
    return out.index_add_(0, seg, src)
def _pad(x, pw):
    flat = tuple(v for pair in reversed(pw) for v in pair)
    return torch.nn.functional.pad(x, flat)

kernel_name = 'standalone__window_attn_swin_v2__vision'

def setup_inputs():

    _w = (lambda a: (lambda t: t.to(torch.bfloat16) if t.is_floating_point() else t)(torch.as_tensor(a)))
    win = 7
    H = W = (512 // win) * win
    C = 192
    nh = 4
    shift = win // 2
    coords = torch.stack(torch.meshgrid(torch.arange(win), torch.arange(win), indexing="ij"), -1).reshape(-1, 2)
    rel = coords[:, None, :] - coords[None, :, :]
    rel_idx = ((rel[..., 0] + win - 1) * (2 * win - 1) + (rel[..., 1] + win - 1)).to(torch.int64)
    tab = torch.stack(torch.meshgrid(torch.arange(1 - win, win), torch.arange(1 - win, win), indexing="ij"), -1).reshape(-1, 2).to(float)
    tab = (lambda _x: torch.sign(torch.as_tensor(_x)))(tab) * (lambda _x: torch.log1p(torch.as_tensor(_x)))(torch.abs(tab))
    img = torch.zeros((H, W), dtype=torch.int64)
    cnt = 0
    for hs in (slice(0, H - win), slice(H - win, H - shift), slice(H - shift, H)):
        for ws in (slice(0, W - win), slice(W - win, W - shift), slice(W - shift, W)):
            img[hs, ws] = cnt; cnt += 1
    mw = img.reshape(H // win, win, W // win, win).permute(0, 2, 1, 3).reshape(-1, win * win)
    mask = (mw[:, :, None] != mw[:, None, :]).to(float) * (-100.0)
    return {
        "x": _w((lambda *s: torch.randn(*s, dtype=torch.bfloat16) * 0.05)(1, H, W, C)),
        "wqkv": _w((lambda *s: torch.randn(*s, dtype=torch.bfloat16) * 1.6)(C, 3 * C)),
        "wo": _w((lambda *s: torch.randn(*s, dtype=torch.bfloat16) * 0.05)(C, C)),
        "logit_scale": _w((lambda *s: torch.randn(*s, dtype=torch.bfloat16) * 1.6)(nh)),
        "cpb_w1": _w((lambda *s: torch.randn(*s, dtype=torch.bfloat16) * 1.6)(2, 4 * nh)),
        "cpb_w2": _w((lambda *s: torch.randn(*s, dtype=torch.bfloat16) * 1.6)(4 * nh, nh)),
        "rel_coords": _w(tab),
        "rel_idx": _w(rel_idx),
        "attn_mask": _w(mask),
    }

def reference(x, wqkv, wo, logit_scale, cpb_w1, cpb_w2, rel_coords, rel_idx, attn_mask):
    B, H, W, C = x.shape
    win = 7
    nh = 4
    hd = C // nh
    shift = win // 2
    ww = win * win
    nH, nW = H // win, W // win
    xs = torch.roll(x, (-shift, -shift), (1, 2))
    xw = (lambda x, *d: x.permute(*d))(xs.reshape(B, nH, win, nW, win, C), 0, 1, 3, 2, 4, 5).reshape(B * nH * nW, ww, C)
    qkv = (lambda x, *d: x.permute(*d))((xw @ wqkv).reshape(B * nH * nW, ww, 3, nh, hd), 2, 0, 3, 1, 4)
    q, k, v = qkv[0], qkv[1], qkv[2]
    qn = q * (torch.einsum("bhqd,bhqd->bhq", q, q)[..., None] + 1e-12) ** -0.5
    kn = k * (torch.einsum("bhkd,bhkd->bhk", k, k)[..., None] + 1e-12) ** -0.5
    logits = torch.einsum("bhqd,bhkd->bhqk", qn, kn)
    tau = torch.exp(torch.clip(logit_scale, -100.0, 4.6052))
    logits = logits * tau[None, :, None, None]
    hcpb = rel_coords @ cpb_w1
    hcpb = torch.where(hcpb > 0, hcpb, hcpb * 0)
    bias_tab = 16.0 * _sigmoid(hcpb @ cpb_w2)
    bias = (lambda x, *d: x.permute(*d))(bias_tab[rel_idx], 2, 0, 1)
    logits = logits.reshape(B, nH * nW, nh, ww, ww) + bias[None, None, :, :, :] + attn_mask[None, :, None, :, :]
    p = _softmax(logits.reshape(B * nH * nW, nh, ww, ww), axis=-1)
    o = (lambda x, *d: x.permute(*d))(torch.einsum("bhqk,bhkd->bhqd", p, v), 0, 2, 1, 3).reshape(B * nH * nW, ww, C) @ wo
    o = (lambda x, *d: x.permute(*d))(o.reshape(B, nH, nW, win, win, C), 0, 1, 3, 2, 4, 5).reshape(B, H, W, C)
    o = torch.roll(o, (shift, shift), (1, 2))
    return _layernorm(o, axis=-1)
```

```cpp
#include <cuda_runtime.h>
#include <cuda.h>
#include <cuda_bf16.h>
#include <stdint.h>
#include <type_traits>

namespace swin {

#define NPAIR 54
#define QFP32 0
#define PF_DIST 3
#define EXP 0
#define QSPLIT 3
#define SSPLIT 0
#define LATEMASK 0
#define CLUSTER 0
#define NOPF 0
#define NTAIL 216
#define PSTORE 1
#define PORDER 1
#define GORD 0
#define GMERGE 0
#define XSPLIT 1
#define EARLYW 1
#define NEARLY 4
#define REG_G 200
#define REG_A 144
#define REG_H 24
constexpr int IMG      = 511;
constexpr int NWS      = 73;
constexpr int NWINDOWS = NWS * NWS;
constexpr int TOK      = 49;
constexpr int NPIX     = IMG * IMG;
constexpr int NTHREADS = 512;

constexpr int W_ATOM = 6144;
constexpr int SM_WA = 0, SM_WB = 6 * W_ATOM, SM_WV = 12 * W_ATOM;
constexpr int GRP   = TOK * 16;
constexpr int XCH   = TOK * 128;
constexpr int SM_V  = 18 * W_ATOM, V_STRIDE = 10240, O_PITCH = 208;
constexpr int SM_QK = SM_V + 4 * V_STRIDE, QK_CHUNK = 4 * XCH;
constexpr int SM_MASK = SM_QK + 3 * QK_CHUNK;
constexpr int SM_TAB  = SM_V + 3 * V_STRIDE + 256;
constexpr int SM_DUMP = SM_MASK + 4816;
constexpr int SM_BAR  = SM_DUMP + 320;
constexpr int B_XFULL = 0, B_WRAW = 32, B_QKRAW = 64, B_QKFREE = 96, B_VFREE = 128, B_ODONE = 160,
              B_VRAW = 224, B_MFULL = 256, B_MCONS = 272, B_WFULL = 280, B_STORED = 288, B_PUBD = 304;
constexpr int SM_A_END = SM_BAR + 320;
static_assert(SM_QK % 1024 == 0 && TOK * O_PITCH + 64 - 16 <= V_STRIDE && (28 * O_PITCH + 64) % 128 == 0, "layout");
constexpr int SM_WO    = 0;
constexpr int SM_STAGE = 73728;
constexpr int STAGE_BYTES = 24576;
constexpr int SM_PBAR  = SM_A_END;
constexpr int SM_TOTAL = SM_PBAR + 152;
static_assert(SM_STAGE + 6 * STAGE_BYTES <= SM_BAR, "smem");
static_assert(SM_TOTAL <= 232448, "smem");
static_assert(SM_BAR % 8 == 0, "barrier alignment");

constexpr int SEG_B   = 3 * IMG;
constexpr int TILES_A = (NPIX - SEG_B + 63) / 64;
constexpr int TILES   = TILES_A + (SEG_B + 63) / 64;
constexpr uint32_t ROW_DONE = NWS * 2;

__device__ uint32_t g_cnt[NWS + 7];
__device__ uint32_t g_done;

#define TR(ev, idx)
constexpr float LOG2E = 1.4426950408889634f;

__device__ __forceinline__ uint32_t smem_u32(const void* p) {
    return (uint32_t)__cvta_generic_to_shared(p);
}
__device__ __forceinline__ uint64_t make_desc(uint32_t saddr, uint32_t lbo, uint32_t sbo, uint32_t swz = 0) {
    return (uint64_t)((saddr & 0x3FFFF) >> 4) | ((uint64_t)(lbo >> 4) << 16) | ((uint64_t)(sbo >> 4) << 32) |
           ((uint64_t)swz << 62);
}
__host__ __device__ constexpr uint64_t make_desc_c(uint32_t saddr, uint32_t lbo, uint32_t sbo, uint32_t swz) {
    return (uint64_t)(saddr >> 4) | ((uint64_t)(lbo >> 4) << 16) | ((uint64_t)(sbo >> 4) << 32) | ((uint64_t)swz << 62);
}
__device__ __forceinline__ void wgmma_fence()  { asm volatile("wgmma.fence.sync.aligned;\n" ::: "memory"); }
__device__ __forceinline__ void wgmma_commit() { asm volatile("wgmma.commit_group.sync.aligned;\n" ::: "memory"); }
template <int N> __device__ __forceinline__ void wgmma_wait() {
    asm volatile("wgmma.wait_group.sync.aligned %0;\n" :: "n"(N) : "memory");
}
__device__ __forceinline__ void fence_async_smem() { asm volatile("fence.proxy.async.shared::cta;\n" ::: "memory"); }
__device__ __forceinline__ void wg_bar(int id) { asm volatile("bar.sync %0, 128;\n" :: "r"(id) : "memory"); }

template <int N> __device__ __forceinline__ void reg_fence(float (&v)[N]) {
#pragma unroll
    for (int i = 0; i < N; i++) asm volatile("" : "+f"(v[i]) :: "memory");
}
template <int N> __device__ __forceinline__ void reg_fence(uint32_t (&v)[N]) {
#pragma unroll
    for (int i = 0; i < N; i++) asm volatile("" : "+r"(v[i]) :: "memory");
}
template <int N, int M> __device__ __forceinline__ void reg_fence(uint32_t (&v)[N][M]) {
#pragma unroll
    for (int i = 0; i < N; i++) reg_fence(v[i]);
}

__device__ __forceinline__ uint32_t pack_bf16(float lo, float hi) {
    uint32_t r;
    asm("cvt.rn.bf16x2.f32 %0, %1, %2;\n" : "=r"(r) : "f"(hi), "f"(lo));
    return r;
}
__device__ __forceinline__ float bf16lo(uint32_t v) { return __uint_as_float(v << 16); }
__device__ __forceinline__ float bf16hi(uint32_t v) { return __uint_as_float(v & 0xFFFF0000u); }
__device__ __forceinline__ uint32_t hadd2_bf16(uint32_t a, uint32_t b) {
    uint32_t r;
    asm("add.rn.bf16x2 %0, %1, %2;\n" : "=r"(r) : "r"(a), "r"(b));
    return r;
}
__device__ __forceinline__ uint32_t hmul2_bf16(uint32_t a, uint32_t b) {
    uint32_t r;
    asm("mul.rn.bf16x2 %0, %1, %2;\n" : "=r"(r) : "r"(a), "r"(b));
    return r;
}
__device__ __forceinline__ uint32_t hsub2_bf16(uint32_t a, uint32_t b) {
    uint32_t r;
    asm("sub.rn.bf16x2 %0, %1, %2;\n" : "=r"(r) : "r"(a), "r"(b));
    return r;
}
__device__ __forceinline__ uint32_t hfma2_bf16(uint32_t a, uint32_t b, uint32_t c) {
    uint32_t r;
    asm("fma.rn.bf16x2 %0, %1, %2, %3;\n" : "=r"(r) : "r"(a), "r"(b), "r"(c));
    return r;
}
__device__ __forceinline__ uint32_t hmax2_bf16(uint32_t a, uint32_t b) {
    uint32_t r;
    asm("max.bf16x2 %0, %1, %2;\n" : "=r"(r) : "r"(a), "r"(b));
    return r;
}
__device__ __forceinline__ uint32_t ex2_bf16x2(uint32_t a) {
    uint32_t r;
    asm("ex2.approx.ftz.bf16x2 %0, %1;\n" : "=r"(r) : "r"(a));
    return r;
}
__device__ __forceinline__ uint32_t ex2_bf16lo(uint32_t a) {
    uint32_t r;
    asm("{\n.reg .b16 l, h;\nmov.b32 {l, h}, %1;\nex2.approx.ftz.bf16 l, l;\ncvt.u32.u16 %0, l;\n}\n" : "=r"(r) : "r"(a));
    return r;
}
__device__ __forceinline__ uint32_t mbar_test(uint32_t bar, uint32_t parity) {
    uint32_t ok;
    asm volatile("{\n.reg .pred p;\nmbarrier.test_wait.parity.shared::cta.b64 p, [%1], %2;\nselp.u32 %0, 1, 0, p;\n}\n"
                 : "=r"(ok) : "r"(bar), "r"(parity) : "memory");
    return ok;
}
__device__ __forceinline__ uint32_t prmt(uint32_t a, uint32_t b, uint32_t sel) {
    uint32_t r;
    asm("prmt.b32 %0, %1, %2, %3;\n" : "=r"(r) : "r"(a), "r"(b), "r"(sel));
    return r;
}
__device__ __forceinline__ float round_bf16(float x) { return __bfloat162float(__float2bfloat16_rn(x)); }

__device__ __forceinline__ void mbar_init(uint32_t bar, uint32_t count) {
    asm volatile("mbarrier.init.shared::cta.b64 [%0], %1;\n" :: "r"(bar), "r"(count) : "memory");
}
__device__ __forceinline__ void mbar_wait(uint32_t bar, uint32_t parity) {
    asm volatile(
        "{\n"
        ".reg .pred p;\n"
        ".reg .u32 n;\n"
        "mov.u32 n, 0;\n"
        "WAIT_%=:\n"
        "mbarrier.try_wait.parity.shared::cta.b64 p, [%0], %1;\n"
        "@p bra DONE_%=;\n"
        "add.u32 n, n, 1;\n"
        "setp.lt.u32 p, n, 4194304;\n"
        "@p bra WAIT_%=;\n"
        "exit;\n"
        "DONE_%=:\n"
        "}\n" :: "r"(bar), "r"(parity) : "memory");
}
__device__ __forceinline__ void mbar_wait4(uint32_t b0, uint32_t p0, uint32_t b1, uint32_t p1, uint32_t b2, uint32_t p2,
                                           uint32_t b3, uint32_t p3) {
    asm volatile(
        "{\n"
        ".reg .pred p, q, r, s;\n"
        ".reg .u32 n;\n"
        "mov.u32 n, 0;\n"
        "WAIT_%=:\n"
        "mbarrier.try_wait.parity.shared::cta.b64 p, [%0], %1;\n"
        "mbarrier.try_wait.parity.shared::cta.b64 q, [%2], %3;\n"
        "mbarrier.try_wait.parity.shared::cta.b64 r, [%4], %5;\n"
        "mbarrier.try_wait.parity.shared::cta.b64 s, [%6], %7;\n"
        "and.pred p, p, q;\n"
        "and.pred r, r, s;\n"
        "and.pred p, p, r;\n"
        "@p bra DONE_%=;\n"
        "add.u32 n, n, 1;\n"
        "setp.lt.u32 p, n, 4194304;\n"
        "@p bra WAIT_%=;\n"
        "exit;\n"
        "DONE_%=:\n"
        "}\n" :: "r"(b0), "r"(p0), "r"(b1), "r"(p1), "r"(b2), "r"(p2), "r"(b3), "r"(p3) : "memory");
}
__device__ __forceinline__ void mbar_wait2(uint32_t b0, uint32_t p0, uint32_t b1, uint32_t p1) {
    asm volatile(
        "{\n"
        ".reg .pred p, q;\n"
        ".reg .u32 n;\n"
        "mov.u32 n, 0;\n"
        "WAIT_%=:\n"
        "mbarrier.try_wait.parity.shared::cta.b64 p, [%0], %1;\n"
        "mbarrier.try_wait.parity.shared::cta.b64 q, [%2], %3;\n"
        "and.pred p, p, q;\n"
        "@p bra DONE_%=;\n"
        "add.u32 n, n, 1;\n"
        "setp.lt.u32 p, n, 4194304;\n"
        "@p bra WAIT_%=;\n"
        "exit;\n"
        "DONE_%=:\n"
        "}\n" :: "r"(b0), "r"(p0), "r"(b1), "r"(p1) : "memory");
}
__device__ __forceinline__ void mbar_wait_unless(uint32_t ok, uint32_t bar, uint32_t parity) {
    asm volatile(
        "{\n"
        ".reg .pred p;\n"
        ".reg .u32 n;\n"
        "setp.ne.u32 p, %2, 0;\n"
        "vote.sync.all.pred p, p, 0xffffffff;\n"
        "@p bra DONE_%=;\n"
        "mov.u32 n, 0;\n"
        "WAIT_%=:\n"
        "mbarrier.try_wait.parity.shared::cta.b64 p, [%0], %1;\n"
        "@p bra DONE_%=;\n"
        "add.u32 n, n, 1;\n"
        "setp.lt.u32 p, n, 4194304;\n"
        "@p bra WAIT_%=;\n"
        "exit;\n"
        "DONE_%=:\n"
        "}\n" :: "r"(bar), "r"(parity), "r"(ok) : "memory");
}
__device__ __forceinline__ void mbar_wait2_unless(uint32_t ok, uint32_t b0, uint32_t p0, uint32_t b1, uint32_t p1) {
    asm volatile(
        "{\n"
        ".reg .pred p, q;\n"
        ".reg .u32 n;\n"
        "setp.ne.u32 p, %4, 0;\n"
        "vote.sync.all.pred p, p, 0xffffffff;\n"
        "@p bra DONE_%=;\n"
        "mov.u32 n, 0;\n"
        "WAIT_%=:\n"
        "mbarrier.try_wait.parity.shared::cta.b64 p, [%0], %1;\n"
        "mbarrier.try_wait.parity.shared::cta.b64 q, [%2], %3;\n"
        "and.pred p, p, q;\n"
        "@p bra DONE_%=;\n"
        "add.u32 n, n, 1;\n"
        "setp.lt.u32 p, n, 4194304;\n"
        "@p bra WAIT_%=;\n"
        "exit;\n"
        "DONE_%=:\n"
        "}\n" :: "r"(b0), "r"(p0), "r"(b1), "r"(p1), "r"(ok) : "memory");
}
__device__ __forceinline__ void mbar_wait4_unless(uint32_t ok, uint32_t b0, uint32_t p0, uint32_t b1, uint32_t p1, uint32_t b2,
                                                  uint32_t p2, uint32_t b3, uint32_t p3) {
    asm volatile(
        "{\n"
        ".reg .pred p, q, r, s;\n"
        ".reg .u32 n;\n"
        "setp.ne.u32 p, %8, 0;\n"
        "vote.sync.all.pred p, p, 0xffffffff;\n"
        "@p bra DONE_%=;\n"
        "mov.u32 n, 0;\n"
        "WAIT_%=:\n"
        "mbarrier.try_wait.parity.shared::cta.b64 p, [%0], %1;\n"
        "mbarrier.try_wait.parity.shared::cta.b64 q, [%2], %3;\n"
        "mbarrier.try_wait.parity.shared::cta.b64 r, [%4], %5;\n"
        "mbarrier.try_wait.parity.shared::cta.b64 s, [%6], %7;\n"
        "and.pred p, p, q;\n"
        "and.pred r, r, s;\n"
        "and.pred p, p, r;\n"
        "@p bra DONE_%=;\n"
        "add.u32 n, n, 1;\n"
        "setp.lt.u32 p, n, 4194304;\n"
        "@p bra WAIT_%=;\n"
        "exit;\n"
        "DONE_%=:\n"
        "}\n" :: "r"(b0), "r"(p0), "r"(b1), "r"(p1), "r"(b2), "r"(p2), "r"(b3), "r"(p3), "r"(ok) : "memory");
}
__device__ __forceinline__ void sched_fence(uint32_t zero, uint32_t a, uint32_t b, uint32_t c, uint32_t d, uint32_t e = 0,
                                            uint32_t f = 0, uint32_t g = 0, uint32_t h = 0, uint32_t i = 0, uint32_t j = 0,
                                            uint32_t k = 0) {
    asm volatile("{\n.reg .pred p;\n.reg .u32 n;\nsetp.eq.u32 p, %0, 0;\n@p bra.uni DONE_%=;\nmov.u32 n, %0;\nSPIN_%=:\n"
                 "nanosleep.u32 %1;\nnanosleep.u32 %2;\nnanosleep.u32 %3;\nnanosleep.u32 %4;\nnanosleep.u32 %5;\n"
                 "nanosleep.u32 %6;\nnanosleep.u32 %7;\nnanosleep.u32 %8;\nnanosleep.u32 %9;\nnanosleep.u32 %10;\n"
                 "nanosleep.u32 %11;\nsub.u32 n, n, 1;\nsetp.ne.u32 p, n, 0;\n@p bra.uni SPIN_%=;\nDONE_%=:\n}\n"
                 :: "r"(zero), "r"(a), "r"(b), "r"(c), "r"(d), "r"(e), "r"(f), "r"(g), "r"(h), "r"(i), "r"(j), "r"(k) : "memory");
}
__device__ __forceinline__ void mbar_arrive(uint32_t bar) {
    asm volatile("mbarrier.arrive.shared::cta.b64 _, [%0];\n" :: "r"(bar) : "memory");
}
__device__ __forceinline__ void mbar_arrive_n(uint32_t bar, uint32_t n) {
    asm volatile("mbarrier.arrive.shared::cta.b64 _, [%0], %1;\n" :: "r"(bar), "r"(n) : "memory");
}
__device__ __forceinline__ void mbar_arrive_expect_tx(uint32_t bar, uint32_t bytes) {
    asm volatile("mbarrier.arrive.expect_tx.shared::cta.b64 _, [%0], %1;\n" :: "r"(bar), "r"(bytes) : "memory");
}
__device__ __forceinline__ void stg128_if(bool p, void* addr, uint32_t x, uint32_t y, uint32_t z, uint32_t w) {
    asm volatile("{\n.reg .pred q;\nsetp.ne.b32 q, %5, 0;\n@q st.global.L1::no_allocate.v4.b32 [%0], {%1, %2, %3, %4};\n}\n"
                 :: "l"(addr), "r"(x), "r"(y), "r"(z), "r"(w), "r"((uint32_t)p) : "memory");
}
__device__ __forceinline__ void stsm_x4(uint32_t addr, uint32_t r0, uint32_t r1, uint32_t r2, uint32_t r3) {
    asm volatile("stmatrix.sync.aligned.m8n8.x4.shared.b16 [%0], {%1, %2, %3, %4};\n"
                 :: "r"(addr), "r"(r0), "r"(r1), "r"(r2), "r"(r3) : "memory");
}
__device__ __forceinline__ void stsm_x2(uint32_t addr, uint32_t r0, uint32_t r1) {
    asm volatile("stmatrix.sync.aligned.m8n8.x2.shared.b16 [%0], {%1, %2};\n" :: "r"(addr), "r"(r0), "r"(r1) : "memory");
}
__device__ __forceinline__ void sts128(uint32_t addr, uint32_t r0, uint32_t r1, uint32_t r2, uint32_t r3) {
    asm volatile("st.shared.v4.b32 [%0], {%1, %2, %3, %4};\n" :: "r"(addr), "r"(r0), "r"(r1), "r"(r2), "r"(r3) : "memory");
}
__device__ __forceinline__ void sts32(uint32_t addr, uint32_t v) {
    asm volatile("st.shared.b32 [%0], %1;\n" :: "r"(addr), "r"(v) : "memory");
}
__device__ __forceinline__ uint32_t lds32(uint32_t addr) {
    uint32_t v;
    asm volatile("ld.shared.b32 %0, [%1];\n" : "=r"(v) : "r"(addr) : "memory");
    return v;
}
__device__ __forceinline__ void ldg_nc_v4(uint32_t (&r)[4], const void* p) {
    asm volatile("ld.global.nc.L1::no_allocate.v4.u32 {%0, %1, %2, %3}, [%4];\n"
                 : "=r"(r[0]), "=r"(r[1]), "=r"(r[2]), "=r"(r[3]) : "l"(p));
}
__device__ __forceinline__ uint32_t ldg_u32(const void* p) {
    uint32_t v;
    asm volatile("ld.global.nc.L1::evict_first.u32 %0, [%1];\n" : "=r"(v) : "l"(p));
    return v;
}
__device__ __forceinline__ void ldg_u64(const void* p, uint32_t& a, uint32_t& b) {
    asm volatile("ld.global.nc.L1::evict_first.v2.u32 {%0, %1}, [%2];\n" : "=r"(a), "=r"(b) : "l"(p));
}
__device__ __forceinline__ void prefetch_l2(const void* p) {
    asm volatile("prefetch.global.L2 [%0];\n" :: "l"(p));
}
__device__ __forceinline__ void cp_async16(uint32_t dst, const void* src) {
    asm volatile("cp.async.cg.shared.global [%0], [%1], 16;\n" :: "r"(dst), "l"(src) : "memory");
}
__device__ __forceinline__ float ex2_ftz(float x) {
    float y;
    asm("ex2.approx.ftz.f32 %0, %1;\n" : "=f"(y) : "f"(x));
    return y;
}
__device__ __forceinline__ float rcp_ftz(float x) {
    float y;
    asm("rcp.approx.ftz.f32 %0, %1;\n" : "=f"(y) : "f"(x));
    return y;
}
__device__ __forceinline__ float rsqrt_ftz(float x) {
    float y;
    asm("rsqrt.approx.ftz.f32 %0, %1;\n" : "=f"(y) : "f"(x));
    return y;
}

__device__ __forceinline__ bool elect_one() {
    uint32_t p;
    asm volatile("{\n.reg .pred q;\nelect.sync _|q, 0xffffffff;\nselp.u32 %0, 1, 0, q;\n}\n" : "=r"(p));
    return p != 0;
}
__device__ __forceinline__ void ldsm_x4(uint32_t (&r)[4], uint32_t addr) {
    asm volatile("ldmatrix.sync.aligned.m8n8.x4.shared.b16 {%0, %1, %2, %3}, [%4];\n"
                 : "=r"(r[0]), "=r"(r[1]), "=r"(r[2]), "=r"(r[3]) : "r"(addr) : "memory");
}
__device__ __forceinline__ void ldsm_x2(uint32_t& r0, uint32_t& r1, uint32_t addr) {
    asm volatile("ldmatrix.sync.aligned.m8n8.x2.shared.b16 {%0, %1}, [%2];\n" : "=r"(r0), "=r"(r1) : "r"(addr) : "memory");
}
__device__ __forceinline__ void tma_2d(uint32_t dst, const CUtensorMap* map, uint32_t bar, int c0, int c1) {
    asm volatile("cp.async.bulk.tensor.2d.shared::cluster.global.mbarrier::complete_tx::bytes [%0], [%1, {%3, %4}], [%2];\n"
                 :: "r"(dst), "l"(reinterpret_cast<uint64_t>(map)), "r"(bar), "r"(c0), "r"(c1) : "memory");
}
__device__ __forceinline__ void tma_3d(uint32_t dst, const CUtensorMap* map, uint32_t bar, int c0, int c1, int c2) {
    asm volatile("cp.async.bulk.tensor.3d.shared::cluster.global.mbarrier::complete_tx::bytes [%0], [%1, {%3, %4, %5}], [%2];\n"
                 :: "r"(dst), "l"(reinterpret_cast<uint64_t>(map)), "r"(bar), "r"(c0), "r"(c1), "r"(c2) : "memory");
}
__device__ __forceinline__ void tma_store_4d(const CUtensorMap* map, uint32_t src, int c0, int c1, int c2, int c3) {
    asm volatile("cp.async.bulk.tensor.4d.global.shared::cta.tile.bulk_group [%0, {%2, %3, %4, %5}], [%1];\n"
                 :: "l"(reinterpret_cast<uint64_t>(map)), "r"(src), "r"(c0), "r"(c1), "r"(c2), "r"(c3) : "memory");
}
__device__ __forceinline__ void mbar_arrive_if(uint32_t bar, uint32_t cnt) {
    asm volatile("{\n.reg .pred q;\nsetp.ne.b32 q, %1, 0;\n@q mbarrier.arrive.shared::cta.b64 _, [%0], %1;\n}\n"
                 :: "r"(bar), "r"(cnt) : "memory");
}

template <int BOFF, int AOFF, int NA>
__device__ __forceinline__ void mma_qkv_a(float (&d)[48], const uint32_t (&a)[NA][4], uint64_t descB) {
    asm volatile(
        "{\n"
        ".reg .pred p0, p1;\n"
        ".reg .b64 ta, ta0, tb, tb0;\n"
        "setp.ne.b32 p0, 0, 0;\n"
        "setp.eq.b32 p1, 0, 0;\n"
        "add.s64 tb0, %72, %73;\n"
        "add.s64 tb, tb0, 0;\n"
        "wgmma.mma_async.sync.aligned.m64n96k16.f32.bf16.bf16 {%0, %1, %2, %3, %4, %5, %6, %7, %8, %9, %10, %11, %12, %13, %14, %15, %16, %17, %18, %19, %20, %21, %22, %23, %24, %25, %26, %27, %28, %29, %30, %31, %32, %33, %34, %35, %36, %37, %38, %39, %40, %41, %42, %43, %44, %45, %46, %47}, {%48, %49, %50, %51}, tb, p0, 1, 1, 1;\n"
        "add.s64 tb, tb0, 32;\n"
        "wgmma.mma_async.sync.aligned.m64n96k16.f32.bf16.bf16 {%0, %1, %2, %3, %4, %5, %6, %7, %8, %9, %10, %11, %12, %13, %14, %15, %16, %17, %18, %19, %20, %21, %22, %23, %24, %25, %26, %27, %28, %29, %30, %31, %32, %33, %34, %35, %36, %37, %38, %39, %40, %41, %42, %43, %44, %45, %46, %47}, {%52, %53, %54, %55}, tb, p1, 1, 1, 1;\n"
        "add.s64 tb, tb0, 64;\n"
        "wgmma.mma_async.sync.aligned.m64n96k16.f32.bf16.bf16 {%0, %1, %2, %3, %4, %5, %6, %7, %8, %9, %10, %11, %12, %13, %14, %15, %16, %17, %18, %19, %20, %21, %22, %23, %24, %25, %26, %27, %28, %29, %30, %31, %32, %33, %34, %35, %36, %37, %38, %39, %40, %41, %42, %43, %44, %45, %46, %47}, {%56, %57, %58, %59}, tb, p1, 1, 1, 1;\n"
        "add.s64 tb, tb0, 96;\n"
        "wgmma.mma_async.sync.aligned.m64n96k16.f32.bf16.bf16 {%0, %1, %2, %3, %4, %5, %6, %7, %8, %9, %10, %11, %12, %13, %14, %15, %16, %17, %18, %19, %20, %21, %22, %23, %24, %25, %26, %27, %28, %29, %30, %31, %32, %33, %34, %35, %36, %37, %38, %39, %40, %41, %42, %43, %44, %45, %46, %47}, {%60, %61, %62, %63}, tb, p1, 1, 1, 1;\n"
        "add.s64 tb, tb0, 128;\n"
        "wgmma.mma_async.sync.aligned.m64n96k16.f32.bf16.bf16 {%0, %1, %2, %3, %4, %5, %6, %7, %8, %9, %10, %11, %12, %13, %14, %15, %16, %17, %18, %19, %20, %21, %22, %23, %24, %25, %26, %27, %28, %29, %30, %31, %32, %33, %34, %35, %36, %37, %38, %39, %40, %41, %42, %43, %44, %45, %46, %47}, {%64, %65, %66, %67}, tb, p1, 1, 1, 1;\n"
        "add.s64 tb, tb0, 160;\n"
        "wgmma.mma_async.sync.aligned.m64n96k16.f32.bf16.bf16 {%0, %1, %2, %3, %4, %5, %6, %7, %8, %9, %10, %11, %12, %13, %14, %15, %16, %17, %18, %19, %20, %21, %22, %23, %24, %25, %26, %27, %28, %29, %30, %31, %32, %33, %34, %35, %36, %37, %38, %39, %40, %41, %42, %43, %44, %45, %46, %47}, {%68, %69, %70, %71}, tb, p1, 1, 1, 1;\n"
        "}\n"
        : "+f"(d[0]), "+f"(d[1]), "+f"(d[2]), "+f"(d[3]), "+f"(d[4]), "+f"(d[5]), "+f"(d[6]), "+f"(d[7]), "+f"(d[8]), "+f"(d[9]), "+f"(d[10]), "+f"(d[11]), "+f"(d[12]), "+f"(d[13]), "+f"(d[14]), "+f"(d[15]), "+f"(d[16]), "+f"(d[17]), "+f"(d[18]), "+f"(d[19]), "+f"(d[20]), "+f"(d[21]), "+f"(d[22]), "+f"(d[23]), "+f"(d[24]), "+f"(d[25]), "+f"(d[26]), "+f"(d[27]), "+f"(d[28]), "+f"(d[29]), "+f"(d[30]), "+f"(d[31]), "+f"(d[32]), "+f"(d[33]), "+f"(d[34]), "+f"(d[35]), "+f"(d[36]), "+f"(d[37]), "+f"(d[38]), "+f"(d[39]), "+f"(d[40]), "+f"(d[41]), "+f"(d[42]), "+f"(d[43]), "+f"(d[44]), "+f"(d[45]), "+f"(d[46]), "+f"(d[47])
        : "r"(a[AOFF + 0][0]), "r"(a[AOFF + 0][1]), "r"(a[AOFF + 0][2]), "r"(a[AOFF + 0][3]), "r"(a[AOFF + 1][0]), "r"(a[AOFF + 1][1]), "r"(a[AOFF + 1][2]), "r"(a[AOFF + 1][3]), "r"(a[AOFF + 2][0]), "r"(a[AOFF + 2][1]), "r"(a[AOFF + 2][2]), "r"(a[AOFF + 2][3]), "r"(a[AOFF + 3][0]), "r"(a[AOFF + 3][1]), "r"(a[AOFF + 3][2]), "r"(a[AOFF + 3][3]), "r"(a[AOFF + 4][0]), "r"(a[AOFF + 4][1]), "r"(a[AOFF + 4][2]), "r"(a[AOFF + 4][3]), "r"(a[AOFF + 5][0]), "r"(a[AOFF + 5][1]), "r"(a[AOFF + 5][2]), "r"(a[AOFF + 5][3]), "l"(descB), "n"(BOFF >> 4));
}

template <int BOFF, int AOFF, int NA>
__device__ __forceinline__ void mma_qkv_b(float (&d)[48], const uint32_t (&a)[NA][4], uint64_t descB) {
    asm volatile(
        "{\n"
        ".reg .pred p0, p1;\n"
        ".reg .b64 ta, ta0, tb, tb0;\n"
        "setp.ne.b32 p0, 0, 0;\n"
        "setp.eq.b32 p1, 0, 0;\n"
        "add.s64 tb0, %72, %73;\n"
        "add.s64 tb, tb0, 192;\n"
        "wgmma.mma_async.sync.aligned.m64n96k16.f32.bf16.bf16 {%0, %1, %2, %3, %4, %5, %6, %7, %8, %9, %10, %11, %12, %13, %14, %15, %16, %17, %18, %19, %20, %21, %22, %23, %24, %25, %26, %27, %28, %29, %30, %31, %32, %33, %34, %35, %36, %37, %38, %39, %40, %41, %42, %43, %44, %45, %46, %47}, {%48, %49, %50, %51}, tb, p1, 1, 1, 1;\n"
        "add.s64 tb, tb0, 224;\n"
        "wgmma.mma_async.sync.aligned.m64n96k16.f32.bf16.bf16 {%0, %1, %2, %3, %4, %5, %6, %7, %8, %9, %10, %11, %12, %13, %14, %15, %16, %17, %18, %19, %20, %21, %22, %23, %24, %25, %26, %27, %28, %29, %30, %31, %32, %33, %34, %35, %36, %37, %38, %39, %40, %41, %42, %43, %44, %45, %46, %47}, {%52, %53, %54, %55}, tb, p1, 1, 1, 1;\n"
        "add.s64 tb, tb0, 256;\n"
        "wgmma.mma_async.sync.aligned.m64n96k16.f32.bf16.bf16 {%0, %1, %2, %3, %4, %5, %6, %7, %8, %9, %10, %11, %12, %13, %14, %15, %16, %17, %18, %19, %20, %21, %22, %23, %24, %25, %26, %27, %28, %29, %30, %31, %32, %33, %34, %35, %36, %37, %38, %39, %40, %41, %42, %43, %44, %45, %46, %47}, {%56, %57, %58, %59}, tb, p1, 1, 1, 1;\n"
        "add.s64 tb, tb0, 288;\n"
        "wgmma.mma_async.sync.aligned.m64n96k16.f32.bf16.bf16 {%0, %1, %2, %3, %4, %5, %6, %7, %8, %9, %10, %11, %12, %13, %14, %15, %16, %17, %18, %19, %20, %21, %22, %23, %24, %25, %26, %27, %28, %29, %30, %31, %32, %33, %34, %35, %36, %37, %38, %39, %40, %41, %42, %43, %44, %45, %46, %47}, {%60, %61, %62, %63}, tb, p1, 1, 1, 1;\n"
        "add.s64 tb, tb0, 320;\n"
        "wgmma.mma_async.sync.aligned.m64n96k16.f32.bf16.bf16 {%0, %1, %2, %3, %4, %5, %6, %7, %8, %9, %10, %11, %12, %13, %14, %15, %16, %17, %18, %19, %20, %21, %22, %23, %24, %25, %26, %27, %28, %29, %30, %31, %32, %33, %34, %35, %36, %37, %38, %39, %40, %41, %42, %43, %44, %45, %46, %47}, {%64, %65, %66, %67}, tb, p1, 1, 1, 1;\n"
        "add.s64 tb, tb0, 352;\n"
        "wgmma.mma_async.sync.aligned.m64n96k16.f32.bf16.bf16 {%0, %1, %2, %3, %4, %5, %6, %7, %8, %9, %10, %11, %12, %13, %14, %15, %16, %17, %18, %19, %20, %21, %22, %23, %24, %25, %26, %27, %28, %29, %30, %31, %32, %33, %34, %35, %36, %37, %38, %39, %40, %41, %42, %43, %44, %45, %46, %47}, {%68, %69, %70, %71}, tb, p1, 1, 1, 1;\n"
        "}\n"
        : "+f"(d[0]), "+f"(d[1]), "+f"(d[2]), "+f"(d[3]), "+f"(d[4]), "+f"(d[5]), "+f"(d[6]), "+f"(d[7]), "+f"(d[8]), "+f"(d[9]), "+f"(d[10]), "+f"(d[11]), "+f"(d[12]), "+f"(d[13]), "+f"(d[14]), "+f"(d[15]), "+f"(d[16]), "+f"(d[17]), "+f"(d[18]), "+f"(d[19]), "+f"(d[20]), "+f"(d[21]), "+f"(d[22]), "+f"(d[23]), "+f"(d[24]), "+f"(d[25]), "+f"(d[26]), "+f"(d[27]), "+f"(d[28]), "+f"(d[29]), "+f"(d[30]), "+f"(d[31]), "+f"(d[32]), "+f"(d[33]), "+f"(d[34]), "+f"(d[35]), "+f"(d[36]), "+f"(d[37]), "+f"(d[38]), "+f"(d[39]), "+f"(d[40]), "+f"(d[41]), "+f"(d[42]), "+f"(d[43]), "+f"(d[44]), "+f"(d[45]), "+f"(d[46]), "+f"(d[47])
        : "r"(a[AOFF + 0][0]), "r"(a[AOFF + 0][1]), "r"(a[AOFF + 0][2]), "r"(a[AOFF + 0][3]), "r"(a[AOFF + 1][0]), "r"(a[AOFF + 1][1]), "r"(a[AOFF + 1][2]), "r"(a[AOFF + 1][3]), "r"(a[AOFF + 2][0]), "r"(a[AOFF + 2][1]), "r"(a[AOFF + 2][2]), "r"(a[AOFF + 2][3]), "r"(a[AOFF + 3][0]), "r"(a[AOFF + 3][1]), "r"(a[AOFF + 3][2]), "r"(a[AOFF + 3][3]), "r"(a[AOFF + 4][0]), "r"(a[AOFF + 4][1]), "r"(a[AOFF + 4][2]), "r"(a[AOFF + 4][3]), "r"(a[AOFF + 5][0]), "r"(a[AOFF + 5][1]), "r"(a[AOFF + 5][2]), "r"(a[AOFF + 5][3]), "l"(descB), "n"(BOFF >> 4));
}

template <int AOFF, int BOFF>
__device__ __forceinline__ void mma_qk0(float (&d)[28], uint64_t descA, uint64_t descB) {
    asm volatile(
        "{\n"
        ".reg .pred p0, p1;\n"
        ".reg .b64 ta, ta0, tb, tb0;\n"
        "setp.ne.b32 p0, 0, 0;\n"
        "setp.eq.b32 p1, 0, 0;\n"
        "add.s64 tb0, %30, %31;\n"
        "add.s64 ta0, %28, %29;\n"
        "add.s64 tb, tb0, 4;\n"
        "add.s64 ta, ta0, 0;\n"
        "wgmma.mma_async.sync.aligned.m64n56k16.f32.bf16.bf16 {%0, %1, %2, %3, %4, %5, %6, %7, %8, %9, %10, %11, %12, %13, %14, %15, %16, %17, %18, %19, %20, %21, %22, %23, %24, %25, %26, %27}, ta, tb, p1, 1, 1, 0, 0;\n"
        "add.s64 tb, tb0, 1572;\n"
        "add.s64 ta, ta0, 1568;\n"
        "wgmma.mma_async.sync.aligned.m64n56k16.f32.bf16.bf16 {%0, %1, %2, %3, %4, %5, %6, %7, %8, %9, %10, %11, %12, %13, %14, %15, %16, %17, %18, %19, %20, %21, %22, %23, %24, %25, %26, %27}, ta, tb, p1, 1, 1, 0, 0;\n"
        "add.s64 tb, tb0, 3140;\n"
        "add.s64 ta, ta0, 3136;\n"
        "wgmma.mma_async.sync.aligned.m64n56k16.f32.bf16.bf16 {%0, %1, %2, %3, %4, %5, %6, %7, %8, %9, %10, %11, %12, %13, %14, %15, %16, %17, %18, %19, %20, %21, %22, %23, %24, %25, %26, %27}, ta, tb, p1, 1, 1, 0, 0;\n"
        "}\n"
        : "+f"(d[0]), "+f"(d[1]), "+f"(d[2]), "+f"(d[3]), "+f"(d[4]), "+f"(d[5]), "+f"(d[6]), "+f"(d[7]), "+f"(d[8]), "+f"(d[9]), "+f"(d[10]), "+f"(d[11]), "+f"(d[12]), "+f"(d[13]), "+f"(d[14]), "+f"(d[15]), "+f"(d[16]), "+f"(d[17]), "+f"(d[18]), "+f"(d[19]), "+f"(d[20]), "+f"(d[21]), "+f"(d[22]), "+f"(d[23]), "+f"(d[24]), "+f"(d[25]), "+f"(d[26]), "+f"(d[27])
        : "l"(descA), "n"(AOFF >> 4), "l"(descB), "n"(BOFF >> 4));
}

template <int AOFF, int BOFF>
__device__ __forceinline__ void mma_qk1(float (&d)[28], uint64_t descA, uint64_t descB) {
    asm volatile(
        "{\n"
        ".reg .pred p0, p1;\n"
        ".reg .b64 ta, ta0, tb, tb0;\n"
        "setp.ne.b32 p0, 0, 0;\n"
        "setp.eq.b32 p1, 0, 0;\n"
        "add.s64 tb0, %30, %31;\n"
        "add.s64 ta0, %28, %29;\n"
        "add.s64 tb, tb0, 6;\n"
        "add.s64 ta, ta0, 2;\n"
        "wgmma.mma_async.sync.aligned.m64n56k16.f32.bf16.bf16 {%0, %1, %2, %3, %4, %5, %6, %7, %8, %9, %10, %11, %12, %13, %14, %15, %16, %17, %18, %19, %20, %21, %22, %23, %24, %25, %26, %27}, ta, tb, p1, 1, 1, 0, 0;\n"
        "add.s64 tb, tb0, 1574;\n"
        "add.s64 ta, ta0, 1570;\n"
        "wgmma.mma_async.sync.aligned.m64n56k16.f32.bf16.bf16 {%0, %1, %2, %3, %4, %5, %6, %7, %8, %9, %10, %11, %12, %13, %14, %15, %16, %17, %18, %19, %20, %21, %22, %23, %24, %25, %26, %27}, ta, tb, p1, 1, 1, 0, 0;\n"
        "add.s64 tb, tb0, 3142;\n"
        "add.s64 ta, ta0, 3138;\n"
        "wgmma.mma_async.sync.aligned.m64n56k16.f32.bf16.bf16 {%0, %1, %2, %3, %4, %5, %6, %7, %8, %9, %10, %11, %12, %13, %14, %15, %16, %17, %18, %19, %20, %21, %22, %23, %24, %25, %26, %27}, ta, tb, p1, 1, 1, 0, 0;\n"
        "}\n"
        : "+f"(d[0]), "+f"(d[1]), "+f"(d[2]), "+f"(d[3]), "+f"(d[4]), "+f"(d[5]), "+f"(d[6]), "+f"(d[7]), "+f"(d[8]), "+f"(d[9]), "+f"(d[10]), "+f"(d[11]), "+f"(d[12]), "+f"(d[13]), "+f"(d[14]), "+f"(d[15]), "+f"(d[16]), "+f"(d[17]), "+f"(d[18]), "+f"(d[19]), "+f"(d[20]), "+f"(d[21]), "+f"(d[22]), "+f"(d[23]), "+f"(d[24]), "+f"(d[25]), "+f"(d[26]), "+f"(d[27])
        : "l"(descA), "n"(AOFF >> 4), "l"(descB), "n"(BOFF >> 4));
}

template <int BOFF, int AOFF, int NA>
__device__ __forceinline__ void mma_pv(float (&d)[28], const uint32_t (&a)[NA][4], uint64_t descB) {
    asm volatile(
        "{\n"
        ".reg .pred p0, p1;\n"
        ".reg .b64 ta, ta0, tb, tb0;\n"
        "setp.ne.b32 p0, 0, 0;\n"
        "setp.eq.b32 p1, 0, 0;\n"
        "add.s64 tb0, %44, %45;\n"
        "add.s64 tb, tb0, 0;\n"
        "wgmma.mma_async.sync.aligned.m64n56k16.f32.bf16.bf16 {%0, %1, %2, %3, %4, %5, %6, %7, %8, %9, %10, %11, %12, %13, %14, %15, %16, %17, %18, %19, %20, %21, %22, %23, %24, %25, %26, %27}, {%28, %29, %30, %31}, tb, p0, 1, 1, 1;\n"
        "add.s64 tb, tb0, 16;\n"
        "wgmma.mma_async.sync.aligned.m64n56k16.f32.bf16.bf16 {%0, %1, %2, %3, %4, %5, %6, %7, %8, %9, %10, %11, %12, %13, %14, %15, %16, %17, %18, %19, %20, %21, %22, %23, %24, %25, %26, %27}, {%32, %33, %34, %35}, tb, p1, 1, 1, 1;\n"
        "add.s64 tb, tb0, 32;\n"
        "wgmma.mma_async.sync.aligned.m64n56k16.f32.bf16.bf16 {%0, %1, %2, %3, %4, %5, %6, %7, %8, %9, %10, %11, %12, %13, %14, %15, %16, %17, %18, %19, %20, %21, %22, %23, %24, %25, %26, %27}, {%36, %37, %38, %39}, tb, p1, 1, 1, 1;\n"
        "add.s64 tb, tb0, 48;\n"
        "wgmma.mma_async.sync.aligned.m64n56k16.f32.bf16.bf16 {%0, %1, %2, %3, %4, %5, %6, %7, %8, %9, %10, %11, %12, %13, %14, %15, %16, %17, %18, %19, %20, %21, %22, %23, %24, %25, %26, %27}, {%40, %41, %42, %43}, tb, p1, 1, 1, 1;\n"
        "}\n"
        : "=f"(d[0]), "=f"(d[1]), "=f"(d[2]), "=f"(d[3]), "=f"(d[4]), "=f"(d[5]), "=f"(d[6]), "=f"(d[7]), "=f"(d[8]), "=f"(d[9]), "=f"(d[10]), "=f"(d[11]), "=f"(d[12]), "=f"(d[13]), "=f"(d[14]), "=f"(d[15]), "=f"(d[16]), "=f"(d[17]), "=f"(d[18]), "=f"(d[19]), "=f"(d[20]), "=f"(d[21]), "=f"(d[22]), "=f"(d[23]), "=f"(d[24]), "=f"(d[25]), "=f"(d[26]), "=f"(d[27])
        : "r"(a[AOFF + 0][0]), "r"(a[AOFF + 0][1]), "r"(a[AOFF + 0][2]), "r"(a[AOFF + 0][3]), "r"(a[AOFF + 1][0]), "r"(a[AOFF + 1][1]), "r"(a[AOFF + 1][2]), "r"(a[AOFF + 1][3]), "r"(a[AOFF + 2][0]), "r"(a[AOFF + 2][1]), "r"(a[AOFF + 2][2]), "r"(a[AOFF + 2][3]), "r"(a[AOFF + 3][0]), "r"(a[AOFF + 3][1]), "r"(a[AOFF + 3][2]), "r"(a[AOFF + 3][3]), "l"(descB), "n"(BOFF >> 4));
}

template <int AOFF, int BOFF>
__device__ __forceinline__ void mma_proj(float (&d)[96], uint64_t descA, uint64_t descB) {
    asm volatile(
        "{\n"
        ".reg .pred p0, p1;\n"
        ".reg .b64 ta, ta0, tb, tb0;\n"
        "setp.ne.b32 p0, 0, 0;\n"
        "setp.eq.b32 p1, 0, 0;\n"
        "add.s64 tb0, %98, %99;\n"
        "add.s64 ta0, %96, %97;\n"
        "add.s64 tb, tb0, 0;\n"
        "add.s64 ta, ta0, 0;\n"
        "wgmma.mma_async.sync.aligned.m64n192k16.f32.bf16.bf16 {%0, %1, %2, %3, %4, %5, %6, %7, %8, %9, %10, %11, %12, %13, %14, %15, %16, %17, %18, %19, %20, %21, %22, %23, %24, %25, %26, %27, %28, %29, %30, %31, %32, %33, %34, %35, %36, %37, %38, %39, %40, %41, %42, %43, %44, %45, %46, %47, %48, %49, %50, %51, %52, %53, %54, %55, %56, %57, %58, %59, %60, %61, %62, %63, %64, %65, %66, %67, %68, %69, %70, %71, %72, %73, %74, %75, %76, %77, %78, %79, %80, %81, %82, %83, %84, %85, %86, %87, %88, %89, %90, %91, %92, %93, %94, %95}, ta, tb, p0, 1, 1, 0, 1;\n"
        "add.s64 tb, tb0, 64;\n"
        "add.s64 ta, ta0, 2;\n"
        "wgmma.mma_async.sync.aligned.m64n192k16.f32.bf16.bf16 {%0, %1, %2, %3, %4, %5, %6, %7, %8, %9, %10, %11, %12, %13, %14, %15, %16, %17, %18, %19, %20, %21, %22, %23, %24, %25, %26, %27, %28, %29, %30, %31, %32, %33, %34, %35, %36, %37, %38, %39, %40, %41, %42, %43, %44, %45, %46, %47, %48, %49, %50, %51, %52, %53, %54, %55, %56, %57, %58, %59, %60, %61, %62, %63, %64, %65, %66, %67, %68, %69, %70, %71, %72, %73, %74, %75, %76, %77, %78, %79, %80, %81, %82, %83, %84, %85, %86, %87, %88, %89, %90, %91, %92, %93, %94, %95}, ta, tb, p1, 1, 1, 0, 1;\n"
        "add.s64 tb, tb0, 128;\n"
        "add.s64 ta, ta0, 4;\n"
        "wgmma.mma_async.sync.aligned.m64n192k16.f32.bf16.bf16 {%0, %1, %2, %3, %4, %5, %6, %7, %8, %9, %10, %11, %12, %13, %14, %15, %16, %17, %18, %19, %20, %21, %22, %23, %24, %25, %26, %27, %28, %29, %30, %31, %32, %33, %34, %35, %36, %37, %38, %39, %40, %41, %42, %43, %44, %45, %46, %47, %48, %49, %50, %51, %52, %53, %54, %55, %56, %57, %58, %59, %60, %61, %62, %63, %64, %65, %66, %67, %68, %69, %70, %71, %72, %73, %74, %75, %76, %77, %78, %79, %80, %81, %82, %83, %84, %85, %86, %87, %88, %89, %90, %91, %92, %93, %94, %95}, ta, tb, p1, 1, 1, 0, 1;\n"
        "add.s64 tb, tb0, 192;\n"
        "add.s64 ta, ta0, 6;\n"
        "wgmma.mma_async.sync.aligned.m64n192k16.f32.bf16.bf16 {%0, %1, %2, %3, %4, %5, %6, %7, %8, %9, %10, %11, %12, %13, %14, %15, %16, %17, %18, %19, %20, %21, %22, %23, %24, %25, %26, %27, %28, %29, %30, %31, %32, %33, %34, %35, %36, %37, %38, %39, %40, %41, %42, %43, %44, %45, %46, %47, %48, %49, %50, %51, %52, %53, %54, %55, %56, %57, %58, %59, %60, %61, %62, %63, %64, %65, %66, %67, %68, %69, %70, %71, %72, %73, %74, %75, %76, %77, %78, %79, %80, %81, %82, %83, %84, %85, %86, %87, %88, %89, %90, %91, %92, %93, %94, %95}, ta, tb, p1, 1, 1, 0, 1;\n"
        "add.s64 tb, tb0, 256;\n"
        "add.s64 ta, ta0, 512;\n"
        "wgmma.mma_async.sync.aligned.m64n192k16.f32.bf16.bf16 {%0, %1, %2, %3, %4, %5, %6, %7, %8, %9, %10, %11, %12, %13, %14, %15, %16, %17, %18, %19, %20, %21, %22, %23, %24, %25, %26, %27, %28, %29, %30, %31, %32, %33, %34, %35, %36, %37, %38, %39, %40, %41, %42, %43, %44, %45, %46, %47, %48, %49, %50, %51, %52, %53, %54, %55, %56, %57, %58, %59, %60, %61, %62, %63, %64, %65, %66, %67, %68, %69, %70, %71, %72, %73, %74, %75, %76, %77, %78, %79, %80, %81, %82, %83, %84, %85, %86, %87, %88, %89, %90, %91, %92, %93, %94, %95}, ta, tb, p1, 1, 1, 0, 1;\n"
        "add.s64 tb, tb0, 320;\n"
        "add.s64 ta, ta0, 514;\n"
        "wgmma.mma_async.sync.aligned.m64n192k16.f32.bf16.bf16 {%0, %1, %2, %3, %4, %5, %6, %7, %8, %9, %10, %11, %12, %13, %14, %15, %16, %17, %18, %19, %20, %21, %22, %23, %24, %25, %26, %27, %28, %29, %30, %31, %32, %33, %34, %35, %36, %37, %38, %39, %40, %41, %42, %43, %44, %45, %46, %47, %48, %49, %50, %51, %52, %53, %54, %55, %56, %57, %58, %59, %60, %61, %62, %63, %64, %65, %66, %67, %68, %69, %70, %71, %72, %73, %74, %75, %76, %77, %78, %79, %80, %81, %82, %83, %84, %85, %86, %87, %88, %89, %90, %91, %92, %93, %94, %95}, ta, tb, p1, 1, 1, 0, 1;\n"
        "add.s64 tb, tb0, 384;\n"
        "add.s64 ta, ta0, 516;\n"
        "wgmma.mma_async.sync.aligned.m64n192k16.f32.bf16.bf16 {%0, %1, %2, %3, %4, %5, %6, %7, %8, %9, %10, %11, %12, %13, %14, %15, %16, %17, %18, %19, %20, %21, %22, %23, %24, %25, %26, %27, %28, %29, %30, %31, %32, %33, %34, %35, %36, %37, %38, %39, %40, %41, %42, %43, %44, %45, %46, %47, %48, %49, %50, %51, %52, %53, %54, %55, %56, %57, %58, %59, %60, %61, %62, %63, %64, %65, %66, %67, %68, %69, %70, %71, %72, %73, %74, %75, %76, %77, %78, %79, %80, %81, %82, %83, %84, %85, %86, %87, %88, %89, %90, %91, %92, %93, %94, %95}, ta, tb, p1, 1, 1, 0, 1;\n"
        "add.s64 tb, tb0, 448;\n"
        "add.s64 ta, ta0, 518;\n"
        "wgmma.mma_async.sync.aligned.m64n192k16.f32.bf16.bf16 {%0, %1, %2, %3, %4, %5, %6, %7, %8, %9, %10, %11, %12, %13, %14, %15, %16, %17, %18, %19, %20, %21, %22, %23, %24, %25, %26, %27, %28, %29, %30, %31, %32, %33, %34, %35, %36, %37, %38, %39, %40, %41, %42, %43, %44, %45, %46, %47, %48, %49, %50, %51, %52, %53, %54, %55, %56, %57, %58, %59, %60, %61, %62, %63, %64, %65, %66, %67, %68, %69, %70, %71, %72, %73, %74, %75, %76, %77, %78, %79, %80, %81, %82, %83, %84, %85, %86, %87, %88, %89, %90, %91, %92, %93, %94, %95}, ta, tb, p1, 1, 1, 0, 1;\n"
        "add.s64 tb, tb0, 512;\n"
        "add.s64 ta, ta0, 1024;\n"
        "wgmma.mma_async.sync.aligned.m64n192k16.f32.bf16.bf16 {%0, %1, %2, %3, %4, %5, %6, %7, %8, %9, %10, %11, %12, %13, %14, %15, %16, %17, %18, %19, %20, %21, %22, %23, %24, %25, %26, %27, %28, %29, %30, %31, %32, %33, %34, %35, %36, %37, %38, %39, %40, %41, %42, %43, %44, %45, %46, %47, %48, %49, %50, %51, %52, %53, %54, %55, %56, %57, %58, %59, %60, %61, %62, %63, %64, %65, %66, %67, %68, %69, %70, %71, %72, %73, %74, %75, %76, %77, %78, %79, %80, %81, %82, %83, %84, %85, %86, %87, %88, %89, %90, %91, %92, %93, %94, %95}, ta, tb, p1, 1, 1, 0, 1;\n"
        "add.s64 tb, tb0, 576;\n"
        "add.s64 ta, ta0, 1026;\n"
        "wgmma.mma_async.sync.aligned.m64n192k16.f32.bf16.bf16 {%0, %1, %2, %3, %4, %5, %6, %7, %8, %9, %10, %11, %12, %13, %14, %15, %16, %17, %18, %19, %20, %21, %22, %23, %24, %25, %26, %27, %28, %29, %30, %31, %32, %33, %34, %35, %36, %37, %38, %39, %40, %41, %42, %43, %44, %45, %46, %47, %48, %49, %50, %51, %52, %53, %54, %55, %56, %57, %58, %59, %60, %61, %62, %63, %64, %65, %66, %67, %68, %69, %70, %71, %72, %73, %74, %75, %76, %77, %78, %79, %80, %81, %82, %83, %84, %85, %86, %87, %88, %89, %90, %91, %92, %93, %94, %95}, ta, tb, p1, 1, 1, 0, 1;\n"
        "add.s64 tb, tb0, 640;\n"
        "add.s64 ta, ta0, 1028;\n"
        "wgmma.mma_async.sync.aligned.m64n192k16.f32.bf16.bf16 {%0, %1, %2, %3, %4, %5, %6, %7, %8, %9, %10, %11, %12, %13, %14, %15, %16, %17, %18, %19, %20, %21, %22, %23, %24, %25, %26, %27, %28, %29, %30, %31, %32, %33, %34, %35, %36, %37, %38, %39, %40, %41, %42, %43, %44, %45, %46, %47, %48, %49, %50, %51, %52, %53, %54, %55, %56, %57, %58, %59, %60, %61, %62, %63, %64, %65, %66, %67, %68, %69, %70, %71, %72, %73, %74, %75, %76, %77, %78, %79, %80, %81, %82, %83, %84, %85, %86, %87, %88, %89, %90, %91, %92, %93, %94, %95}, ta, tb, p1, 1, 1, 0, 1;\n"
        "add.s64 tb, tb0, 704;\n"
        "add.s64 ta, ta0, 1030;\n"
        "wgmma.mma_async.sync.aligned.m64n192k16.f32.bf16.bf16 {%0, %1, %2, %3, %4, %5, %6, %7, %8, %9, %10, %11, %12, %13, %14, %15, %16, %17, %18, %19, %20, %21, %22, %23, %24, %25, %26, %27, %28, %29, %30, %31, %32, %33, %34, %35, %36, %37, %38, %39, %40, %41, %42, %43, %44, %45, %46, %47, %48, %49, %50, %51, %52, %53, %54, %55, %56, %57, %58, %59, %60, %61, %62, %63, %64, %65, %66, %67, %68, %69, %70, %71, %72, %73, %74, %75, %76, %77, %78, %79, %80, %81, %82, %83, %84, %85, %86, %87, %88, %89, %90, %91, %92, %93, %94, %95}, ta, tb, p1, 1, 1, 0, 1;\n"
        "}\n"
        : "+f"(d[0]), "+f"(d[1]), "+f"(d[2]), "+f"(d[3]), "+f"(d[4]), "+f"(d[5]), "+f"(d[6]), "+f"(d[7]), "+f"(d[8]), "+f"(d[9]), "+f"(d[10]), "+f"(d[11]), "+f"(d[12]), "+f"(d[13]), "+f"(d[14]), "+f"(d[15]), "+f"(d[16]), "+f"(d[17]), "+f"(d[18]), "+f"(d[19]), "+f"(d[20]), "+f"(d[21]), "+f"(d[22]), "+f"(d[23]), "+f"(d[24]), "+f"(d[25]), "+f"(d[26]), "+f"(d[27]), "+f"(d[28]), "+f"(d[29]), "+f"(d[30]), "+f"(d[31]), "+f"(d[32]), "+f"(d[33]), "+f"(d[34]), "+f"(d[35]), "+f"(d[36]), "+f"(d[37]), "+f"(d[38]), "+f"(d[39]), "+f"(d[40]), "+f"(d[41]), "+f"(d[42]), "+f"(d[43]), "+f"(d[44]), "+f"(d[45]), "+f"(d[46]), "+f"(d[47]), "+f"(d[48]), "+f"(d[49]), "+f"(d[50]), "+f"(d[51]), "+f"(d[52]), "+f"(d[53]), "+f"(d[54]), "+f"(d[55]), "+f"(d[56]), "+f"(d[57]), "+f"(d[58]), "+f"(d[59]), "+f"(d[60]), "+f"(d[61]), "+f"(d[62]), "+f"(d[63]), "+f"(d[64]), "+f"(d[65]), "+f"(d[66]), "+f"(d[67]), "+f"(d[68]), "+f"(d[69]), "+f"(d[70]), "+f"(d[71]), "+f"(d[72]), "+f"(d[73]), "+f"(d[74]), "+f"(d[75]), "+f"(d[76]), "+f"(d[77]), "+f"(d[78]), "+f"(d[79]), "+f"(d[80]), "+f"(d[81]), "+f"(d[82]), "+f"(d[83]), "+f"(d[84]), "+f"(d[85]), "+f"(d[86]), "+f"(d[87]), "+f"(d[88]), "+f"(d[89]), "+f"(d[90]), "+f"(d[91]), "+f"(d[92]), "+f"(d[93]), "+f"(d[94]), "+f"(d[95])
        : "l"(descA), "n"(AOFF >> 4), "l"(descB), "n"(BOFF >> 4));
}

struct Params {
    const __nv_bfloat16* x;
    const __nv_bfloat16* wqkv;
    const __nv_bfloat16* wo;
    const __nv_bfloat16* logit_scale;
    const __nv_bfloat16* cpb_w1;
    const __nv_bfloat16* cpb_w2;
    const __nv_bfloat16* rel_coords;
    const int*           rel_idx;
    const __nv_bfloat16* mask;
    __nv_bfloat16*       out;
    unsigned long long   z1;
    int                  npair;
    uint32_t             need;
    int                  nq, nr;
    int                  t1;
};

__device__ __forceinline__ void finish(uint32_t total) {
    __threadfence();
    if (atomicAdd(&g_done, 1u) == total - 1) {
        for (int i = 0; i < NWS; i++) g_cnt[i] = 0;
        g_done = 0;
    }
}

__global__ void __launch_bounds__(NTHREADS, 1)
swin_window_attn_kernel(const Params P, const __grid_constant__ CUtensorMap xmap, const __grid_constant__ CUtensorMap xmap4,
                        const __grid_constant__ CUtensorMap xmap3,
                        const __grid_constant__ CUtensorMap omap, const __grid_constant__ CUtensorMap wmap,
                        const __grid_constant__ CUtensorMap smap, const __grid_constant__ CUtensorMap omapb,
                        const __grid_constant__ CUtensorMap xmapa, const __grid_constant__ CUtensorMap xmapb,
                        const __grid_constant__ CUtensorMap smap3, const __grid_constant__ CUtensorMap wraw) {
    extern __shared__ __align__(1024) uint8_t smem[];
    constexpr uint32_t sbase = 1024;
    if (smem_u32(smem) != sbase) return;
    const int tid = threadIdx.x;
    const int wg = __shfl_sync(0xffffffffu, tid >> 7, 0);
    const int warp = __shfl_sync(0xffffffffu, (tid >> 5) & 3, 0);
    const int lane = tid & 31;
    const int g = lane >> 2, c = lane & 3;

    TR(26, wg);
    const bool attn = (int)blockIdx.x < 2 * P.npair;
    const int pair = blockIdx.x >> 1, half = blockIdx.x & 1;
    const int nwin = P.nq + (pair < P.nr ? 1 : 0);
    const int ntiles = (nwin * TOK + 63) >> 6;
    const uint32_t bars = sbase + SM_BAR;
    const int t0 = min(warp * 16 + g, TOK - 1), t1 = min(warp * 16 + g + 8, TOK - 1);
    int ridx[26];
    uint32_t rc, w2[16];
    uint4 w1[4];
    if (attn && (wg == 1 || wg == 2)) {
        rc = reinterpret_cast<const uint32_t*>(P.rel_coords)[min(tid - 128, 168)];
#pragma unroll
        for (int i = 0; i < 4; i++) w1[i] = reinterpret_cast<const uint4*>(P.cpb_w1)[i];
#pragma unroll
        for (int u = 0; u < 16; u++) w2[u] = reinterpret_cast<const uint32_t*>(P.cpb_w2)[2 * u + half];
#pragma unroll
        for (int rh = 0; rh < 2; rh++) {
            const int* ri = P.rel_idx + (rh ? t1 : t0) * TOK;
#pragma unroll
            for (int j = 0; j < 12; j++) ridx[13 * rh + j] = ri[8 * (j >> 1) + 2 * c + (j & 1)];
            ridx[13 * rh + 12] = ri[48];
        }
    }
    {
        if (tid == 416) {
            const CUtensorMap* maps[4] = {attn ? &smap : &omap, &smap3, &xmapa, &xmapb};
#pragma unroll
            for (int i = 0; i < 4; i++) asm volatile("prefetch.tensormap [%0];\n" :: "l"(reinterpret_cast<uint64_t>(maps[i])) : "memory");
        }
        if (tid == 384) {
            for (int b = 0; b < 4; b++) {
                mbar_init(bars + B_XFULL + b * 8, 2);
                mbar_init(bars + B_QKRAW + b * 8, 4);
                mbar_init(bars + B_VRAW + b * 8, 4);
                mbar_init(bars + B_VFREE + b * 8, 2);
                mbar_init(bars + B_QKFREE + b * 8, 4);
                mbar_init(bars + B_ODONE + b * 8, 4);
            }
            mbar_init(bars + B_MFULL, 1);
            mbar_init(bars + B_MFULL + 8, 1);
            mbar_init(bars + B_MCONS, 4);
            mbar_init(bars + B_WFULL, 2);
            mbar_init(bars + B_WRAW, 1);
            for (int b = 0; b < 4; b++) mbar_init(bars + B_STORED + b * 8, 1);
            for (int b = 0; b < 6; b++) {
                mbar_init(sbase + SM_PBAR + b * 8, 1);
                mbar_init(sbase + SM_PBAR + 48 + b * 8, PSTORE ? 1 : 4);
                mbar_init(sbase + SM_PBAR + 104 + b * 8, 4);
            }
            mbar_init(sbase + SM_PBAR + 96, 13);
            asm volatile("fence.mbarrier_init.release.cluster;\n" ::: "memory");
        }
        if (wg == 3) {
            if (attn) *reinterpret_cast<uint4*>(smem + SM_V + warp * V_STRIDE + (lane < 16 ? lane * 16 : V_STRIDE - 64 + (lane & 3) * 16)) = make_uint4(0, 0, 0, 0);
            fence_async_smem();
        }
        __syncthreads();
        TR(26, 4 + wg);
            if (attn && tid == 0) {
                mbar_arrive_expect_tx(bars + B_WRAW, 2 * 192 * O_PITCH);
#pragma unroll
                for (int i = 0; i < 4; i++) {
                    const int q = (i + pair) & 3;
                    tma_3d(sbase + q * 96 * O_PITCH, &wraw, bars + B_WRAW, 0, 2 * (q >> 1) + half, (q & 1) * 96);
                }
                int wh = 0, ww = pair;
#pragma unroll
                for (int j = 0; j < NEARLY; j++) {
                    if (ww < NWS - 1) {
                        const uint32_t bar = bars + B_XFULL + (j ? j - 1 : 0) * 8;
                        if (j >= 2) mbar_arrive(bar);
                        mbar_arrive_expect_tx(bar, 3 * XCH);
#pragma unroll
                        for (int ch = 0; ch < 3; ch++)
                            tma_3d(sbase + SM_QK + j * XCH + ch * QK_CHUNK, &xmap, bar, ch * 64, 7 * ww + 3, 7 * wh + 3);
                    }
                    ww += P.npair; if (ww >= NWS) { ww -= NWS; wh++; }
                    if (j == 1) {
                        mbar_arrive_expect_tx(bars + B_MFULL, 4816);
                        asm volatile("cp.async.bulk.shared::cluster.global.mbarrier::complete_tx::bytes [%0], [%1], 4816, [%2];\n"
                                     :: "r"(sbase + SM_MASK), "l"(reinterpret_cast<const char*>(P.mask) + (((uint32_t)pair * 4802u) & ~15u)),
                                        "r"(bars + B_MFULL) : "memory");
                        mbar_arrive_expect_tx(bars + B_WFULL, 5 * W_ATOM);
#pragma unroll
                        for (int a = 1; a < 6; a++)
                            tma_2d(sbase + SM_WV + a * W_ATOM, &wmap, bars + B_WFULL, 384 + half * 96 + a * 16, 0);
                    }
                }
            }
        __syncwarp();
        TR(26, 13);
    }

    auto permute_w = [&]() {
        uint4 w[3][4];
        TR(26, 16 + wg);
        mbar_wait(bars + B_WRAW, 0);
        TR(26, 20 + wg);
#pragma unroll
        for (int it = 0; it < 3; it++) {
            const int o = ((tid >> 5) * 3 + it) * 4 + (lane >> 3);
            const uint8_t* src = smem + ((o / 6) * 8 + (lane & 7)) * O_PITCH + (o % 6) * 16;
#pragma unroll
            for (int m = 0; m < 4; m++) w[it][m] = *reinterpret_cast<const uint4*>(src + (m >> 1) * 192 * O_PITCH + (m & 1) * 96);
        }
        asm volatile("bar.sync 2, 384;\n" ::: "memory");
        if (tid == 0) {
            fence_async_smem();
            TR(26, 24);
            mbar_arrive_expect_tx(bars + B_WFULL, W_ATOM);
            tma_2d(sbase + SM_WV, &wmap, bars + B_WFULL, 384 + half * 96, 0);
        }
#pragma unroll
        for (int it = 0; it < 3; it++) {
            const int o = ((tid >> 5) * 3 + it) * 4 + (lane >> 3);
            const uint32_t d = sbase + (o % 6) * 2 * W_ATOM + ((o / 6) * 8 + (lane & 7)) * 32 + ((lane >> 2) & 1) * 16;
            sts128(d, w[it][0].x, w[it][1].x, w[it][2].x, w[it][3].x);
            sts128(d ^ 16, w[it][0].y, w[it][1].y, w[it][2].y, w[it][3].y);
            sts128(d + W_ATOM, w[it][0].z, w[it][1].z, w[it][2].z, w[it][3].z);
            sts128((d ^ 16) + W_ATOM, w[it][0].w, w[it][1].w, w[it][2].w, w[it][3].w);
        }
    };
    static_assert(2 * 192 * O_PITCH <= 13 * W_ATOM, "raw weights");
    const uint32_t nfinish = gridDim.x + 2 * P.npair;
#define PROJ_SCHEDULE                                                                                   \
    int bid = blockIdx.x;                                                                               \
    asm volatile("" : "+r"(bid));                      \
    const bool at = bid < 2 * P.npair;                                                                  \
    const int tile0 = at ? P.t1 + bid : bid - 2 * P.npair;                                              \
    const int tstep = at ? 2 * P.npair : (int)gridDim.x - 2 * P.npair;                                  \
    const int tend = at ? TILES : P.t1;
    if (wg == 3) {
        asm volatile("setmaxnreg.dec.sync.aligned.u32 %0;\n" :: "n"(REG_H));
        if (!elect_one()) return;
        if (warp == 0) {
          if (attn) {
            const int kmax = (64 * ntiles + 63) / TOK;
            int wh = 0, ww = pair;
            int ph2 = (pair + PF_DIST * P.npair) / NWS, pw2 = pair + PF_DIST * P.npair - ph2 * NWS;
#pragma unroll 1
            for (int k = -4; k + 4 <= kmax; k++) {
                const int row0 = (k + 4) * TOK;
                const uint32_t dst = sbase + SM_QK + (k & 3) * XCH, bar = bars + B_XFULL + ((row0 >> 6) & 3) * 8;
                const bool alone = (row0 & 63) >= 64 - TOK && (row0 & 63) < TOK;
                const int x0 = 7 * ww + 3, y0 = 7 * wh + 3;
                const bool done = k < NEARLY - 4 && ww < NWS - 1;
                mbar_wait(bars + B_QKFREE + (k & 3) * 8, (k >> 2) & 1);
                if (alone && !done) mbar_arrive(bar);
                if (k + 4 >= nwin) {
                    mbar_arrive(bar);
                    continue;
                }
                TR(20, k + 4);
                const bool inner = wh < NWS - 1 && ww < NWS - 1;
                if (done) {
                } else if (XSPLIT && inner && (row0 & 63) >= 64 - 21) {
                    const uint32_t bar2 = bars + B_XFULL + (((row0 >> 6) + 1) & 3) * 8;
                    mbar_arrive_expect_tx(bar, 3 * 21 * 128);
#pragma unroll
                    for (int ch = 0; ch < 3; ch++) tma_3d(dst + ch * QK_CHUNK, &xmapa, bar, ch * 64, x0, y0);
                    asm volatile("mbarrier.expect_tx.relaxed.cta.shared::cta.b64 [%0], %1;\n" :: "r"(bar2), "r"(3 * 28 * 128) : "memory");
#pragma unroll
                    for (int ch = 0; ch < 3; ch++) tma_3d(dst + ch * QK_CHUNK + 21 * 128, &xmapb, bar2, ch * 64, x0, y0 + 3);
                } else if (inner) {
                    mbar_arrive_expect_tx(bar, 3 * XCH);
#pragma unroll
                    for (int ch = 0; ch < 3; ch++) tma_3d(dst + ch * QK_CHUNK, &xmap, bar, ch * 64, x0, y0);
                } else if (ww < NWS - 1) {
                    mbar_arrive_expect_tx(bar, 3 * XCH);
#pragma unroll
                    for (int ch = 0; ch < 3; ch++) {
                        tma_3d(dst + ch * QK_CHUNK, &xmapb, bar, ch * 64, x0, y0);
                        tma_3d(dst + ch * QK_CHUNK + 28 * 128, &xmapa, bar, ch * 64, x0, 0);
                    }
                } else {
                    mbar_arrive_expect_tx(bar, 3 * XCH);
                    const int x1 = (ww == NWS - 1) ? 0 : x0 + 4;
#pragma unroll 1
                    for (int i = 0; i < 7; i++) {
                        const int y = (y0 + i >= IMG) ? y0 + i - IMG : y0 + i;
#pragma unroll
                        for (int ch = 0; ch < 3; ch++) {
                            tma_3d(dst + ch * QK_CHUNK + i * 896, &xmap4, bar, ch * 64, x0, y);
                            tma_3d(dst + ch * QK_CHUNK + i * 896 + 512, &xmap3, bar, ch * 64, x1, y);
                        }
                    }
                }
                if (NOPF) {
                } else if (half == 0) {
                    if (ph2 < NWS) {
#pragma unroll
                        for (int ch = 0; ch < 3; ch++)
                            asm volatile("cp.async.bulk.prefetch.tensor.3d.L2.global.tile [%0, {%1, %2, %3}];\n"
                                         :: "l"(reinterpret_cast<uint64_t>(&xmap)), "r"(ch * 64), "r"(7 * pw2 + 3), "r"(7 * ph2 + 3)
                                         : "memory");
                    }
                } else if (ph2 < NWS) {
                    asm volatile("cp.async.bulk.prefetch.L2.global [%0], %1;\n"
                                 :: "l"(reinterpret_cast<const char*>(P.mask) + (((uint32_t)(ph2 * NWS + pw2) * 4802u) & ~15u)),
                                    "r"(4800) : "memory");
                }
                ww += P.npair; if (ww >= NWS) { ww -= NWS; wh++; }
                pw2 += P.npair; if (pw2 >= NWS) { pw2 -= NWS; ph2++; }
            }
            mbar_wait(sbase + SM_PBAR + 96, 0);
            fence_async_smem();
          }
            PROJ_SCHEDULE
            int st = 0, ready = -1;
            uint32_t ph = 1;
#pragma unroll 1
            for (int t = tile0; t < tend; t += tstep) {
                const int p0 = (t < TILES_A) ? SEG_B + 64 * t : 64 * (t - TILES_A);
                const int w1 = (t < TILES_A) ? min((64 * t + 63) / (7 * IMG), NWS - 1) : NWS - 1;
                if (ready < w1) {
                    ready = max(ready, w1 - 2);
#pragma unroll 1
                    while (ready < w1) {
                        ready++;
#pragma unroll 1
                        for (uint32_t n = 0; n < (1u << 22); n++) {
                            uint32_t a;
                            asm volatile("ld.acquire.gpu.global.u32 %0, [%1];\n" : "=r"(a) : "l"(g_cnt + ready) : "memory");
                            if (a >= P.need) break;
                            __nanosleep(64);
                        }
                    }
                    asm volatile("fence.proxy.async.global;\n" ::: "memory");
                }
                mbar_wait(sbase + SM_PBAR + 48 + st * 8, ph);
                mbar_arrive_expect_tx(sbase + SM_PBAR + st * 8, STAGE_BYTES);
#pragma unroll
                for (int ch = 0; ch < 3; ch++)
                    tma_2d(sbase + SM_STAGE + st * STAGE_BYTES + ch * 8192, &omap, sbase + SM_PBAR + st * 8, ch * 64, p0);
                if (++st == 6) { st = 0; ph ^= 1; }
            }
            finish(nfinish);
        } else if (!attn) {
        } else if (warp == 1) {
          {
            const uint16_t mlast = reinterpret_cast<const uint16_t*>(P.mask)[NWINDOWS * TOK * TOK - 1];
            auto load_mask = [&](int k) {
                const int win = pair + k * P.npair;
                uint32_t bytes = 4816;
                if (win == NWINDOWS - 1) {
                    bytes = 4800;
                    asm volatile("st.shared.u16 [%0], %1;\n" :: "r"(sbase + SM_MASK + 4800), "h"(mlast) : "memory");
                }
                TR(25, k);
                mbar_arrive_expect_tx(bars + B_MFULL + (k & 1) * 8, bytes);
                asm volatile("cp.async.bulk.shared::cluster.global.mbarrier::complete_tx::bytes [%0], [%1], %2, [%3];\n"
                             :: "r"(sbase + SM_MASK),
                                "l"(reinterpret_cast<const char*>(P.mask) + (((uint32_t)win * 4802u) & ~15u)),
                                "r"(bytes), "r"(bars + B_MFULL + (k & 1) * 8) : "memory");
            };
#pragma unroll 1
            for (int k = 1; k < nwin; k++) {
                mbar_wait(bars + B_MCONS, (k + 1) & 1);
                fence_async_smem();
                load_mask(k);
            }
          }
        } else if (warp == 2) {
            int wh = 0, ww = pair;
#pragma unroll 1
            for (int k = 0; k < nwin; k++) {
                mbar_wait(bars + B_STORED + (k & 1) * 8, (k >> 1) & 1);
                mbar_arrive(bars + B_PUBD + (k & 1) * 8);
                asm volatile("red.release.gpu.global.add.u32 [%0], 1;\n" :: "l"(g_cnt + wh) : "memory");
                TR(24, k);
                ww += P.npair; if (ww >= NWS) { ww -= NWS; wh++; }
            }
            finish(nfinish);
        } else {
            for (int t = 0; t < 3; t++) mbar_arrive_n(bars + B_VFREE + t * 8, 2);
            int wh = 0, ww = pair;
#pragma unroll 1
            for (int k = 0; k < nwin; k++) {
                const uint32_t src = sbase + SM_V + (k & 3) * V_STRIDE;
                const int x0 = 7 * ww + 3, y0 = 7 * wh + 3;
                mbar_wait(bars + B_ODONE + (k & 3) * 8, (k >> 2) & 1);
                fence_async_smem();
                TR(22, k);
                tma_store_4d(&smap, src, 0, half, x0, y0);
                tma_store_4d(&smap3, src + 28 * O_PITCH + 64, 0, half, x0, wh == NWS - 1 ? 0 : y0 + 4);
                if (ww == NWS - 1) {
#pragma unroll 1
                    for (int i = 0; i < 7; i++) {
                        char* const d = reinterpret_cast<char*>(P.out) + (uint32_t)((y0 + i >= IMG ? y0 + i - IMG : y0 + i) * IMG) * 384u + half * 192;
#pragma unroll
                        for (int j = 0; j < 3; j++)
                            asm volatile("cp.async.bulk.global.shared::cta.bulk_group [%0], [%1], 192;\n"
                                         :: "l"(d + j * 384), "r"(src + (7 * i + 4 + j) * O_PITCH + (i >= 4 ? 64 : 0)) : "memory");
                    }
                }
                asm volatile("cp.async.bulk.commit_group;\n" ::: "memory");
                asm volatile("cp.async.bulk.wait_group.read 0;\n" ::: "memory");
                {
                    const int row0 = (k + 4) * TOK;
                    mbar_arrive_n(bars + B_VFREE + ((row0 >> 6) & 3) * 8, ((row0 & 63) >= 64 - TOK && (row0 & 63) < TOK) ? 2 : 1);
                }
                TR(23, k);
                asm volatile("cp.async.bulk.wait_group 0;\n" ::: "memory");
                asm volatile("fence.proxy.async.global;\n" ::: "memory");
                mbar_wait(bars + B_PUBD + (k & 1) * 8, ((k >> 1) + 1) & 1);
                mbar_arrive(bars + B_STORED + (k & 1) * 8);
                ww += P.npair; if (ww >= NWS) { ww -= NWS; wh++; }
            }
            mbar_arrive(sbase + SM_PBAR + 96);
        }
        if (PSTORE && warp == 1) {
            PROJ_SCHEDULE
            int st = 0, prev = -1;
            uint32_t ph = 0;
#pragma unroll 1
            for (int t = tile0; t < tend; t += tstep) {
                const int p0 = (t < TILES_A) ? SEG_B + 64 * t : 64 * (t - TILES_A);
                mbar_wait(sbase + SM_PBAR + 104 + st * 8, ph);
                fence_async_smem();
#pragma unroll
                for (int ch = 0; ch < 3; ch++)
                    asm volatile("cp.async.bulk.tensor.2d.global.shared::cta.tile.bulk_group [%0, {%2, %3}], [%1];\n"
                                 :: "l"(reinterpret_cast<uint64_t>(t < TILES_A ? &omap : &omapb)),
                                    "r"(sbase + SM_STAGE + st * STAGE_BYTES + ch * 8192), "r"(ch * 64), "r"(p0) : "memory");
                asm volatile("cp.async.bulk.commit_group;\n" ::: "memory");
                if (prev >= 0) {
                    asm volatile("cp.async.bulk.wait_group.read 1;\n" ::: "memory");
                    mbar_arrive(sbase + SM_PBAR + 48 + prev * 8);
                }
                prev = st;
                if (++st == 6) { st = 0; ph ^= 1; }
            }
            asm volatile("cp.async.bulk.wait_group 0;\n" ::: "memory");
            TR(30, 0);
        }
        return;
    }
    if (!attn) {
        asm volatile("setmaxnreg.inc.sync.aligned.u32 160;\n");
    } else if (wg == 0) {
        asm volatile("setmaxnreg.inc.sync.aligned.u32 %0;\n" :: "n"(REG_G));
        float qs = 1.f;
        if (c < 2) qs = round_bf16(expf(round_bf16(fminf(fmaxf(__bfloat162float(P.logit_scale[2 * half + c]), -100.f), 4.6052f))));
        uint32_t xa[12][4];
        float accA[48], accB[48];
#pragma unroll
        for (int i = 0; i < 48; i++) { accA[i] = 0.f; accB[i] = 0.f; }
        uint32_t rho = warp * 16 + (lane & 15), rq = warp * 16 + g;
        uint32_t hi = lane >> 4, lane0 = lane == 0, c2 = 2 * c;
        asm volatile("" : "+r"(hi), "+r"(lane0), "+r"(c2));
        auto row_addr = [&](uint32_t (&ax)[4], uint32_t r) {
            ax[0] = sbase + SM_QK + r * 128 + (((r & 7) ^ hi) << 4);
#pragma unroll
            for (int i = 1; i < 4; i++) ax[i] = ax[0] ^ (32 * i);
        };
#define XADDR(ax, s) ((ax)[((s) & 3) ^ (((s) >> 1) & 2)] + ((s) >> 2) * QK_CHUNK)
        uint64_t descW = make_desc(sbase, W_ATOM, 256, 3);
        const uint32_t zero = (uint32_t)P.z1;
        const uint32_t vbase = sbase + SM_V + (lane >> 4) * GRP;
        uint32_t ones = 0x3F803F80u | zero, ones2 = ones | (zero >> 1);
        asm volatile("" : "+r"(ones), "+r"(ones2));
        permute_w();
        TR(26, 10);
        {
            uint32_t ax[4];
            row_addr(ax, rho);
            mbar_wait(bars + B_XFULL, 0);
#pragma unroll
            for (int s = 0; s < 12; s++) ldsm_x4(xa[s], XADDR(ax, s));
        }
        TR(26, 8);
        asm volatile("bar.sync 7, 384;\n" ::: "memory");
        fence_async_smem();
        TR(26, 9);
        wgmma_fence();
        mma_qkv_a<SM_WA, 0>(accA, xa, descW);
        mma_qkv_b<SM_WA, 6>(accA, xa, descW);
        wgmma_commit();
        mma_qkv_a<SM_WB, 0>(accB, xa, descW);
        wgmma_commit();
        TR(26, 11);
        mbar_wait(bars + B_WFULL, 0);
        TR(26, 12);
        for (int t = 0; t < ntiles; t++) {
            descW += P.z1;
            float ss[4];
            uint32_t pk[2][24];
            wgmma_wait<1>();
            reg_fence(accA);
            TR(0, t);
#pragma unroll
            for (int i = 0; i < 4; i++) ss[i] = accA[i] * accA[i];
#pragma unroll
            for (int i = 4; i < 48; i++) ss[i & 3] = fmaf(accA[i], accA[i], ss[i & 3]);
            mma_qkv_b<SM_WB, 6>(accB, xa, descW);
            wgmma_commit();
            sched_fence(zero, __float_as_uint(ss[0]), __float_as_uint(ss[1]), __float_as_uint(ss[2]), __float_as_uint(ss[3]));
#pragma unroll
            for (int j = 0; j < 12; j++) {
                pk[0][j] = pack_bf16(accA[4 * j], accA[4 * j + 1]);
                pk[1][j] = pack_bf16(accA[4 * j + 2], accA[4 * j + 3]);
                asm volatile("" : "+r"(pk[0][j]), "+r"(pk[1][j]));
            }
            wgmma_fence();
            mma_qkv_a<SM_WV, 0>(accA, xa, descW);
            wgmma_commit();
            uint32_t av = vbase + rho * 16 + ((rho * 1338) >> 16) * (V_STRIDE - GRP);
            uint32_t aq[2];
            aq[0] = sbase + SM_QK + rq * 128 + (((rq & 7) ^ c2) << 4);
            aq[1] = aq[0] + 1024;
            if (rq >= 4 * TOK - 8) aq[1] = (aq[1] - QK_CHUNK) ^ 64;
            rho += 64;
            if (rho >= 4 * TOK) rho -= 4 * TOK;
            rq += 64;
            if (rq >= 4 * TOK) rq -= 4 * TOK;
            uint32_t an[4];
            row_addr(an, rho);
            const uint32_t bt = bars + (t & 3) * 8, pt = (t >> 2) & 1, bn = bars + ((t + 1) & 3) * 8, pn = ((t + 1) >> 2) & 1;
            const uint32_t xok = mbar_test(bn + B_XFULL, pn);
            wgmma_wait<1>();
            reg_fence(accB);
#pragma unroll
            for (int i = 0; i < 48; i++) ss[i & 3] = fmaf(accB[i], accB[i], ss[i & 3]);
            ss[0] += ss[1]; ss[2] += ss[3];
            mma_qkv_b<SM_WV, 6>(accA, xa, descW);
            wgmma_commit();
            sched_fence(zero, __float_as_uint(ss[0]), __float_as_uint(ss[2]), av, aq[0], aq[1], an[0], an[1], an[2], an[3], rho, rq);
            const float f0 = rsqrt_ftz(ss[0] + 1e-12f) * qs, f1 = rsqrt_ftz(ss[2] + 1e-12f) * qs;
            const uint32_t f2[2] = {pack_bf16(f0, f0), pack_bf16(f1, f1)};
#pragma unroll
            for (int j = 0; j < 12; j++) {
                pk[0][12 + j] = pack_bf16(accB[4 * j], accB[4 * j + 1]);
                pk[1][12 + j] = pack_bf16(accB[4 * j + 2], accB[4 * j + 3]);
            }
            auto qk_store = [&](int u0, int u1) {
#pragma unroll
                for (int u = u0; u < u1; u++)
#pragma unroll
                    for (int r = 0; r < 2; r++)
                        sts128((aq[r] ^ ((u & 1) * 16 + (u & 2) * 32)) + (u >> 1) * QK_CHUNK,
                               hmul2_bf16(pk[r][4 * u], f2[r]), hmul2_bf16(pk[r][4 * u + 1], f2[r]),
                               hmul2_bf16(pk[r][4 * u + 2], f2[r]), hmul2_bf16(pk[r][4 * u + 3], f2[r]));
            };
            qk_store(0, QSPLIT);
            TR(1, t);
            mbar_wait_unless(xok, bn + B_XFULL, pn);
            TR(2, t);
            wgmma_wait<0>();
            reg_fence(accA);
#pragma unroll
            for (int s = 0; s < 12; s++) ldsm_x4(xa[s], XADDR(an, s));
            const uint32_t vok = mbar_test(bt + B_VFREE, pt);
            qk_store(QSPLIT, 6);
            __syncwarp();
            mbar_arrive_if(bt + B_QKRAW, lane0);
            TR(3, t);
            uint32_t vp[24];
#pragma unroll
            for (int j = 0; j < 24; j++) vp[j] = pack_bf16(accA[2 * j], accA[2 * j + 1]);
            reg_fence(vp);
            wgmma_fence();
            mma_qkv_a<SM_WA, 0>(accA, xa, descW);
            mma_qkv_b<SM_WA, 6>(accA, xa, descW);
            wgmma_commit();
            mbar_wait_unless(vok, bt + B_VFREE, pt);
            if (t == 2) asm volatile("bar.sync 3, 384;\n" ::: "memory");
#pragma unroll
            for (int p = 0; p < 6; p++)
                stsm_x4(av + (p < 3 ? 2 * p : 2 * p + 1) * GRP, vp[4 * p], vp[4 * p + 1], vp[4 * p + 2], vp[4 * p + 3]);
            stsm_x2(av + 6 * GRP, ones, ones2);
            __syncwarp();
            mbar_arrive_if(bt + B_VRAW, lane0);
            TR(4, t);
            wgmma_fence();
            mma_qkv_a<SM_WB, 0>(accB, xa, descW);
            wgmma_commit();
        }
        wgmma_wait<0>();
        reg_fence(accA);
        reg_fence(accB);
        wg_bar(2);
        asm volatile("setmaxnreg.dec.sync.aligned.u32 160;\n");
    } else {
        if (REG_A > 128) asm volatile("setmaxnreg.inc.sync.aligned.u32 %0;\n" :: "n"(REG_A));
        {
            const float c0 = bf16lo(rc), c1 = bf16hi(rc);
            float a0 = 0.f, a1 = 0.f;
#pragma unroll
            for (int u = 0; u < 16; u++) {
                const uint32_t p = reinterpret_cast<const uint32_t*>(w1)[u >> 1], q = reinterpret_cast<const uint32_t*>(w1)[8 + (u >> 1)];
                float h = round_bf16(c0 * ((u & 1) ? bf16hi(p) : bf16lo(p)) + c1 * ((u & 1) ? bf16hi(q) : bf16lo(q)));
                h = fmaxf(h, 0.f);
                a0 += h * bf16lo(w2[u]);
                a1 += h * bf16hi(w2[u]);
            }
            const float s0 = round_bf16(__fdividef(1.f, 1.f + expf(-round_bf16(a0))));
            const float s1 = round_bf16(__fdividef(1.f, 1.f + expf(-round_bf16(a1))));
            if (tid - 128 < 169) sts32(sbase + SM_TAB + (tid - 128) * 4, pack_bf16(16.f * s0, 16.f * s1));
        }
        permute_w();
        asm volatile("bar.arrive 7, 384;\n" ::: "memory");
        asm volatile("bar.sync 1, 256;\n" ::: "memory");
        uint32_t bias[28];
        {
            const uint32_t* tab = reinterpret_cast<const uint32_t*>(smem + SM_TAB);
#pragma unroll
            for (int rh = 0; rh < 2; rh++) {
#pragma unroll
                for (int j = 0; j < 6; j++) {
                    const uint32_t lo = tab[min(max(ridx[13 * rh + 2 * j], 0), 168)];
                    const uint32_t hi = tab[min(max(ridx[13 * rh + 2 * j + 1], 0), 168)];
                    bias[2 * j + rh]      = prmt(lo, hi, 0x5410);
                    bias[14 + 2 * j + rh] = prmt(lo, hi, 0x7632);
                }
                const uint32_t l = (c == 0) ? tab[min(max(ridx[13 * rh + 12], 0), 168)] : 0xFF80FF80u;
                bias[12 + rh] = (l & 0xFFFFu) | 0xFF800000u;
                bias[26 + rh] = (l >> 16) | 0xFF800000u;
            }
        }
        reg_fence(bias);
        asm volatile("bar.arrive 3, 384;\n" ::: "memory");
        const bool ov = warp * 16 + (lane & 15) < TOK;
        const int orow = warp * 16 + (lane & 15);
        const uint32_t orel = sbase + (ov ? SM_V + orow * O_PITCH + (orow >= 28 ? 64 : 0) : SM_DUMP + (lane & 7) * 16) + (lane >> 4) * 16;
        const uint32_t omul = ov ? V_STRIDE : 0;
        uint32_t mdelta = 2 * (pair + (wg - 1) * P.npair);
        const uint64_t descK0 = make_desc(sbase + SM_QK, 16, 1024, 1);
        const uint64_t descV0 = make_desc(sbase + SM_V, 128, GRP, 0);
        const uint32_t mrel = (sbase + SM_MASK + t0 * 98 + c * 4 + (mdelta & 2)) & ~3u;
        const uint32_t msel = ((t0 * 98 + mdelta) & 2) ? 0x5432u : 0x3210u;
        const uint32_t mrow = (warp < 3) ? 784 : 0;
        const uint32_t pmask = (c == 0) ? 0xFFFFu : 0u;

        uint32_t mk[14];
        auto align_mask = [&](const uint32_t (&mw)[26]) {
#pragma unroll
            for (int i = 0; i < 14; i++) mk[i] = prmt(mw[i], i < 12 ? mw[14 + i] : 0u, msel);
        };
        auto load_mask = [&](uint32_t (&mw)[26]) {
            const uint32_t ma = mrel + (mdelta & 12);
#pragma unroll
            for (int i = 0; i < 14; i++) {
                mw[i] = lds32(ma + (i & 1) * mrow + (i >> 1) * 16);
                if (i < 12) mw[14 + i] = lds32(ma + (i & 1) * mrow + (i >> 1) * 16 + 4);
            }
            __syncwarp();
            if (lane == 0) mbar_arrive(bars + B_MCONS);
            mdelta += 4 * P.npair;
        };
        {
            uint32_t mw[26];
            mbar_wait(bars + B_MFULL + (wg - 1) * 8, 0);
            load_mask(mw);
            align_mask(mw);
        }
        const uint32_t barw = bars + (wg - 1) * 8;
        const uint64_t descKw = descK0 + (uint64_t)((wg - 1) * (XCH >> 4)), descVw = descV0 + (uint64_t)((wg - 1) * (V_STRIDE >> 4));
        uint32_t oa = orel + (wg - 1) * omul;
        const uint32_t oflip = oa ^ (oa + 2 * omul);
        uint32_t qok = 0;
        const uint32_t zero = (uint32_t)P.z1;
        auto window = [&](auto IT_, int k) {
            constexpr int IT = decltype(IT_)::value;
            const uint32_t bar = barw + 16 * IT;
            const int tl = (k * TOK + TOK - 1) >> 6, tn = ((k + 2) * TOK + TOK - 1) >> 6;
            const uint32_t bt = bars + (tl & 3) * 8, pt = (tl >> 2) & 1;
            TR(8, k);
            float sc0[28], sc1[28];
            auto init = [&](float (&S)[28], int h) {
#pragma unroll
                for (int i = 0; i < 14; i++) {
                    const uint32_t b = hadd2_bf16(bias[14 * h + i], mk[i]);
                    S[2 * i] = bf16lo(b);
                    S[2 * i + 1] = (i < 12) ? bf16hi(b) : 0.f;
                }
                reg_fence(S);
            };
            init(sc0, 0);
            init(sc1, 1);
            TR(10, k);
            mbar_wait_unless(qok, bt + B_QKRAW, pt);
            fence_async_smem();
            TR(11, k);
            wgmma_fence();
            mma_qk0<2 * IT * XCH, 2 * IT * XCH>(sc0, descKw, descKw);
            mma_qk1<2 * IT * XCH, 2 * IT * XCH>(sc1, descKw, descKw);
            wgmma_commit();
            const uint32_t mok = mbar_test(barw + B_MFULL, IT ^ 1) | (k + 2 >= nwin);
            const uint32_t vok = mbar_test(bt + B_VRAW, pt);
            float m[4];
            auto rowmax = [&](const float (&S)[28], int h) {
#pragma unroll
                for (int o = 0; o < 4; o += 2) {
                    float a = fmaxf(S[o], S[o + 1]), b = fmaxf(S[4 + o], S[5 + o]);
#pragma unroll
                    for (int j = 2; j < 6; j += 2) {
                        a = fmaxf(a, fmaxf(S[4 * j + o], S[4 * j + o + 1]));
                        b = fmaxf(b, fmaxf(S[4 * j + 4 + o], S[4 * j + 5 + o]));
                    }
                    m[2 * h + (o >> 1)] = fmaxf(fmaxf(a, b), S[24 + o]);
                }
            };
            wgmma_wait<0>();
            reg_fence(sc0);
            reg_fence(sc1);
            if (lane == 0) mbar_arrive(bar + B_QKFREE);
            TR(12, k);
            rowmax(sc0, 0);
            rowmax(sc1, 1);
#pragma unroll
            for (int i = 0; i < 4; i++) m[i] = fmaxf(m[i], __shfl_xor_sync(0xffffffffu, m[i], 1));
#pragma unroll
            for (int i = 0; i < 4; i++) m[i] = fmaxf(m[i], __shfl_xor_sync(0xffffffffu, m[i], 2)) * -LOG2E;
            auto probs = [&](const float (&S)[28], float m0, float m1, uint32_t (&pa)[4][4]) {
#pragma unroll
                for (int j = 0; j < 6; j++) {
                    pa[j >> 1][(j & 1) * 2]     = pack_bf16(ex2_ftz(fmaf(S[4 * j], LOG2E, m0)), ex2_ftz(fmaf(S[4 * j + 1], LOG2E, m0)));
                    pa[j >> 1][(j & 1) * 2 + 1] = pack_bf16(ex2_ftz(fmaf(S[4 * j + 2], LOG2E, m1)), ex2_ftz(fmaf(S[4 * j + 3], LOG2E, m1)));
                }
                pa[3][0] = pack_bf16(ex2_ftz(fmaf(S[24], LOG2E, m0)), 0.f) & pmask;
                pa[3][1] = pack_bf16(ex2_ftz(fmaf(S[26], LOG2E, m1)), 0.f) & pmask;
                pa[3][2] = 0u; pa[3][3] = 0u;
                reg_fence(pa);
            };
            uint32_t pa0[4][4], pa1[4][4];
            float o0[28], o1[28];
            TR(13, k);
            mbar_wait2_unless(vok & mok, bt + B_VRAW, pt, k + 2 < nwin ? barw + B_MFULL : bt + B_VRAW, k + 2 < nwin ? IT ^ 1 : pt);
            fence_async_smem();
            TR(14, k);
            uint32_t mw[26];
            load_mask(mw);
            probs(sc0, m[0], m[1], pa0);
            align_mask(mw);
            wgmma_fence();
            mma_pv<2 * IT * V_STRIDE, 0>(o0, pa0, descVw);
            wgmma_commit();
            probs(sc1, m[2], m[3], pa1);
            wgmma_fence();
            mma_pv<2 * IT * V_STRIDE + 6 * GRP, 0>(o1, pa1, descVw);
            wgmma_commit();
            uint32_t w[24];
            wgmma_wait<1>();
            reg_fence(o0);
            {
                const float il0 = rcp_ftz(o0[24]), il1 = rcp_ftz(o0[26]);
                const uint32_t l0 = pack_bf16(il0, il0), l1 = pack_bf16(il1, il1);
#pragma unroll
                for (int j = 0; j < 12; j++) w[j] = hmul2_bf16(pack_bf16(o0[2 * j], o0[2 * j + 1]), (j & 1) ? l1 : l0);
            }
            wgmma_wait<0>();
            reg_fence(o1);
            TR(15, k);
            asm volatile("{\n.reg .pred p;\nsetp.eq.u32 p, %0, 1;\n@p bar.sync 4, 128;\n@!p bar.sync 5, 128;\n}\n"
                         :: "r"(wg) : "memory");
            qok = mbar_test(bars + (tn & 3) * 8 + B_QKRAW, (tn >> 2) & 1);
            {
                const float il2 = rcp_ftz(o1[0]), il3 = rcp_ftz(o1[2]);
                const uint32_t l2 = pack_bf16(il2, il2), l3 = pack_bf16(il3, il3);
#pragma unroll
                for (int j = 0; j < 12; j++) w[12 + j] = hmul2_bf16(pack_bf16(o1[2 * j + 4], o1[2 * j + 5]), (j & 1) ? l3 : l2);
#pragma unroll
                for (int p = 0; p < 6; p++) stsm_x4(oa + p * 32, w[4 * p], w[4 * p + 1], w[4 * p + 2], w[4 * p + 3]);
            }
            __syncwarp();
            if (lane == 0) mbar_arrive(bar + B_ODONE);
            TR(16, k);
            oa ^= oflip;
            asm volatile("" : "+r"(oa));
        };
        for (int k = wg - 1;; k += 4) {
            window(std::integral_constant<int, 0>(), k);
            if (k + 2 >= nwin) break;
            window(std::integral_constant<int, 1>(), k + 2);
            if (k + 4 >= nwin) break;
        }
        (void)zero;
        asm volatile("setmaxnreg.inc.sync.aligned.u32 160;\n");
    }

    TR(27, wg);
    if (attn) {
        __syncwarp();
        if (lane == 0) mbar_arrive(sbase + SM_PBAR + 96);
    }
    if (!attn || wg == 0) {
#pragma unroll 3
        for (int row = tid >> 2; row < 192; row += attn ? 32 : 96) {
            uint4 w[6];
#pragma unroll
            for (int a = 0; a < 6; a++) w[a] = *reinterpret_cast<const uint4*>(P.wo + row * 192 + 32 * a + 8 * c);
            float s = 0.f;
#pragma unroll
            for (int a = 0; a < 6; a++)
                s += ((bf16lo(w[a].x) + bf16hi(w[a].x)) + (bf16lo(w[a].y) + bf16hi(w[a].y))) +
                     ((bf16lo(w[a].z) + bf16hi(w[a].z)) + (bf16lo(w[a].w) + bf16hi(w[a].w)));
            s += __shfl_xor_sync(0xffffffffu, s, 1);
            s += __shfl_xor_sync(0xffffffffu, s, 2);
            s *= (1.f / 192.f);
            const uint32_t d = sbase + SM_WO + row * 64 + ((c ^ ((row >> 1) & 3)) << 4);
#pragma unroll
            for (int a = 0; a < 6; a++)
                sts128(d + a * 12288, pack_bf16(bf16lo(w[a].x) - s, bf16hi(w[a].x) - s), pack_bf16(bf16lo(w[a].y) - s, bf16hi(w[a].y) - s),
                       pack_bf16(bf16lo(w[a].z) - s, bf16hi(w[a].z) - s), pack_bf16(bf16lo(w[a].w) - s, bf16hi(w[a].w) - s));
        }
        fence_async_smem();
    }
    asm volatile("bar.sync 6, 384;\n" ::: "memory");
    TR(27, 4 + wg);
    {
        PROJ_SCHEDULE
        uint64_t descW = make_desc(sbase + SM_WO, 12288, 512, 2);
        const uint64_t descA = make_desc(sbase + SM_STAGE + wg * STAGE_BYTES, 16, 1024, 1);
        const uint32_t bar = sbase + SM_PBAR + wg * 8;
        const uint32_t yrel = sbase + SM_STAGE + wg * STAGE_BYTES + (warp * 16 + (lane & 15)) * 128 + (((lane & 7) ^ (lane >> 4)) << 4);
        float acc[96];
#pragma unroll
        for (int i = 0; i < 96; i++) acc[i] = 0.f;
        uint32_t it = 0;
        for (int tile = tile0 + wg * tstep; tile < tend; tile += 3 * tstep, it++) {
            descW += P.z1;
            mbar_wait(bar + (it & 1) * 24, (it >> 1) & 1);
            TR(28, it * 3 + wg);
            if (it > 0 || wg > 0) asm volatile("bar.sync %0, 256;\n" :: "r"(8 + wg) : "memory");
            wgmma_fence();
            mma_proj<0, 0>(acc, descA + (uint64_t)((it & 1) * (3 * STAGE_BYTES >> 4)), descW);
            wgmma_commit();
            if (tile + tstep < tend) asm volatile("bar.arrive %0, 256;\n" :: "r"(wg == 2 ? 8 : 9 + wg) : "memory");
            wgmma_wait<0>();
            reg_fence(acc);
            float a[4];
#pragma unroll
            for (int i = 0; i < 4; i++) a[i] = acc[i] * acc[i];
#pragma unroll
            for (int j = 1; j < 24; j++)
#pragma unroll
                for (int i = 0; i < 4; i++) a[i] = fmaf(acc[4 * j + i], acc[4 * j + i], a[i]);
            float s0 = a[0] + a[1], s1 = a[2] + a[3];
            s0 += __shfl_xor_sync(0xffffffffu, s0, 1);
            s1 += __shfl_xor_sync(0xffffffffu, s1, 1);
            s0 += __shfl_xor_sync(0xffffffffu, s0, 2);
            s1 += __shfl_xor_sync(0xffffffffu, s1, 2);
            const float rs0 = rsqrt_ftz(fmaf(s0, 1.f / 192.f, 1e-5f));
            const float rs1 = rsqrt_ftz(fmaf(s1, 1.f / 192.f, 1e-5f));
            const uint32_t ya = yrel + (it & 1) * 3 * STAGE_BYTES;
#pragma unroll
            for (int p = 0; p < 12; p++)
                stsm_x4((ya ^ (32 * (p & 3))) + (p >> 2) * 8192,
                        pack_bf16(acc[8 * p] * rs0, acc[8 * p + 1] * rs0), pack_bf16(acc[8 * p + 2] * rs1, acc[8 * p + 3] * rs1),
                        pack_bf16(acc[8 * p + 4] * rs0, acc[8 * p + 5] * rs0), pack_bf16(acc[8 * p + 6] * rs1, acc[8 * p + 7] * rs1));
            __syncwarp();
            if (lane == 0) mbar_arrive(bar + 104 + (it & 1) * 24);
            TR(29, it * 3 + wg);
        }
    }
}

}

typedef CUresult (*PFN_encodeTiled)(CUtensorMap*, CUtensorMapDataType, cuuint32_t, void*, const cuuint64_t*,
                                    const cuuint64_t*, const cuuint32_t*, const cuuint32_t*, CUtensorMapInterleave,
                                    CUtensorMapSwizzle, CUtensorMapL2promotion, CUtensorMapFloatOOBfill);

extern "C" void kernel_launch(void* const* d_in, const int* in_sizes, int n_in, void* d_out, int out_size) {
    swin::Params P;
    P.x           = (const __nv_bfloat16*)d_in[0];
    P.wqkv        = (const __nv_bfloat16*)d_in[1];
    P.wo          = (const __nv_bfloat16*)d_in[2];
    P.logit_scale = (const __nv_bfloat16*)d_in[3];
    P.cpb_w1      = (const __nv_bfloat16*)d_in[4];
    P.cpb_w2      = (const __nv_bfloat16*)d_in[5];
    P.rel_coords  = (const __nv_bfloat16*)d_in[6];
    P.rel_idx     = (const int*)d_in[7];
    P.mask        = (const __nv_bfloat16*)d_in[8];
    P.out         = (__nv_bfloat16*)d_out;
    P.z1 = 0;
    static PFN_encodeTiled encode = nullptr;
    if (!encode) {
        cudaFuncSetAttribute(swin::swin_window_attn_kernel, cudaFuncAttributeMaxDynamicSharedMemorySize, swin::SM_TOTAL);
        cudaDriverEntryPointQueryResult qr;
        cudaGetDriverEntryPoint("cuTensorMapEncodeTiled", (void**)&encode, cudaEnableDefault, &qr);
    }
    CUtensorMap xmap, xmap4, xmap3, omap, wmap, smap, omapb, xmapa, xmapb, smap3, wraw;
    const cuuint32_t estr[4] = {1, 1, 1, 1};
    auto make = [&](CUtensorMap* m, const void* base, int rank, const cuuint64_t* gdim, const cuuint64_t* gstr,
                    const cuuint32_t* box, CUtensorMapSwizzle swz = CU_TENSOR_MAP_SWIZZLE_128B) {
        CUresult r = encode(m, CU_TENSOR_MAP_DATA_TYPE_BFLOAT16, rank, const_cast<void*>(base), gdim, gstr, box, estr,
               CU_TENSOR_MAP_INTERLEAVE_NONE, swz, CU_TENSOR_MAP_L2_PROMOTION_L2_128B,
               CU_TENSOR_MAP_FLOAT_OOB_FILL_NONE);
        (void)r;
    };
    {
        const cuuint64_t gdim[3] = {192, swin::IMG, swin::IMG}, gstr[2] = {384, swin::IMG * 384};
        const cuuint32_t box[3] = {64, 7, 7}, box4[3] = {64, 4, 1}, box3[3] = {64, 3, 1};
        make(&xmap, P.x, 3, gdim, gstr, box);
        make(&xmap4, P.x, 3, gdim, gstr, box4);
        make(&xmap3, P.x, 3, gdim, gstr, box3);
        const cuuint32_t boxa[3] = {64, 7, 3}, boxb[3] = {64, 7, 4};
        make(&xmapa, P.x, 3, gdim, gstr, boxa);
        make(&xmapb, P.x, 3, gdim, gstr, boxb);
    }
    {
        const cuuint64_t gdim[2] = {192, (cuuint64_t)swin::NPIX}, gstr[1] = {384};
        const cuuint32_t box64[2] = {64, 64};
        make(&omap, d_out, 2, gdim, gstr, box64);
        const cuuint64_t gdimb[2] = {192, (cuuint64_t)swin::SEG_B};
        make(&omapb, d_out, 2, gdimb, gstr, box64);
    }
    {
        const cuuint64_t gdim[2] = {576, 192}, gstr[1] = {1152};
        const cuuint32_t box[2] = {16, 192};
        make(&wmap, P.wqkv, 2, gdim, gstr, box, CU_TENSOR_MAP_SWIZZLE_32B);
        const cuuint64_t gdim3[3] = {96, 6, 192}, gstr3[2] = {192, 1152};
        const cuuint32_t box3[3] = {104, 1, 96};
        make(&wraw, P.wqkv, 3, gdim3, gstr3, box3, CU_TENSOR_MAP_SWIZZLE_NONE);
    }
    {
        const cuuint64_t gdim[4] = {96, 2, swin::IMG, swin::IMG}, gstr[3] = {192, 384, swin::IMG * 384};
        const cuuint32_t box4[4] = {104, 1, 7, 4}, box3[4] = {104, 1, 7, 3};
        make(&smap, d_out, 4, gdim, gstr, box4, CU_TENSOR_MAP_SWIZZLE_NONE);
        make(&smap3, d_out, 4, gdim, gstr, box3, CU_TENSOR_MAP_SWIZZLE_NONE);
    }
    P.npair = NPAIR; P.need = swin::ROW_DONE; P.nq = swin::NWINDOWS / NPAIR; P.nr = swin::NWINDOWS % NPAIR;
    P.t1 = swin::TILES - NTAIL;
    swin::swin_window_attn_kernel<<<132, swin::NTHREADS, swin::SM_TOTAL>>>(P, xmap, xmap4, xmap3, omap, wmap, smap, omapb, xmapa, xmapb, smap3, wraw);
}
```

```cpp
#include <cuda_runtime.h>
#include <cuda.h>
#include <cuda_bf16.h>
#include <stdint.h>
#include <type_traits>

namespace swin {

#define NPAIR 52
#define QFP32 0
#define PF_DIST 3
#define EXP 0
#define QSPLIT 3
#define SSPLIT 0
#define LATEMASK 0
#define CLUSTER 0
#define NOPF 0
#define NTAIL 216
#define PSTORE 1
#define PORDER 1
#define GORD 0
#define GMERGE 0
#define XSPLIT 1
#define EARLYW 1
#define NEARLY 4
#define W1 1
#define W2 2
#define W3 2
#define T_ONEBUF 0
#define T_NOWV 0
#define MPF 3
#define MRND 5
#define HINT 0
#define HINT_A ""
#define HINT_B ""
#define REG_G 232
#define REG_A 120
#define REG_H 32
constexpr int IMG      = 511;
constexpr int NWS      = 73;
constexpr int NWINDOWS = NWS * NWS;
constexpr int TOK      = 49;
constexpr int NPIX     = IMG * IMG;
constexpr int NTHREADS = 512;

constexpr int W_ATOM = 6144;
constexpr int SM_WA = 0, SM_WB = 6 * W_ATOM, SM_WV = 12 * W_ATOM;
constexpr int GRP   = TOK * 16;
constexpr int XCH   = TOK * 128;
constexpr int SM_V  = 18 * W_ATOM, V_STRIDE = 10240, O_PITCH = 208;
constexpr int SM_QK = SM_V + 4 * V_STRIDE, QK_CHUNK = 4 * XCH;
constexpr int SM_MASK = SM_QK + 3 * QK_CHUNK;
constexpr int SM_TAB  = SM_V + 3 * V_STRIDE + 256;
constexpr int SM_DUMP = SM_MASK + 4816;
constexpr int SM_BAR  = SM_DUMP + 320;
constexpr int B_XFULL = 0, B_WRAW = 32, B_XCONS = 40, B_QKRAW = 64, B_QKFREE = 96, B_VFREE = 128, B_ODONE = 160,
              B_VRAW = 224, B_MFULL = 256, B_MSTATE = 264, B_MCONS = 272, B_WFULL = 280, B_STORED = 288, B_PUBD = 304;
constexpr int SM_A_END = SM_BAR + 320;
static_assert(SM_QK % 1024 == 0 && TOK * O_PITCH + 64 - 16 <= V_STRIDE && (28 * O_PITCH + 64) % 128 == 0, "layout");
constexpr int SM_WO    = 0;
constexpr int SM_STAGE = 73728;
constexpr int STAGE_BYTES = 24576;
constexpr int SM_PBAR  = SM_A_END;
constexpr int SM_TOTAL = SM_PBAR + 152;
static_assert(SM_STAGE + 6 * STAGE_BYTES <= SM_BAR, "smem");
static_assert(SM_TOTAL <= 232448, "smem");
static_assert(SM_BAR % 8 == 0, "barrier alignment");

constexpr int SEG_B   = 3 * IMG;
constexpr int TILES_A = (NPIX - SEG_B + 63) / 64;
constexpr int TILES   = TILES_A + (SEG_B + 63) / 64;
constexpr uint32_t ROW_DONE = NWS * 2;

__device__ uint32_t g_cnt[NWS + 7];
__device__ uint32_t g_done;
__device__ __align__(16) uint32_t g_guard[4];
constexpr uint32_t F32_INF = 0x7F800000u;
constexpr uint32_t SS_MIN  = 0x3B800000u;
constexpr uint32_t VAR_MIN = 0x3D400000u;

#define TR(ev, idx)
constexpr float LOG2E = 1.4426950408889634f;

__device__ __forceinline__ uint32_t smem_u32(const void* p) {
    return (uint32_t)__cvta_generic_to_shared(p);
}
__device__ __forceinline__ uint64_t make_desc(uint32_t saddr, uint32_t lbo, uint32_t sbo, uint32_t swz = 0) {
    return (uint64_t)((saddr & 0x3FFFF) >> 4) | ((uint64_t)(lbo >> 4) << 16) | ((uint64_t)(sbo >> 4) << 32) |
           ((uint64_t)swz << 62);
}
__host__ __device__ constexpr uint64_t make_desc_c(uint32_t saddr, uint32_t lbo, uint32_t sbo, uint32_t swz) {
    return (uint64_t)(saddr >> 4) | ((uint64_t)(lbo >> 4) << 16) | ((uint64_t)(sbo >> 4) << 32) | ((uint64_t)swz << 62);
}
__device__ __forceinline__ void wgmma_fence()  { asm volatile("wgmma.fence.sync.aligned;\n" ::: "memory"); }
__device__ __forceinline__ void wgmma_commit() { asm volatile("wgmma.commit_group.sync.aligned;\n" ::: "memory"); }
template <int N> __device__ __forceinline__ void wgmma_wait() {
    asm volatile("wgmma.wait_group.sync.aligned %0;\n" :: "n"(N) : "memory");
}
__device__ __forceinline__ void fence_async_smem() { asm volatile("fence.proxy.async.shared::cta;\n" ::: "memory"); }
__device__ __forceinline__ void wg_bar(int id) { asm volatile("bar.sync %0, 128;\n" :: "r"(id) : "memory"); }

template <int N> __device__ __forceinline__ void reg_fence(float (&v)[N]) {
#pragma unroll
    for (int i = 0; i < N; i++) asm volatile("" : "+f"(v[i]) :: "memory");
}
template <int N> __device__ __forceinline__ void reg_fence(uint32_t (&v)[N]) {
#pragma unroll
    for (int i = 0; i < N; i++) asm volatile("" : "+r"(v[i]) :: "memory");
}
template <int N, int M> __device__ __forceinline__ void reg_fence(uint32_t (&v)[N][M]) {
#pragma unroll
    for (int i = 0; i < N; i++) reg_fence(v[i]);
}

__device__ __forceinline__ uint32_t pack_bf16(float lo, float hi) {
    uint32_t r;
    asm("cvt.rn.bf16x2.f32 %0, %1, %2;\n" : "=r"(r) : "f"(hi), "f"(lo));
    return r;
}
__device__ __forceinline__ uint32_t pack_f16(float lo, float hi) {
    uint32_t r;
    asm("cvt.rn.f16x2.f32 %0, %1, %2;\n" : "=r"(r) : "f"(hi), "f"(lo));
    return r;
}
__device__ __forceinline__ uint32_t pack_f16_sat(float lo, float hi) {
    uint32_t r;
    asm("cvt.rn.satfinite.f16x2.f32 %0, %1, %2;\n" : "=r"(r) : "f"(hi), "f"(lo));
    return r;
}
__device__ __forceinline__ uint32_t hmul2_f16(uint32_t a, uint32_t b) {
    uint32_t r;
    asm("mul.rn.f16x2 %0, %1, %2;\n" : "=r"(r) : "r"(a), "r"(b));
    return r;
}
__device__ __forceinline__ uint32_t hadd2_f16(uint32_t a, uint32_t b) {
    uint32_t r;
    asm("add.rn.f16x2 %0, %1, %2;\n" : "=r"(r) : "r"(a), "r"(b));
    return r;
}
__device__ __forceinline__ uint32_t hfma2_f16(uint32_t a, uint32_t b, uint32_t c) {
    uint32_t r;
    asm("fma.rn.f16x2 %0, %1, %2, %3;\n" : "=r"(r) : "r"(a), "r"(b), "r"(c));
    return r;
}
__device__ __forceinline__ uint32_t hmax2_f16(uint32_t a, uint32_t b) {
    uint32_t r;
    asm("max.f16x2 %0, %1, %2;\n" : "=r"(r) : "r"(a), "r"(b));
    return r;
}
template <int H> __device__ __forceinline__ uint32_t hsub2_bc(uint32_t a, uint32_t b) {
    uint32_t r;
    if (H == 0) asm("{\n.reg .b16 l, h;\n.reg .b32 t;\nmov.b32 {l, h}, %2;\nmov.b32 t, {l, l};\nsub.rn.f16x2 %0, %1, t;\n}\n" : "=r"(r) : "r"(a), "r"(b));
    else        asm("{\n.reg .b16 l, h;\n.reg .b32 t;\nmov.b32 {l, h}, %2;\nmov.b32 t, {h, h};\nsub.rn.f16x2 %0, %1, t;\n}\n" : "=r"(r) : "r"(a), "r"(b));
    return r;
}
__device__ __forceinline__ uint32_t ex2_f16x2(uint32_t a) {
    uint32_t r;
    asm("ex2.approx.f16x2 %0, %1;\n" : "=r"(r) : "r"(a));
    return r;
}
__device__ __forceinline__ uint32_t ex2_f16lo(uint32_t a) {
    uint32_t r;
    asm("{\n.reg .b16 l, h;\nmov.b32 {l, h}, %1;\nex2.approx.f16 l, l;\nmov.b32 %0, {l, h};\n}\n" : "=r"(r) : "r"(a));
    return r;
}
__device__ __forceinline__ uint32_t lds16(uint32_t addr) {
    uint32_t v;
    asm volatile("ld.shared.u16 %0, [%1];\n" : "=r"(v) : "r"(addr) : "memory");
    return v;
}
__device__ __forceinline__ float f16lo(uint32_t v) {
    float r;
    asm("{\n.reg .b16 l, h;\nmov.b32 {l, h}, %1;\ncvt.f32.f16 %0, l;\n}\n" : "=f"(r) : "r"(v));
    return r;
}
__device__ __forceinline__ float f16hi(uint32_t v) {
    float r;
    asm("{\n.reg .b16 l, h;\nmov.b32 {l, h}, %1;\ncvt.f32.f16 %0, h;\n}\n" : "=f"(r) : "r"(v));
    return r;
}
__device__ __forceinline__ uint32_t bf2h(uint32_t v) {
    return pack_f16(__uint_as_float(v << 16), __uint_as_float(v & 0xFFFF0000u));
}
__device__ __forceinline__ float bf16lo(uint32_t v) { return __uint_as_float(v << 16); }
__device__ __forceinline__ float bf16hi(uint32_t v) { return __uint_as_float(v & 0xFFFF0000u); }
__device__ __forceinline__ uint32_t hadd2_bf16(uint32_t a, uint32_t b) {
    uint32_t r;
    asm("add.rn.bf16x2 %0, %1, %2;\n" : "=r"(r) : "r"(a), "r"(b));
    return r;
}
__device__ __forceinline__ uint32_t hmul2_bf16(uint32_t a, uint32_t b) {
    uint32_t r;
    asm("mul.rn.bf16x2 %0, %1, %2;\n" : "=r"(r) : "r"(a), "r"(b));
    return r;
}
__device__ __forceinline__ uint32_t hsub2_bf16(uint32_t a, uint32_t b) {
    uint32_t r;
    asm("sub.rn.bf16x2 %0, %1, %2;\n" : "=r"(r) : "r"(a), "r"(b));
    return r;
}
__device__ __forceinline__ uint32_t hfma2_bf16(uint32_t a, uint32_t b, uint32_t c) {
    uint32_t r;
    asm("fma.rn.bf16x2 %0, %1, %2, %3;\n" : "=r"(r) : "r"(a), "r"(b), "r"(c));
    return r;
}
__device__ __forceinline__ uint32_t hmax2_bf16(uint32_t a, uint32_t b) {
    uint32_t r;
    asm("max.bf16x2 %0, %1, %2;\n" : "=r"(r) : "r"(a), "r"(b));
    return r;
}
__device__ __forceinline__ uint32_t ex2_bf16x2(uint32_t a) {
    uint32_t r;
    asm("ex2.approx.ftz.bf16x2 %0, %1;\n" : "=r"(r) : "r"(a));
    return r;
}
__device__ __forceinline__ uint32_t ex2_bf16lo(uint32_t a) {
    uint32_t r;
    asm("{\n.reg .b16 l, h;\nmov.b32 {l, h}, %1;\nex2.approx.ftz.bf16 l, l;\ncvt.u32.u16 %0, l;\n}\n" : "=r"(r) : "r"(a));
    return r;
}
__device__ __forceinline__ uint32_t mbar_test(uint32_t bar, uint32_t parity) {
    uint32_t ok;
    asm volatile("{\n.reg .pred p;\nmbarrier.test_wait.parity.shared::cta.b64 p, [%1], %2;\nselp.u32 %0, 1, 0, p;\n}\n"
                 : "=r"(ok) : "r"(bar), "r"(parity) : "memory");
    return ok;
}
__device__ __forceinline__ uint32_t prmt(uint32_t a, uint32_t b, uint32_t sel) {
    uint32_t r;
    asm("prmt.b32 %0, %1, %2, %3;\n" : "=r"(r) : "r"(a), "r"(b), "r"(sel));
    return r;
}
__device__ __forceinline__ float round_bf16(float x) { return __bfloat162float(__float2bfloat16_rn(x)); }

__device__ __forceinline__ void mbar_init(uint32_t bar, uint32_t count) {
    asm volatile("mbarrier.init.shared::cta.b64 [%0], %1;\n" :: "r"(bar), "r"(count) : "memory");
}
__device__ __forceinline__ void mbar_wait(uint32_t bar, uint32_t parity) {
    asm volatile(
        "{\n"
        ".reg .pred p;\n"
        ".reg .u32 n;\n"
        "mov.u32 n, 0;\n"
        "WAIT_%=:\n"
        "mbarrier.try_wait.parity.shared::cta.b64 p, [%0], %1" HINT_A ";\n"
        "@p bra DONE_%=;\n"
        "add.u32 n, n, 1;\n"
        "setp.lt.u32 p, n, 4194304;\n"
        "@p bra WAIT_%=;\n"
        "exit;\n"
        "DONE_%=:\n"
        "}\n" :: "r"(bar), "r"(parity) : "memory");
}
__device__ __forceinline__ void mbar_wait4(uint32_t b0, uint32_t p0, uint32_t b1, uint32_t p1, uint32_t b2, uint32_t p2,
                                           uint32_t b3, uint32_t p3) {
    asm volatile(
        "{\n"
        ".reg .pred p, q, r, s;\n"
        ".reg .u32 n;\n"
        "mov.u32 n, 0;\n"
        "WAIT_%=:\n"
        "mbarrier.try_wait.parity.shared::cta.b64 p, [%0], %1;\n"
        "mbarrier.try_wait.parity.shared::cta.b64 q, [%2], %3;\n"
        "mbarrier.try_wait.parity.shared::cta.b64 r, [%4], %5;\n"
        "mbarrier.try_wait.parity.shared::cta.b64 s, [%6], %7;\n"
        "and.pred p, p, q;\n"
        "and.pred r, r, s;\n"
        "and.pred p, p, r;\n"
        "@p bra DONE_%=;\n"
        "add.u32 n, n, 1;\n"
        "setp.lt.u32 p, n, 4194304;\n"
        "@p bra WAIT_%=;\n"
        "exit;\n"
        "DONE_%=:\n"
        "}\n" :: "r"(b0), "r"(p0), "r"(b1), "r"(p1), "r"(b2), "r"(p2), "r"(b3), "r"(p3) : "memory");
}
__device__ __forceinline__ void mbar_wait2(uint32_t b0, uint32_t p0, uint32_t b1, uint32_t p1) {
    asm volatile(
        "{\n"
        ".reg .pred p, q;\n"
        ".reg .u32 n;\n"
        "mov.u32 n, 0;\n"
        "WAIT_%=:\n"
        "mbarrier.try_wait.parity.shared::cta.b64 p, [%0], %1;\n"
        "mbarrier.try_wait.parity.shared::cta.b64 q, [%2], %3;\n"
        "and.pred p, p, q;\n"
        "@p bra DONE_%=;\n"
        "add.u32 n, n, 1;\n"
        "setp.lt.u32 p, n, 4194304;\n"
        "@p bra WAIT_%=;\n"
        "exit;\n"
        "DONE_%=:\n"
        "}\n" :: "r"(b0), "r"(p0), "r"(b1), "r"(p1) : "memory");
}
__device__ __forceinline__ void mbar_wait_unless(uint32_t ok, uint32_t bar, uint32_t parity) {
    asm volatile(
        "{\n"
        ".reg .pred p;\n"
        ".reg .u32 n;\n"
        "setp.ne.u32 p, %2, 0;\n"
        "vote.sync.all.pred p, p, 0xffffffff;\n"
        "@p bra DONE_%=;\n"
        "mov.u32 n, 0;\n"
        "WAIT_%=:\n"
        "mbarrier.try_wait.parity.shared::cta.b64 p, [%0], %1" HINT_B ";\n"
        "@p bra DONE_%=;\n"
        "add.u32 n, n, 1;\n"
        "setp.lt.u32 p, n, 4194304;\n"
        "@p bra WAIT_%=;\n"
        "exit;\n"
        "DONE_%=:\n"
        "}\n" :: "r"(bar), "r"(parity), "r"(ok) : "memory");
}
__device__ __forceinline__ void mbar_wait_unless_dep(uint32_t ok, uint32_t bar, uint32_t parity, uint32_t zero, uint32_t& a,
                                                     uint32_t& b, uint32_t& c, uint32_t& d) {
    asm volatile(
        "{\n"
        ".reg .pred p;\n"
        ".reg .u32 n;\n"
        "setp.ne.u32 p, %6, 0;\n"
        "vote.sync.all.pred p, p, 0xffffffff;\n"
        "@p bra DONE_%=;\n"
        "mov.u32 n, 0;\n"
        "WAIT_%=:\n"
        "setp.ne.u32 p, %7, 0;\n"
        "@p ld.shared.v4.b32 {%0, %1, %2, %3}, [%7];\n"
        "mbarrier.try_wait.parity.shared::cta.b64 p, [%4], %5;\n"
        "@p bra DONE_%=;\n"
        "add.u32 n, n, 1;\n"
        "setp.lt.u32 p, n, 4194304;\n"
        "@p bra WAIT_%=;\n"
        "exit;\n"
        "DONE_%=:\n"
        "}\n" : "+r"(a), "+r"(b), "+r"(c), "+r"(d) : "r"(bar), "r"(parity), "r"(ok), "r"(zero) : "memory");
}
__device__ __forceinline__ void mbar_wait2_unless(uint32_t ok, uint32_t b0, uint32_t p0, uint32_t b1, uint32_t p1) {
    asm volatile(
        "{\n"
        ".reg .pred p, q;\n"
        ".reg .u32 n;\n"
        "setp.ne.u32 p, %4, 0;\n"
        "vote.sync.all.pred p, p, 0xffffffff;\n"
        "@p bra DONE_%=;\n"
        "mov.u32 n, 0;\n"
        "WAIT_%=:\n"
        "mbarrier.try_wait.parity.shared::cta.b64 p, [%0], %1" HINT_B ";\n"
        "mbarrier.try_wait.parity.shared::cta.b64 q, [%2], %3" HINT_B ";\n"
        "and.pred p, p, q;\n"
        "@p bra DONE_%=;\n"
        "add.u32 n, n, 1;\n"
        "setp.lt.u32 p, n, 4194304;\n"
        "@p bra WAIT_%=;\n"
        "exit;\n"
        "DONE_%=:\n"
        "}\n" :: "r"(b0), "r"(p0), "r"(b1), "r"(p1), "r"(ok) : "memory");
}
__device__ __forceinline__ void mbar_wait4_unless(uint32_t ok, uint32_t b0, uint32_t p0, uint32_t b1, uint32_t p1, uint32_t b2,
                                                  uint32_t p2, uint32_t b3, uint32_t p3) {
    asm volatile(
        "{\n"
        ".reg .pred p, q, r, s;\n"
        ".reg .u32 n;\n"
        "setp.ne.u32 p, %8, 0;\n"
        "vote.sync.all.pred p, p, 0xffffffff;\n"
        "@p bra DONE_%=;\n"
        "mov.u32 n, 0;\n"
        "WAIT_%=:\n"
        "mbarrier.try_wait.parity.shared::cta.b64 p, [%0], %1;\n"
        "mbarrier.try_wait.parity.shared::cta.b64 q, [%2], %3;\n"
        "mbarrier.try_wait.parity.shared::cta.b64 r, [%4], %5;\n"
        "mbarrier.try_wait.parity.shared::cta.b64 s, [%6], %7;\n"
        "and.pred p, p, q;\n"
        "and.pred r, r, s;\n"
        "and.pred p, p, r;\n"
        "@p bra DONE_%=;\n"
        "add.u32 n, n, 1;\n"
        "setp.lt.u32 p, n, 4194304;\n"
        "@p bra WAIT_%=;\n"
        "exit;\n"
        "DONE_%=:\n"
        "}\n" :: "r"(b0), "r"(p0), "r"(b1), "r"(p1), "r"(b2), "r"(p2), "r"(b3), "r"(p3), "r"(ok) : "memory");
}
__device__ __forceinline__ void sched_fence(uint32_t zero, uint32_t a, uint32_t b, uint32_t c, uint32_t d, uint32_t e = 0,
                                            uint32_t f = 0, uint32_t g = 0, uint32_t h = 0, uint32_t i = 0, uint32_t j = 0,
                                            uint32_t k = 0) {
    asm volatile("{\n.reg .pred p;\n.reg .u32 n;\nsetp.eq.u32 p, %0, 0;\n@p bra.uni DONE_%=;\nmov.u32 n, %0;\nSPIN_%=:\n"
                 "nanosleep.u32 %1;\nnanosleep.u32 %2;\nnanosleep.u32 %3;\nnanosleep.u32 %4;\nnanosleep.u32 %5;\n"
                 "nanosleep.u32 %6;\nnanosleep.u32 %7;\nnanosleep.u32 %8;\nnanosleep.u32 %9;\nnanosleep.u32 %10;\n"
                 "nanosleep.u32 %11;\nsub.u32 n, n, 1;\nsetp.ne.u32 p, n, 0;\n@p bra.uni SPIN_%=;\nDONE_%=:\n}\n"
                 :: "r"(zero), "r"(a), "r"(b), "r"(c), "r"(d), "r"(e), "r"(f), "r"(g), "r"(h), "r"(i), "r"(j), "r"(k) : "memory");
}
__device__ __forceinline__ void sched_fence16(uint32_t zero, const uint32_t (&v)[4][4], uint32_t a = 0, uint32_t b = 0) {
    asm volatile("{\n.reg .pred p;\n.reg .u32 n;\nsetp.eq.u32 p, %0, 0;\n@p bra.uni DONE_%=;\nmov.u32 n, %0;\nSPIN_%=:\n"
                 "nanosleep.u32 %17;\nnanosleep.u32 %18;\n"
                 "st.shared.v4.b32 [n], {%1, %2, %3, %4};\nst.shared.v4.b32 [n + 16], {%5, %6, %7, %8};\n"
                 "st.shared.v4.b32 [n + 32], {%9, %10, %11, %12};\nst.shared.v4.b32 [n + 48], {%13, %14, %15, %16};\n"
                 "sub.u32 n, n, 1;\nsetp.ne.u32 p, n, 0;\n@p bra.uni SPIN_%=;\nDONE_%=:\n}\n"
                 :: "r"(zero), "r"(v[0][0]), "r"(v[0][1]), "r"(v[0][2]), "r"(v[0][3]), "r"(v[1][0]), "r"(v[1][1]), "r"(v[1][2]), "r"(v[1][3]),
                    "r"(v[2][0]), "r"(v[2][1]), "r"(v[2][2]), "r"(v[2][3]), "r"(v[3][0]), "r"(v[3][1]), "r"(v[3][2]), "r"(v[3][3]),
                    "r"(a), "r"(b) : "memory");
}
__device__ __forceinline__ void sched_dep(uint32_t zero, uint32_t& a, uint32_t& b, uint32_t& c, uint32_t& d) {
    asm volatile("{\n.reg .pred p;\n.reg .u32 n;\nsetp.eq.u32 p, %4, 0;\n@p bra.uni DONE_%=;\nmov.u32 n, %4;\nSPIN_%=:\n"
                 "ld.shared.v4.b32 {%0, %1, %2, %3}, [n];\n"
                 "sub.u32 n, n, 1;\nsetp.ne.u32 p, n, 0;\n@p bra.uni SPIN_%=;\nDONE_%=:\n}\n"
                 : "+r"(a), "+r"(b), "+r"(c), "+r"(d) : "r"(zero) : "memory");
}
__device__ __forceinline__ void mbar_arrive(uint32_t bar) {
    asm volatile("mbarrier.arrive.shared::cta.b64 _, [%0];\n" :: "r"(bar) : "memory");
}
__device__ __forceinline__ void mbar_arrive_n(uint32_t bar, uint32_t n) {
    asm volatile("mbarrier.arrive.shared::cta.b64 _, [%0], %1;\n" :: "r"(bar), "r"(n) : "memory");
}
__device__ __forceinline__ void mbar_arrive_expect_tx(uint32_t bar, uint32_t bytes) {
    asm volatile("mbarrier.arrive.expect_tx.shared::cta.b64 _, [%0], %1;\n" :: "r"(bar), "r"(bytes) : "memory");
}
__device__ __forceinline__ void stg128_if(bool p, void* addr, uint32_t x, uint32_t y, uint32_t z, uint32_t w) {
    asm volatile("{\n.reg .pred q;\nsetp.ne.b32 q, %5, 0;\n@q st.global.L1::no_allocate.v4.b32 [%0], {%1, %2, %3, %4};\n}\n"
                 :: "l"(addr), "r"(x), "r"(y), "r"(z), "r"(w), "r"((uint32_t)p) : "memory");
}
__device__ __forceinline__ void stsm_x4(uint32_t addr, uint32_t r0, uint32_t r1, uint32_t r2, uint32_t r3) {
    asm volatile("stmatrix.sync.aligned.m8n8.x4.shared.b16 [%0], {%1, %2, %3, %4};\n"
                 :: "r"(addr), "r"(r0), "r"(r1), "r"(r2), "r"(r3) : "memory");
}
__device__ __forceinline__ void stsm_x2(uint32_t addr, uint32_t r0, uint32_t r1) {
    asm volatile("stmatrix.sync.aligned.m8n8.x2.shared.b16 [%0], {%1, %2};\n" :: "r"(addr), "r"(r0), "r"(r1) : "memory");
}
__device__ __forceinline__ void sts128(uint32_t addr, uint32_t r0, uint32_t r1, uint32_t r2, uint32_t r3) {
    asm volatile("st.shared.v4.b32 [%0], {%1, %2, %3, %4};\n" :: "r"(addr), "r"(r0), "r"(r1), "r"(r2), "r"(r3) : "memory");
}
__device__ __forceinline__ void sts32(uint32_t addr, uint32_t v) {
    asm volatile("st.shared.b32 [%0], %1;\n" :: "r"(addr), "r"(v) : "memory");
}
__device__ __forceinline__ uint32_t lds32(uint32_t addr) {
    uint32_t v;
    asm volatile("ld.shared.b32 %0, [%1];\n" : "=r"(v) : "r"(addr) : "memory");
    return v;
}
__device__ __forceinline__ void lds128(uint32_t (&r)[4], uint32_t addr) {
    asm volatile("ld.shared.v4.b32 {%0, %1, %2, %3}, [%4];\n" : "=r"(r[0]), "=r"(r[1]), "=r"(r[2]), "=r"(r[3]) : "r"(addr) : "memory");
}
__device__ __forceinline__ uint32_t lds32v(uint32_t addr) {
    uint32_t v;
    asm volatile("ld.volatile.shared.b32 %0, [%1];\n" : "=r"(v) : "r"(addr) : "memory");
    return v;
}
__device__ __forceinline__ void ldg_nc_v4(uint32_t (&r)[4], const void* p) {
    asm volatile("ld.global.nc.L1::no_allocate.v4.u32 {%0, %1, %2, %3}, [%4];\n"
                 : "=r"(r[0]), "=r"(r[1]), "=r"(r[2]), "=r"(r[3]) : "l"(p));
}
__device__ __forceinline__ uint32_t ldg_u32(const void* p) {
    uint32_t v;
    asm volatile("ld.global.nc.L1::evict_first.u32 %0, [%1];\n" : "=r"(v) : "l"(p));
    return v;
}
__device__ __forceinline__ void ldg_u64(const void* p, uint32_t& a, uint32_t& b) {
    asm volatile("ld.global.nc.L1::evict_first.v2.u32 {%0, %1}, [%2];\n" : "=r"(a), "=r"(b) : "l"(p));
}
__device__ __forceinline__ void prefetch_l2(const void* p) {
    asm volatile("prefetch.global.L2 [%0];\n" :: "l"(p));
}
__device__ __forceinline__ void cp_async16(uint32_t dst, const void* src) {
    asm volatile("cp.async.cg.shared.global [%0], [%1], 16;\n" :: "r"(dst), "l"(src) : "memory");
}
__device__ __forceinline__ float ex2_ftz(float x) {
    float y;
    asm("ex2.approx.ftz.f32 %0, %1;\n" : "=f"(y) : "f"(x));
    return y;
}
__device__ __forceinline__ float rcp_ftz(float x) {
    float y;
    asm("rcp.approx.ftz.f32 %0, %1;\n" : "=f"(y) : "f"(x));
    return y;
}
__device__ __forceinline__ float rsqrt_ftz(float x) {
    float y;
    asm("rsqrt.approx.ftz.f32 %0, %1;\n" : "=f"(y) : "f"(x));
    return y;
}

__device__ __forceinline__ bool elect_one() {
    uint32_t p;
    asm volatile("{\n.reg .pred q;\nelect.sync _|q, 0xffffffff;\nselp.u32 %0, 1, 0, q;\n}\n" : "=r"(p));
    return p != 0;
}
__device__ __forceinline__ void ldsm_x4(uint32_t (&r)[4], uint32_t addr) {
    asm volatile("ldmatrix.sync.aligned.m8n8.x4.shared.b16 {%0, %1, %2, %3}, [%4];\n"
                 : "=r"(r[0]), "=r"(r[1]), "=r"(r[2]), "=r"(r[3]) : "r"(addr) : "memory");
}
__device__ __forceinline__ void ldsm_x2(uint32_t& r0, uint32_t& r1, uint32_t addr) {
    asm volatile("ldmatrix.sync.aligned.m8n8.x2.shared.b16 {%0, %1}, [%2];\n" : "=r"(r0), "=r"(r1) : "r"(addr) : "memory");
}
__device__ __forceinline__ void tma_2d(uint32_t dst, const CUtensorMap* map, uint32_t bar, int c0, int c1) {
    asm volatile("cp.async.bulk.tensor.2d.shared::cluster.global.mbarrier::complete_tx::bytes [%0], [%1, {%3, %4}], [%2];\n"
                 :: "r"(dst), "l"(reinterpret_cast<uint64_t>(map)), "r"(bar), "r"(c0), "r"(c1) : "memory");
}
__device__ __forceinline__ void tma_3d(uint32_t dst, const CUtensorMap* map, uint32_t bar, int c0, int c1, int c2) {
    asm volatile("cp.async.bulk.tensor.3d.shared::cluster.global.mbarrier::complete_tx::bytes [%0], [%1, {%3, %4, %5}], [%2];\n"
                 :: "r"(dst), "l"(reinterpret_cast<uint64_t>(map)), "r"(bar), "r"(c0), "r"(c1), "r"(c2) : "memory");
}
__device__ __forceinline__ void tma_store_4d(const CUtensorMap* map, uint32_t src, int c0, int c1, int c2, int c3) {
    asm volatile("cp.async.bulk.tensor.4d.global.shared::cta.tile.bulk_group [%0, {%2, %3, %4, %5}], [%1];\n"
                 :: "l"(reinterpret_cast<uint64_t>(map)), "r"(src), "r"(c0), "r"(c1), "r"(c2), "r"(c3) : "memory");
}
__device__ __forceinline__ void mbar_arrive_if(uint32_t bar, uint32_t cnt) {
    asm volatile("{\n.reg .pred q;\nsetp.ne.b32 q, %1, 0;\n@q mbarrier.arrive.shared::cta.b64 _, [%0], %1;\n}\n"
                 :: "r"(bar), "r"(cnt) : "memory");
}

template <int BOFF, int AOFF, int NA>
__device__ __forceinline__ void mma_qk_first(uint32_t (&d)[48], const uint32_t (&a)[NA][4], uint64_t descB) {
    asm volatile(
        "{\n"
        ".reg .pred p0, p1;\n"
        ".reg .b64 ta, ta0, tb, tb0;\n"
        "setp.ne.b32 p0, 0, 0;\n"
        "setp.eq.b32 p1, 0, 0;\n"
        "add.s64 tb0, %64, %65;\n"
        "add.s64 tb, tb0, 0;\n"
        "wgmma.mma_async.sync.aligned.m64n192k16.f16.f16.f16 {%0, %1, %2, %3, %4, %5, %6, %7, %8, %9, %10, %11, %12, %13, %14, %15, %16, %17, %18, %19, %20, %21, %22, %23, %24, %25, %26, %27, %28, %29, %30, %31, %32, %33, %34, %35, %36, %37, %38, %39, %40, %41, %42, %43, %44, %45, %46, %47}, {%48, %49, %50, %51}, tb, p0, 1, 1, 1;\n"
        "add.s64 tb, tb0, 32;\n"
        "wgmma.mma_async.sync.aligned.m64n192k16.f16.f16.f16 {%0, %1, %2, %3, %4, %5, %6, %7, %8, %9, %10, %11, %12, %13, %14, %15, %16, %17, %18, %19, %20, %21, %22, %23, %24, %25, %26, %27, %28, %29, %30, %31, %32, %33, %34, %35, %36, %37, %38, %39, %40, %41, %42, %43, %44, %45, %46, %47}, {%52, %53, %54, %55}, tb, p1, 1, 1, 1;\n"
        "add.s64 tb, tb0, 64;\n"
        "wgmma.mma_async.sync.aligned.m64n192k16.f16.f16.f16 {%0, %1, %2, %3, %4, %5, %6, %7, %8, %9, %10, %11, %12, %13, %14, %15, %16, %17, %18, %19, %20, %21, %22, %23, %24, %25, %26, %27, %28, %29, %30, %31, %32, %33, %34, %35, %36, %37, %38, %39, %40, %41, %42, %43, %44, %45, %46, %47}, {%56, %57, %58, %59}, tb, p1, 1, 1, 1;\n"
        "add.s64 tb, tb0, 96;\n"
        "wgmma.mma_async.sync.aligned.m64n192k16.f16.f16.f16 {%0, %1, %2, %3, %4, %5, %6, %7, %8, %9, %10, %11, %12, %13, %14, %15, %16, %17, %18, %19, %20, %21, %22, %23, %24, %25, %26, %27, %28, %29, %30, %31, %32, %33, %34, %35, %36, %37, %38, %39, %40, %41, %42, %43, %44, %45, %46, %47}, {%60, %61, %62, %63}, tb, p1, 1, 1, 1;\n"
        "}\n"
        : "=r"(d[0]), "=r"(d[1]), "=r"(d[2]), "=r"(d[3]), "=r"(d[4]), "=r"(d[5]), "=r"(d[6]), "=r"(d[7]), "=r"(d[8]), "=r"(d[9]), "=r"(d[10]), "=r"(d[11]), "=r"(d[12]), "=r"(d[13]), "=r"(d[14]), "=r"(d[15]), "=r"(d[16]), "=r"(d[17]), "=r"(d[18]), "=r"(d[19]), "=r"(d[20]), "=r"(d[21]), "=r"(d[22]), "=r"(d[23]), "=r"(d[24]), "=r"(d[25]), "=r"(d[26]), "=r"(d[27]), "=r"(d[28]), "=r"(d[29]), "=r"(d[30]), "=r"(d[31]), "=r"(d[32]), "=r"(d[33]), "=r"(d[34]), "=r"(d[35]), "=r"(d[36]), "=r"(d[37]), "=r"(d[38]), "=r"(d[39]), "=r"(d[40]), "=r"(d[41]), "=r"(d[42]), "=r"(d[43]), "=r"(d[44]), "=r"(d[45]), "=r"(d[46]), "=r"(d[47])
        : "r"(a[AOFF + 0][0]), "r"(a[AOFF + 0][1]), "r"(a[AOFF + 0][2]), "r"(a[AOFF + 0][3]), "r"(a[AOFF + 1][0]), "r"(a[AOFF + 1][1]), "r"(a[AOFF + 1][2]), "r"(a[AOFF + 1][3]), "r"(a[AOFF + 2][0]), "r"(a[AOFF + 2][1]), "r"(a[AOFF + 2][2]), "r"(a[AOFF + 2][3]), "r"(a[AOFF + 3][0]), "r"(a[AOFF + 3][1]), "r"(a[AOFF + 3][2]), "r"(a[AOFF + 3][3]), "l"(descB), "n"(BOFF >> 4));
}

template <int BOFF, int AOFF, int NA>
__device__ __forceinline__ void mma_qk_next(uint32_t (&d)[48], const uint32_t (&a)[NA][4], uint64_t descB) {
    asm volatile(
        "{\n"
        ".reg .pred p0, p1;\n"
        ".reg .b64 ta, ta0, tb, tb0;\n"
        "setp.ne.b32 p0, 0, 0;\n"
        "setp.eq.b32 p1, 0, 0;\n"
        "add.s64 tb0, %64, %65;\n"
        "add.s64 tb, tb0, 0;\n"
        "wgmma.mma_async.sync.aligned.m64n192k16.f16.f16.f16 {%0, %1, %2, %3, %4, %5, %6, %7, %8, %9, %10, %11, %12, %13, %14, %15, %16, %17, %18, %19, %20, %21, %22, %23, %24, %25, %26, %27, %28, %29, %30, %31, %32, %33, %34, %35, %36, %37, %38, %39, %40, %41, %42, %43, %44, %45, %46, %47}, {%48, %49, %50, %51}, tb, p1, 1, 1, 1;\n"
        "add.s64 tb, tb0, 32;\n"
        "wgmma.mma_async.sync.aligned.m64n192k16.f16.f16.f16 {%0, %1, %2, %3, %4, %5, %6, %7, %8, %9, %10, %11, %12, %13, %14, %15, %16, %17, %18, %19, %20, %21, %22, %23, %24, %25, %26, %27, %28, %29, %30, %31, %32, %33, %34, %35, %36, %37, %38, %39, %40, %41, %42, %43, %44, %45, %46, %47}, {%52, %53, %54, %55}, tb, p1, 1, 1, 1;\n"
        "add.s64 tb, tb0, 64;\n"
        "wgmma.mma_async.sync.aligned.m64n192k16.f16.f16.f16 {%0, %1, %2, %3, %4, %5, %6, %7, %8, %9, %10, %11, %12, %13, %14, %15, %16, %17, %18, %19, %20, %21, %22, %23, %24, %25, %26, %27, %28, %29, %30, %31, %32, %33, %34, %35, %36, %37, %38, %39, %40, %41, %42, %43, %44, %45, %46, %47}, {%56, %57, %58, %59}, tb, p1, 1, 1, 1;\n"
        "add.s64 tb, tb0, 96;\n"
        "wgmma.mma_async.sync.aligned.m64n192k16.f16.f16.f16 {%0, %1, %2, %3, %4, %5, %6, %7, %8, %9, %10, %11, %12, %13, %14, %15, %16, %17, %18, %19, %20, %21, %22, %23, %24, %25, %26, %27, %28, %29, %30, %31, %32, %33, %34, %35, %36, %37, %38, %39, %40, %41, %42, %43, %44, %45, %46, %47}, {%60, %61, %62, %63}, tb, p1, 1, 1, 1;\n"
        "}\n"
        : "+r"(d[0]), "+r"(d[1]), "+r"(d[2]), "+r"(d[3]), "+r"(d[4]), "+r"(d[5]), "+r"(d[6]), "+r"(d[7]), "+r"(d[8]), "+r"(d[9]), "+r"(d[10]), "+r"(d[11]), "+r"(d[12]), "+r"(d[13]), "+r"(d[14]), "+r"(d[15]), "+r"(d[16]), "+r"(d[17]), "+r"(d[18]), "+r"(d[19]), "+r"(d[20]), "+r"(d[21]), "+r"(d[22]), "+r"(d[23]), "+r"(d[24]), "+r"(d[25]), "+r"(d[26]), "+r"(d[27]), "+r"(d[28]), "+r"(d[29]), "+r"(d[30]), "+r"(d[31]), "+r"(d[32]), "+r"(d[33]), "+r"(d[34]), "+r"(d[35]), "+r"(d[36]), "+r"(d[37]), "+r"(d[38]), "+r"(d[39]), "+r"(d[40]), "+r"(d[41]), "+r"(d[42]), "+r"(d[43]), "+r"(d[44]), "+r"(d[45]), "+r"(d[46]), "+r"(d[47])
        : "r"(a[AOFF + 0][0]), "r"(a[AOFF + 0][1]), "r"(a[AOFF + 0][2]), "r"(a[AOFF + 0][3]), "r"(a[AOFF + 1][0]), "r"(a[AOFF + 1][1]), "r"(a[AOFF + 1][2]), "r"(a[AOFF + 1][3]), "r"(a[AOFF + 2][0]), "r"(a[AOFF + 2][1]), "r"(a[AOFF + 2][2]), "r"(a[AOFF + 2][3]), "r"(a[AOFF + 3][0]), "r"(a[AOFF + 3][1]), "r"(a[AOFF + 3][2]), "r"(a[AOFF + 3][3]), "l"(descB), "n"(BOFF >> 4));
}

template <int BOFF, int AOFF, int NA>
__device__ __forceinline__ void mma_v_first(uint32_t (&d)[24], const uint32_t (&a)[NA][4], uint64_t descB) {
    asm volatile(
        "{\n"
        ".reg .pred p0, p1;\n"
        ".reg .b64 ta, ta0, tb, tb0;\n"
        "setp.ne.b32 p0, 0, 0;\n"
        "setp.eq.b32 p1, 0, 0;\n"
        "add.s64 tb0, %40, %41;\n"
        "add.s64 tb, tb0, 0;\n"
        "wgmma.mma_async.sync.aligned.m64n96k16.f16.f16.f16 {%0, %1, %2, %3, %4, %5, %6, %7, %8, %9, %10, %11, %12, %13, %14, %15, %16, %17, %18, %19, %20, %21, %22, %23}, {%24, %25, %26, %27}, tb, p0, 1, 1, 1;\n"
        "add.s64 tb, tb0, 32;\n"
        "wgmma.mma_async.sync.aligned.m64n96k16.f16.f16.f16 {%0, %1, %2, %3, %4, %5, %6, %7, %8, %9, %10, %11, %12, %13, %14, %15, %16, %17, %18, %19, %20, %21, %22, %23}, {%28, %29, %30, %31}, tb, p1, 1, 1, 1;\n"
        "add.s64 tb, tb0, 64;\n"
        "wgmma.mma_async.sync.aligned.m64n96k16.f16.f16.f16 {%0, %1, %2, %3, %4, %5, %6, %7, %8, %9, %10, %11, %12, %13, %14, %15, %16, %17, %18, %19, %20, %21, %22, %23}, {%32, %33, %34, %35}, tb, p1, 1, 1, 1;\n"
        "add.s64 tb, tb0, 96;\n"
        "wgmma.mma_async.sync.aligned.m64n96k16.f16.f16.f16 {%0, %1, %2, %3, %4, %5, %6, %7, %8, %9, %10, %11, %12, %13, %14, %15, %16, %17, %18, %19, %20, %21, %22, %23}, {%36, %37, %38, %39}, tb, p1, 1, 1, 1;\n"
        "}\n"
        : "=r"(d[0]), "=r"(d[1]), "=r"(d[2]), "=r"(d[3]), "=r"(d[4]), "=r"(d[5]), "=r"(d[6]), "=r"(d[7]), "=r"(d[8]), "=r"(d[9]), "=r"(d[10]), "=r"(d[11]), "=r"(d[12]), "=r"(d[13]), "=r"(d[14]), "=r"(d[15]), "=r"(d[16]), "=r"(d[17]), "=r"(d[18]), "=r"(d[19]), "=r"(d[20]), "=r"(d[21]), "=r"(d[22]), "=r"(d[23])
        : "r"(a[AOFF + 0][0]), "r"(a[AOFF + 0][1]), "r"(a[AOFF + 0][2]), "r"(a[AOFF + 0][3]), "r"(a[AOFF + 1][0]), "r"(a[AOFF + 1][1]), "r"(a[AOFF + 1][2]), "r"(a[AOFF + 1][3]), "r"(a[AOFF + 2][0]), "r"(a[AOFF + 2][1]), "r"(a[AOFF + 2][2]), "r"(a[AOFF + 2][3]), "r"(a[AOFF + 3][0]), "r"(a[AOFF + 3][1]), "r"(a[AOFF + 3][2]), "r"(a[AOFF + 3][3]), "l"(descB), "n"(BOFF >> 4));
}

template <int BOFF, int AOFF, int NA>
__device__ __forceinline__ void mma_v_next(uint32_t (&d)[24], const uint32_t (&a)[NA][4], uint64_t descB) {
    asm volatile(
        "{\n"
        ".reg .pred p0, p1;\n"
        ".reg .b64 ta, ta0, tb, tb0;\n"
        "setp.ne.b32 p0, 0, 0;\n"
        "setp.eq.b32 p1, 0, 0;\n"
        "add.s64 tb0, %40, %41;\n"
        "add.s64 tb, tb0, 0;\n"
        "wgmma.mma_async.sync.aligned.m64n96k16.f16.f16.f16 {%0, %1, %2, %3, %4, %5, %6, %7, %8, %9, %10, %11, %12, %13, %14, %15, %16, %17, %18, %19, %20, %21, %22, %23}, {%24, %25, %26, %27}, tb, p1, 1, 1, 1;\n"
        "add.s64 tb, tb0, 32;\n"
        "wgmma.mma_async.sync.aligned.m64n96k16.f16.f16.f16 {%0, %1, %2, %3, %4, %5, %6, %7, %8, %9, %10, %11, %12, %13, %14, %15, %16, %17, %18, %19, %20, %21, %22, %23}, {%28, %29, %30, %31}, tb, p1, 1, 1, 1;\n"
        "add.s64 tb, tb0, 64;\n"
        "wgmma.mma_async.sync.aligned.m64n96k16.f16.f16.f16 {%0, %1, %2, %3, %4, %5, %6, %7, %8, %9, %10, %11, %12, %13, %14, %15, %16, %17, %18, %19, %20, %21, %22, %23}, {%32, %33, %34, %35}, tb, p1, 1, 1, 1;\n"
        "add.s64 tb, tb0, 96;\n"
        "wgmma.mma_async.sync.aligned.m64n96k16.f16.f16.f16 {%0, %1, %2, %3, %4, %5, %6, %7, %8, %9, %10, %11, %12, %13, %14, %15, %16, %17, %18, %19, %20, %21, %22, %23}, {%36, %37, %38, %39}, tb, p1, 1, 1, 1;\n"
        "}\n"
        : "+r"(d[0]), "+r"(d[1]), "+r"(d[2]), "+r"(d[3]), "+r"(d[4]), "+r"(d[5]), "+r"(d[6]), "+r"(d[7]), "+r"(d[8]), "+r"(d[9]), "+r"(d[10]), "+r"(d[11]), "+r"(d[12]), "+r"(d[13]), "+r"(d[14]), "+r"(d[15]), "+r"(d[16]), "+r"(d[17]), "+r"(d[18]), "+r"(d[19]), "+r"(d[20]), "+r"(d[21]), "+r"(d[22]), "+r"(d[23])
        : "r"(a[AOFF + 0][0]), "r"(a[AOFF + 0][1]), "r"(a[AOFF + 0][2]), "r"(a[AOFF + 0][3]), "r"(a[AOFF + 1][0]), "r"(a[AOFF + 1][1]), "r"(a[AOFF + 1][2]), "r"(a[AOFF + 1][3]), "r"(a[AOFF + 2][0]), "r"(a[AOFF + 2][1]), "r"(a[AOFF + 2][2]), "r"(a[AOFF + 2][3]), "r"(a[AOFF + 3][0]), "r"(a[AOFF + 3][1]), "r"(a[AOFF + 3][2]), "r"(a[AOFF + 3][3]), "l"(descB), "n"(BOFF >> 4));
}

template <int AOFF, int BOFF>
__device__ __forceinline__ void mma_s0_f32(float (&d)[28], uint64_t descA, uint64_t descB) {
    asm volatile(
        "{\n"
        ".reg .pred p0, p1;\n"
        ".reg .b64 ta, ta0, tb, tb0;\n"
        "setp.ne.b32 p0, 0, 0;\n"
        "setp.eq.b32 p1, 0, 0;\n"
        "add.s64 tb0, %30, %31;\n"
        "add.s64 ta0, %28, %29;\n"
        "add.s64 tb, tb0, 4;\n"
        "add.s64 ta, ta0, 0;\n"
        "wgmma.mma_async.sync.aligned.m64n56k16.f32.f16.f16 {%0, %1, %2, %3, %4, %5, %6, %7, %8, %9, %10, %11, %12, %13, %14, %15, %16, %17, %18, %19, %20, %21, %22, %23, %24, %25, %26, %27}, ta, tb, p1, 1, 1, 0, 0;\n"
        "add.s64 tb, tb0, 1572;\n"
        "add.s64 ta, ta0, 1568;\n"
        "wgmma.mma_async.sync.aligned.m64n56k16.f32.f16.f16 {%0, %1, %2, %3, %4, %5, %6, %7, %8, %9, %10, %11, %12, %13, %14, %15, %16, %17, %18, %19, %20, %21, %22, %23, %24, %25, %26, %27}, ta, tb, p1, 1, 1, 0, 0;\n"
        "add.s64 tb, tb0, 3140;\n"
        "add.s64 ta, ta0, 3136;\n"
        "wgmma.mma_async.sync.aligned.m64n56k16.f32.f16.f16 {%0, %1, %2, %3, %4, %5, %6, %7, %8, %9, %10, %11, %12, %13, %14, %15, %16, %17, %18, %19, %20, %21, %22, %23, %24, %25, %26, %27}, ta, tb, p1, 1, 1, 0, 0;\n"
        "}\n"
        : "+f"(d[0]), "+f"(d[1]), "+f"(d[2]), "+f"(d[3]), "+f"(d[4]), "+f"(d[5]), "+f"(d[6]), "+f"(d[7]), "+f"(d[8]), "+f"(d[9]), "+f"(d[10]), "+f"(d[11]), "+f"(d[12]), "+f"(d[13]), "+f"(d[14]), "+f"(d[15]), "+f"(d[16]), "+f"(d[17]), "+f"(d[18]), "+f"(d[19]), "+f"(d[20]), "+f"(d[21]), "+f"(d[22]), "+f"(d[23]), "+f"(d[24]), "+f"(d[25]), "+f"(d[26]), "+f"(d[27])
        : "l"(descA), "n"(AOFF >> 4), "l"(descB), "n"(BOFF >> 4));
}

template <int AOFF, int BOFF>
__device__ __forceinline__ void mma_s0_f16(uint32_t (&d)[14], uint64_t descA, uint64_t descB) {
    asm volatile(
        "{\n"
        ".reg .pred p0, p1;\n"
        ".reg .b64 ta, ta0, tb, tb0;\n"
        "setp.ne.b32 p0, 0, 0;\n"
        "setp.eq.b32 p1, 0, 0;\n"
        "add.s64 tb0, %16, %17;\n"
        "add.s64 ta0, %14, %15;\n"
        "add.s64 tb, tb0, 4;\n"
        "add.s64 ta, ta0, 0;\n"
        "wgmma.mma_async.sync.aligned.m64n56k16.f16.f16.f16 {%0, %1, %2, %3, %4, %5, %6, %7, %8, %9, %10, %11, %12, %13}, ta, tb, p1, 1, 1, 0, 0;\n"
        "add.s64 tb, tb0, 1572;\n"
        "add.s64 ta, ta0, 1568;\n"
        "wgmma.mma_async.sync.aligned.m64n56k16.f16.f16.f16 {%0, %1, %2, %3, %4, %5, %6, %7, %8, %9, %10, %11, %12, %13}, ta, tb, p1, 1, 1, 0, 0;\n"
        "add.s64 tb, tb0, 3140;\n"
        "add.s64 ta, ta0, 3136;\n"
        "wgmma.mma_async.sync.aligned.m64n56k16.f16.f16.f16 {%0, %1, %2, %3, %4, %5, %6, %7, %8, %9, %10, %11, %12, %13}, ta, tb, p1, 1, 1, 0, 0;\n"
        "}\n"
        : "+r"(d[0]), "+r"(d[1]), "+r"(d[2]), "+r"(d[3]), "+r"(d[4]), "+r"(d[5]), "+r"(d[6]), "+r"(d[7]), "+r"(d[8]), "+r"(d[9]), "+r"(d[10]), "+r"(d[11]), "+r"(d[12]), "+r"(d[13])
        : "l"(descA), "n"(AOFF >> 4), "l"(descB), "n"(BOFF >> 4));
}

template <int AOFF, int BOFF>
__device__ __forceinline__ void mma_s1_f32(float (&d)[28], uint64_t descA, uint64_t descB) {
    asm volatile(
        "{\n"
        ".reg .pred p0, p1;\n"
        ".reg .b64 ta, ta0, tb, tb0;\n"
        "setp.ne.b32 p0, 0, 0;\n"
        "setp.eq.b32 p1, 0, 0;\n"
        "add.s64 tb0, %30, %31;\n"
        "add.s64 ta0, %28, %29;\n"
        "add.s64 tb, tb0, 6;\n"
        "add.s64 ta, ta0, 2;\n"
        "wgmma.mma_async.sync.aligned.m64n56k16.f32.f16.f16 {%0, %1, %2, %3, %4, %5, %6, %7, %8, %9, %10, %11, %12, %13, %14, %15, %16, %17, %18, %19, %20, %21, %22, %23, %24, %25, %26, %27}, ta, tb, p1, 1, 1, 0, 0;\n"
        "add.s64 tb, tb0, 1574;\n"
        "add.s64 ta, ta0, 1570;\n"
        "wgmma.mma_async.sync.aligned.m64n56k16.f32.f16.f16 {%0, %1, %2, %3, %4, %5, %6, %7, %8, %9, %10, %11, %12, %13, %14, %15, %16, %17, %18, %19, %20, %21, %22, %23, %24, %25, %26, %27}, ta, tb, p1, 1, 1, 0, 0;\n"
        "add.s64 tb, tb0, 3142;\n"
        "add.s64 ta, ta0, 3138;\n"
        "wgmma.mma_async.sync.aligned.m64n56k16.f32.f16.f16 {%0, %1, %2, %3, %4, %5, %6, %7, %8, %9, %10, %11, %12, %13, %14, %15, %16, %17, %18, %19, %20, %21, %22, %23, %24, %25, %26, %27}, ta, tb, p1, 1, 1, 0, 0;\n"
        "}\n"
        : "+f"(d[0]), "+f"(d[1]), "+f"(d[2]), "+f"(d[3]), "+f"(d[4]), "+f"(d[5]), "+f"(d[6]), "+f"(d[7]), "+f"(d[8]), "+f"(d[9]), "+f"(d[10]), "+f"(d[11]), "+f"(d[12]), "+f"(d[13]), "+f"(d[14]), "+f"(d[15]), "+f"(d[16]), "+f"(d[17]), "+f"(d[18]), "+f"(d[19]), "+f"(d[20]), "+f"(d[21]), "+f"(d[22]), "+f"(d[23]), "+f"(d[24]), "+f"(d[25]), "+f"(d[26]), "+f"(d[27])
        : "l"(descA), "n"(AOFF >> 4), "l"(descB), "n"(BOFF >> 4));
}

template <int AOFF, int BOFF>
__device__ __forceinline__ void mma_s1_f16(uint32_t (&d)[14], uint64_t descA, uint64_t descB) {
    asm volatile(
        "{\n"
        ".reg .pred p0, p1;\n"
        ".reg .b64 ta, ta0, tb, tb0;\n"
        "setp.ne.b32 p0, 0, 0;\n"
        "setp.eq.b32 p1, 0, 0;\n"
        "add.s64 tb0, %16, %17;\n"
        "add.s64 ta0, %14, %15;\n"
        "add.s64 tb, tb0, 6;\n"
        "add.s64 ta, ta0, 2;\n"
        "wgmma.mma_async.sync.aligned.m64n56k16.f16.f16.f16 {%0, %1, %2, %3, %4, %5, %6, %7, %8, %9, %10, %11, %12, %13}, ta, tb, p1, 1, 1, 0, 0;\n"
        "add.s64 tb, tb0, 1574;\n"
        "add.s64 ta, ta0, 1570;\n"
        "wgmma.mma_async.sync.aligned.m64n56k16.f16.f16.f16 {%0, %1, %2, %3, %4, %5, %6, %7, %8, %9, %10, %11, %12, %13}, ta, tb, p1, 1, 1, 0, 0;\n"
        "add.s64 tb, tb0, 3142;\n"
        "add.s64 ta, ta0, 3138;\n"
        "wgmma.mma_async.sync.aligned.m64n56k16.f16.f16.f16 {%0, %1, %2, %3, %4, %5, %6, %7, %8, %9, %10, %11, %12, %13}, ta, tb, p1, 1, 1, 0, 0;\n"
        "}\n"
        : "+r"(d[0]), "+r"(d[1]), "+r"(d[2]), "+r"(d[3]), "+r"(d[4]), "+r"(d[5]), "+r"(d[6]), "+r"(d[7]), "+r"(d[8]), "+r"(d[9]), "+r"(d[10]), "+r"(d[11]), "+r"(d[12]), "+r"(d[13])
        : "l"(descA), "n"(AOFF >> 4), "l"(descB), "n"(BOFF >> 4));
}

template <int BOFF, int AOFF, int NA>
__device__ __forceinline__ void mma_pv(uint32_t (&d)[14], const uint32_t (&a)[NA][4], uint64_t descB) {
    asm volatile(
        "{\n"
        ".reg .pred p0, p1;\n"
        ".reg .b64 ta, ta0, tb, tb0;\n"
        "setp.ne.b32 p0, 0, 0;\n"
        "setp.eq.b32 p1, 0, 0;\n"
        "add.s64 tb0, %30, %31;\n"
        "add.s64 tb, tb0, 0;\n"
        "wgmma.mma_async.sync.aligned.m64n56k16.f16.f16.f16 {%0, %1, %2, %3, %4, %5, %6, %7, %8, %9, %10, %11, %12, %13}, {%14, %15, %16, %17}, tb, p0, 1, 1, 1;\n"
        "add.s64 tb, tb0, 16;\n"
        "wgmma.mma_async.sync.aligned.m64n56k16.f16.f16.f16 {%0, %1, %2, %3, %4, %5, %6, %7, %8, %9, %10, %11, %12, %13}, {%18, %19, %20, %21}, tb, p1, 1, 1, 1;\n"
        "add.s64 tb, tb0, 32;\n"
        "wgmma.mma_async.sync.aligned.m64n56k16.f16.f16.f16 {%0, %1, %2, %3, %4, %5, %6, %7, %8, %9, %10, %11, %12, %13}, {%22, %23, %24, %25}, tb, p1, 1, 1, 1;\n"
        "add.s64 tb, tb0, 48;\n"
        "wgmma.mma_async.sync.aligned.m64n56k16.f16.f16.f16 {%0, %1, %2, %3, %4, %5, %6, %7, %8, %9, %10, %11, %12, %13}, {%26, %27, %28, %29}, tb, p1, 1, 1, 1;\n"
        "}\n"
        : "=r"(d[0]), "=r"(d[1]), "=r"(d[2]), "=r"(d[3]), "=r"(d[4]), "=r"(d[5]), "=r"(d[6]), "=r"(d[7]), "=r"(d[8]), "=r"(d[9]), "=r"(d[10]), "=r"(d[11]), "=r"(d[12]), "=r"(d[13])
        : "r"(a[AOFF + 0][0]), "r"(a[AOFF + 0][1]), "r"(a[AOFF + 0][2]), "r"(a[AOFF + 0][3]), "r"(a[AOFF + 1][0]), "r"(a[AOFF + 1][1]), "r"(a[AOFF + 1][2]), "r"(a[AOFF + 1][3]), "r"(a[AOFF + 2][0]), "r"(a[AOFF + 2][1]), "r"(a[AOFF + 2][2]), "r"(a[AOFF + 2][3]), "r"(a[AOFF + 3][0]), "r"(a[AOFF + 3][1]), "r"(a[AOFF + 3][2]), "r"(a[AOFF + 3][3]), "l"(descB), "n"(BOFF >> 4));
}

template <int AOFF, int BOFF>
__device__ __forceinline__ void mma_proj(float (&d)[96], uint64_t descA, uint64_t descB) {
    asm volatile(
        "{\n"
        ".reg .pred p0, p1;\n"
        ".reg .b64 ta, ta0, tb, tb0;\n"
        "setp.ne.b32 p0, 0, 0;\n"
        "setp.eq.b32 p1, 0, 0;\n"
        "add.s64 tb0, %98, %99;\n"
        "add.s64 ta0, %96, %97;\n"
        "add.s64 tb, tb0, 0;\n"
        "add.s64 ta, ta0, 0;\n"
        "wgmma.mma_async.sync.aligned.m64n192k16.f32.f16.f16 {%0, %1, %2, %3, %4, %5, %6, %7, %8, %9, %10, %11, %12, %13, %14, %15, %16, %17, %18, %19, %20, %21, %22, %23, %24, %25, %26, %27, %28, %29, %30, %31, %32, %33, %34, %35, %36, %37, %38, %39, %40, %41, %42, %43, %44, %45, %46, %47, %48, %49, %50, %51, %52, %53, %54, %55, %56, %57, %58, %59, %60, %61, %62, %63, %64, %65, %66, %67, %68, %69, %70, %71, %72, %73, %74, %75, %76, %77, %78, %79, %80, %81, %82, %83, %84, %85, %86, %87, %88, %89, %90, %91, %92, %93, %94, %95}, ta, tb, p0, 1, 1, 0, 1;\n"
        "add.s64 tb, tb0, 64;\n"
        "add.s64 ta, ta0, 2;\n"
        "wgmma.mma_async.sync.aligned.m64n192k16.f32.f16.f16 {%0, %1, %2, %3, %4, %5, %6, %7, %8, %9, %10, %11, %12, %13, %14, %15, %16, %17, %18, %19, %20, %21, %22, %23, %24, %25, %26, %27, %28, %29, %30, %31, %32, %33, %34, %35, %36, %37, %38, %39, %40, %41, %42, %43, %44, %45, %46, %47, %48, %49, %50, %51, %52, %53, %54, %55, %56, %57, %58, %59, %60, %61, %62, %63, %64, %65, %66, %67, %68, %69, %70, %71, %72, %73, %74, %75, %76, %77, %78, %79, %80, %81, %82, %83, %84, %85, %86, %87, %88, %89, %90, %91, %92, %93, %94, %95}, ta, tb, p1, 1, 1, 0, 1;\n"
        "add.s64 tb, tb0, 128;\n"
        "add.s64 ta, ta0, 4;\n"
        "wgmma.mma_async.sync.aligned.m64n192k16.f32.f16.f16 {%0, %1, %2, %3, %4, %5, %6, %7, %8, %9, %10, %11, %12, %13, %14, %15, %16, %17, %18, %19, %20, %21, %22, %23, %24, %25, %26, %27, %28, %29, %30, %31, %32, %33, %34, %35, %36, %37, %38, %39, %40, %41, %42, %43, %44, %45, %46, %47, %48, %49, %50, %51, %52, %53, %54, %55, %56, %57, %58, %59, %60, %61, %62, %63, %64, %65, %66, %67, %68, %69, %70, %71, %72, %73, %74, %75, %76, %77, %78, %79, %80, %81, %82, %83, %84, %85, %86, %87, %88, %89, %90, %91, %92, %93, %94, %95}, ta, tb, p1, 1, 1, 0, 1;\n"
        "add.s64 tb, tb0, 192;\n"
        "add.s64 ta, ta0, 6;\n"
        "wgmma.mma_async.sync.aligned.m64n192k16.f32.f16.f16 {%0, %1, %2, %3, %4, %5, %6, %7, %8, %9, %10, %11, %12, %13, %14, %15, %16, %17, %18, %19, %20, %21, %22, %23, %24, %25, %26, %27, %28, %29, %30, %31, %32, %33, %34, %35, %36, %37, %38, %39, %40, %41, %42, %43, %44, %45, %46, %47, %48, %49, %50, %51, %52, %53, %54, %55, %56, %57, %58, %59, %60, %61, %62, %63, %64, %65, %66, %67, %68, %69, %70, %71, %72, %73, %74, %75, %76, %77, %78, %79, %80, %81, %82, %83, %84, %85, %86, %87, %88, %89, %90, %91, %92, %93, %94, %95}, ta, tb, p1, 1, 1, 0, 1;\n"
        "add.s64 tb, tb0, 256;\n"
        "add.s64 ta, ta0, 512;\n"
        "wgmma.mma_async.sync.aligned.m64n192k16.f32.f16.f16 {%0, %1, %2, %3, %4, %5, %6, %7, %8, %9, %10, %11, %12, %13, %14, %15, %16, %17, %18, %19, %20, %21, %22, %23, %24, %25, %26, %27, %28, %29, %30, %31, %32, %33, %34, %35, %36, %37, %38, %39, %40, %41, %42, %43, %44, %45, %46, %47, %48, %49, %50, %51, %52, %53, %54, %55, %56, %57, %58, %59, %60, %61, %62, %63, %64, %65, %66, %67, %68, %69, %70, %71, %72, %73, %74, %75, %76, %77, %78, %79, %80, %81, %82, %83, %84, %85, %86, %87, %88, %89, %90, %91, %92, %93, %94, %95}, ta, tb, p1, 1, 1, 0, 1;\n"
        "add.s64 tb, tb0, 320;\n"
        "add.s64 ta, ta0, 514;\n"
        "wgmma.mma_async.sync.aligned.m64n192k16.f32.f16.f16 {%0, %1, %2, %3, %4, %5, %6, %7, %8, %9, %10, %11, %12, %13, %14, %15, %16, %17, %18, %19, %20, %21, %22, %23, %24, %25, %26, %27, %28, %29, %30, %31, %32, %33, %34, %35, %36, %37, %38, %39, %40, %41, %42, %43, %44, %45, %46, %47, %48, %49, %50, %51, %52, %53, %54, %55, %56, %57, %58, %59, %60, %61, %62, %63, %64, %65, %66, %67, %68, %69, %70, %71, %72, %73, %74, %75, %76, %77, %78, %79, %80, %81, %82, %83, %84, %85, %86, %87, %88, %89, %90, %91, %92, %93, %94, %95}, ta, tb, p1, 1, 1, 0, 1;\n"
        "add.s64 tb, tb0, 384;\n"
        "add.s64 ta, ta0, 516;\n"
        "wgmma.mma_async.sync.aligned.m64n192k16.f32.f16.f16 {%0, %1, %2, %3, %4, %5, %6, %7, %8, %9, %10, %11, %12, %13, %14, %15, %16, %17, %18, %19, %20, %21, %22, %23, %24, %25, %26, %27, %28, %29, %30, %31, %32, %33, %34, %35, %36, %37, %38, %39, %40, %41, %42, %43, %44, %45, %46, %47, %48, %49, %50, %51, %52, %53, %54, %55, %56, %57, %58, %59, %60, %61, %62, %63, %64, %65, %66, %67, %68, %69, %70, %71, %72, %73, %74, %75, %76, %77, %78, %79, %80, %81, %82, %83, %84, %85, %86, %87, %88, %89, %90, %91, %92, %93, %94, %95}, ta, tb, p1, 1, 1, 0, 1;\n"
        "add.s64 tb, tb0, 448;\n"
        "add.s64 ta, ta0, 518;\n"
        "wgmma.mma_async.sync.aligned.m64n192k16.f32.f16.f16 {%0, %1, %2, %3, %4, %5, %6, %7, %8, %9, %10, %11, %12, %13, %14, %15, %16, %17, %18, %19, %20, %21, %22, %23, %24, %25, %26, %27, %28, %29, %30, %31, %32, %33, %34, %35, %36, %37, %38, %39, %40, %41, %42, %43, %44, %45, %46, %47, %48, %49, %50, %51, %52, %53, %54, %55, %56, %57, %58, %59, %60, %61, %62, %63, %64, %65, %66, %67, %68, %69, %70, %71, %72, %73, %74, %75, %76, %77, %78, %79, %80, %81, %82, %83, %84, %85, %86, %87, %88, %89, %90, %91, %92, %93, %94, %95}, ta, tb, p1, 1, 1, 0, 1;\n"
        "add.s64 tb, tb0, 512;\n"
        "add.s64 ta, ta0, 1024;\n"
        "wgmma.mma_async.sync.aligned.m64n192k16.f32.f16.f16 {%0, %1, %2, %3, %4, %5, %6, %7, %8, %9, %10, %11, %12, %13, %14, %15, %16, %17, %18, %19, %20, %21, %22, %23, %24, %25, %26, %27, %28, %29, %30, %31, %32, %33, %34, %35, %36, %37, %38, %39, %40, %41, %42, %43, %44, %45, %46, %47, %48, %49, %50, %51, %52, %53, %54, %55, %56, %57, %58, %59, %60, %61, %62, %63, %64, %65, %66, %67, %68, %69, %70, %71, %72, %73, %74, %75, %76, %77, %78, %79, %80, %81, %82, %83, %84, %85, %86, %87, %88, %89, %90, %91, %92, %93, %94, %95}, ta, tb, p1, 1, 1, 0, 1;\n"
        "add.s64 tb, tb0, 576;\n"
        "add.s64 ta, ta0, 1026;\n"
        "wgmma.mma_async.sync.aligned.m64n192k16.f32.f16.f16 {%0, %1, %2, %3, %4, %5, %6, %7, %8, %9, %10, %11, %12, %13, %14, %15, %16, %17, %18, %19, %20, %21, %22, %23, %24, %25, %26, %27, %28, %29, %30, %31, %32, %33, %34, %35, %36, %37, %38, %39, %40, %41, %42, %43, %44, %45, %46, %47, %48, %49, %50, %51, %52, %53, %54, %55, %56, %57, %58, %59, %60, %61, %62, %63, %64, %65, %66, %67, %68, %69, %70, %71, %72, %73, %74, %75, %76, %77, %78, %79, %80, %81, %82, %83, %84, %85, %86, %87, %88, %89, %90, %91, %92, %93, %94, %95}, ta, tb, p1, 1, 1, 0, 1;\n"
        "add.s64 tb, tb0, 640;\n"
        "add.s64 ta, ta0, 1028;\n"
        "wgmma.mma_async.sync.aligned.m64n192k16.f32.f16.f16 {%0, %1, %2, %3, %4, %5, %6, %7, %8, %9, %10, %11, %12, %13, %14, %15, %16, %17, %18, %19, %20, %21, %22, %23, %24, %25, %26, %27, %28, %29, %30, %31, %32, %33, %34, %35, %36, %37, %38, %39, %40, %41, %42, %43, %44, %45, %46, %47, %48, %49, %50, %51, %52, %53, %54, %55, %56, %57, %58, %59, %60, %61, %62, %63, %64, %65, %66, %67, %68, %69, %70, %71, %72, %73, %74, %75, %76, %77, %78, %79, %80, %81, %82, %83, %84, %85, %86, %87, %88, %89, %90, %91, %92, %93, %94, %95}, ta, tb, p1, 1, 1, 0, 1;\n"
        "add.s64 tb, tb0, 704;\n"
        "add.s64 ta, ta0, 1030;\n"
        "wgmma.mma_async.sync.aligned.m64n192k16.f32.f16.f16 {%0, %1, %2, %3, %4, %5, %6, %7, %8, %9, %10, %11, %12, %13, %14, %15, %16, %17, %18, %19, %20, %21, %22, %23, %24, %25, %26, %27, %28, %29, %30, %31, %32, %33, %34, %35, %36, %37, %38, %39, %40, %41, %42, %43, %44, %45, %46, %47, %48, %49, %50, %51, %52, %53, %54, %55, %56, %57, %58, %59, %60, %61, %62, %63, %64, %65, %66, %67, %68, %69, %70, %71, %72, %73, %74, %75, %76, %77, %78, %79, %80, %81, %82, %83, %84, %85, %86, %87, %88, %89, %90, %91, %92, %93, %94, %95}, ta, tb, p1, 1, 1, 0, 1;\n"
        "}\n"
        : "+f"(d[0]), "+f"(d[1]), "+f"(d[2]), "+f"(d[3]), "+f"(d[4]), "+f"(d[5]), "+f"(d[6]), "+f"(d[7]), "+f"(d[8]), "+f"(d[9]), "+f"(d[10]), "+f"(d[11]), "+f"(d[12]), "+f"(d[13]), "+f"(d[14]), "+f"(d[15]), "+f"(d[16]), "+f"(d[17]), "+f"(d[18]), "+f"(d[19]), "+f"(d[20]), "+f"(d[21]), "+f"(d[22]), "+f"(d[23]), "+f"(d[24]), "+f"(d[25]), "+f"(d[26]), "+f"(d[27]), "+f"(d[28]), "+f"(d[29]), "+f"(d[30]), "+f"(d[31]), "+f"(d[32]), "+f"(d[33]), "+f"(d[34]), "+f"(d[35]), "+f"(d[36]), "+f"(d[37]), "+f"(d[38]), "+f"(d[39]), "+f"(d[40]), "+f"(d[41]), "+f"(d[42]), "+f"(d[43]), "+f"(d[44]), "+f"(d[45]), "+f"(d[46]), "+f"(d[47]), "+f"(d[48]), "+f"(d[49]), "+f"(d[50]), "+f"(d[51]), "+f"(d[52]), "+f"(d[53]), "+f"(d[54]), "+f"(d[55]), "+f"(d[56]), "+f"(d[57]), "+f"(d[58]), "+f"(d[59]), "+f"(d[60]), "+f"(d[61]), "+f"(d[62]), "+f"(d[63]), "+f"(d[64]), "+f"(d[65]), "+f"(d[66]), "+f"(d[67]), "+f"(d[68]), "+f"(d[69]), "+f"(d[70]), "+f"(d[71]), "+f"(d[72]), "+f"(d[73]), "+f"(d[74]), "+f"(d[75]), "+f"(d[76]), "+f"(d[77]), "+f"(d[78]), "+f"(d[79]), "+f"(d[80]), "+f"(d[81]), "+f"(d[82]), "+f"(d[83]), "+f"(d[84]), "+f"(d[85]), "+f"(d[86]), "+f"(d[87]), "+f"(d[88]), "+f"(d[89]), "+f"(d[90]), "+f"(d[91]), "+f"(d[92]), "+f"(d[93]), "+f"(d[94]), "+f"(d[95])
        : "l"(descA), "n"(AOFF >> 4), "l"(descB), "n"(BOFF >> 4));
}

struct Params {
    const __nv_bfloat16* x;
    const __nv_bfloat16* wqkv;
    const __nv_bfloat16* wo;
    const __nv_bfloat16* logit_scale;
    const __nv_bfloat16* cpb_w1;
    const __nv_bfloat16* cpb_w2;
    const __nv_bfloat16* rel_coords;
    const int*           rel_idx;
    const __nv_bfloat16* mask;
    __nv_bfloat16*       out;
    unsigned long long   z1;
    int                  npair;
    uint32_t             need;
    int                  nq, nr;
    int                  t1;
};

__device__ __forceinline__ void finish(uint32_t total) {
    __threadfence();
    if (atomicAdd(&g_done, 1u) == total - 1) {
        for (int i = 0; i < NWS; i++) g_cnt[i] = 0;
        g_done = 0;
    }
}

constexpr int FB_PITCH = 584, FB_X = TOK * FB_PITCH * 2, FB_TAB = FB_X + TOK * 384, FB_BYTES = FB_TAB + 169 * 8 + 8;
static_assert(3 * FB_BYTES <= SM_TOTAL && FB_BYTES % 16 == 0, "smem");
__device__ __forceinline__ void redo(const Params& P, uint8_t* sm, uint32_t tag, int barid) {
    typedef __nv_bfloat16 bf;
    const int t = threadIdx.x & 127, lane = t & 31;
    bf* const qkv = reinterpret_cast<bf*>(sm);
    bf* const xs = reinterpret_cast<bf*>(sm + FB_X);
    bf* const tab = reinterpret_cast<bf*>(sm + FB_TAB);
    volatile int* const next = reinterpret_cast<volatile int*>(sm + FB_TAB + 169 * 8);
#pragma unroll 1
    for (uint32_t n = 0; n < (1u << 22); n++) {
        uint32_t a;
        asm volatile("ld.acquire.gpu.global.u32 %0, [%1];\n" : "=r"(a) : "l"(g_guard) : "memory");
        if (a == tag + 1) break;
        __nanosleep(256);
    }
    asm volatile("fence.proxy.async;\n" ::: "memory");
#pragma unroll 1
    for (int i = t; i < 169 * 4; i += 128) {
        float a = 0.f;
#pragma unroll 1
        for (int u = 0; u < 16; u++) {
            const float h = round_bf16(__bfloat162float(P.rel_coords[(i >> 2) * 2]) * __bfloat162float(P.cpb_w1[u]) +
                                       __bfloat162float(P.rel_coords[(i >> 2) * 2 + 1]) * __bfloat162float(P.cpb_w1[16 + u]));
            a += (h > 0.f ? h : h * 0.f) * __bfloat162float(P.cpb_w2[u * 4 + (i & 3)]);
        }
        tab[i] = __float2bfloat16_rn(16.f * round_bf16(1.f / (1.f + expf(-round_bf16(a)))));
    }
#pragma unroll 1
    for (;;) {
        wg_bar(barid);
        if (t == 0) *next = (int)atomicAdd(g_guard + 2, 1u);
        wg_bar(barid);
        const int win = *next;
        if (win >= NWINDOWS) return;
        const int y0 = 7 * (win / NWS) + 3, x0 = 7 * (win % NWS) + 3;
        auto pixel = [&](int r) { return (size_t)(((y0 + r / 7) % IMG) * IMG + (x0 + r % 7) % IMG) * 192; };
#pragma unroll 1
        for (int i = t; i < TOK * 24; i += 128)
            reinterpret_cast<uint4*>(xs)[i] = reinterpret_cast<const uint4*>(P.x + pixel(i / 24))[i % 24];
#pragma unroll 1
        for (int ph = 0; ph < 2; ph++) {
            const bf* const a = ph ? qkv : xs;
            bf* const d = ph ? xs : qkv;
            const int n = ph ? 192 : 576, pa = ph ? FB_PITCH : 192, pd = ph ? 192 : FB_PITCH;
            wg_bar(barid);
#pragma unroll 1
            for (int col = t; col < n; col += 128) {
                const bf* w = (ph ? P.wo : P.wqkv) + col;
                float acc[TOK];
#pragma unroll
                for (int r = 0; r < TOK; r++) acc[r] = 0.f;
#pragma unroll 1
                for (int k = 0; k < 192; k += 2) {
                    const float w0 = __bfloat162float(w[k * n]), w1 = __bfloat162float(w[(k + 1) * n]);
#pragma unroll
                    for (int r = 0; r < TOK; r++) {
                        const uint32_t v = *reinterpret_cast<const uint32_t*>(a + r * pa + k);
                        acc[r] = fmaf(bf16hi(v), w1, fmaf(bf16lo(v), w0, acc[r]));
                    }
                }
#pragma unroll
                for (int r = 0; r < TOK; r++) d[r * pd + col] = __float2bfloat16_rn(acc[r]);
            }
            wg_bar(barid);
            if (ph) break;
#pragma unroll 1
            for (int i = t; i < TOK * 8; i += 128) {
                bf* const v = qkv + (i % TOK) * FB_PITCH + (i / TOK) * 48;
                float s = 0.f;
#pragma unroll 1
                for (int j = 0; j < 48; j++) s = fmaf(__bfloat162float(v[j]), __bfloat162float(v[j]), s);
                s = round_bf16(1.f / sqrtf(round_bf16(round_bf16(s) + 1e-12f)));
#pragma unroll 1
                for (int j = 0; j < 48; j++) v[j] = __float2bfloat16_rn(__bfloat162float(v[j]) * s);
            }
            wg_bar(barid);
#pragma unroll 1
            for (int i = t; i < TOK * 4; i += 128) {
                const int r = i % TOK, h = i / TOK;
                uint32_t* const q = reinterpret_cast<uint32_t*>(qkv + r * FB_PITCH + h * 48);
                const float tau = round_bf16(expf(round_bf16(fminf(fmaxf(__bfloat162float(P.logit_scale[h]), -100.f), 4.6052f))));
                float v[48], mx = -INFINITY, sum = 0.f;
#pragma unroll
                for (int j = 0; j < 24; j++) { v[2 * j] = bf16lo(q[j]); v[2 * j + 1] = bf16hi(q[j]); }
#pragma unroll 1
                for (int j = 0; j < TOK; j++) {
                    const uint32_t* kk = reinterpret_cast<const uint32_t*>(qkv + j * FB_PITCH + 192 + h * 48);
                    float s = 0.f;
#pragma unroll
                    for (int u = 0; u < 24; u++) s = fmaf(v[2 * u + 1], bf16hi(kk[u]), fmaf(v[2 * u], bf16lo(kk[u]), s));
                    s = round_bf16(round_bf16(s) * tau);
                    s = round_bf16(s + __bfloat162float(tab[min(max(P.rel_idx[r * TOK + j], 0), 168) * 4 + h]));
                    s = round_bf16(s + __bfloat162float(P.mask[(size_t)win * (TOK * TOK) + r * TOK + j]));
                    xs[j * 128 + t] = __float2bfloat16_rn(s);
                    mx = fmaxf(mx, s);
                }
#pragma unroll 1
                for (int j = 0; j < TOK; j++) sum += expf(__bfloat162float(xs[j * 128 + t]) - mx);
#pragma unroll
                for (int j = 0; j < 48; j++) v[j] = 0.f;
#pragma unroll 1
                for (int j = 0; j < TOK; j++) {
                    const uint32_t* vv = reinterpret_cast<const uint32_t*>(qkv + j * FB_PITCH + 384 + h * 48);
                    const float p = round_bf16(expf(__bfloat162float(xs[j * 128 + t]) - mx) / sum);
#pragma unroll
                    for (int u = 0; u < 24; u++) {
                        v[2 * u] = fmaf(p, bf16lo(vv[u]), v[2 * u]);
                        v[2 * u + 1] = fmaf(p, bf16hi(vv[u]), v[2 * u + 1]);
                    }
                }
#pragma unroll
                for (int j = 0; j < 24; j++) q[j] = pack_bf16(v[2 * j], v[2 * j + 1]);
            }
        }
#pragma unroll 1
        for (int r = t >> 5; r < TOK; r += 4) {
            float v[6], m = 0.f, s = 0.f;
#pragma unroll
            for (int j = 0; j < 6; j++) { v[j] = __bfloat162float(xs[r * 192 + j * 32 + lane]); m += v[j]; }
#pragma unroll
            for (int o = 16; o; o >>= 1) m += __shfl_xor_sync(0xffffffffu, m, o);
            m *= 1.f / 192.f;
#pragma unroll
            for (int j = 0; j < 6; j++) s = fmaf(v[j] - m, v[j] - m, s);
#pragma unroll
            for (int o = 16; o; o >>= 1) s += __shfl_xor_sync(0xffffffffu, s, o);
            s = round_bf16(sqrtf(round_bf16(round_bf16(s * (1.f / 192.f)) + 1e-5f)));
            m = round_bf16(m);
#pragma unroll
            for (int j = 0; j < 6; j++) P.out[pixel(r) + j * 32 + lane] = __float2bfloat16_rn(round_bf16(v[j] - m) / s);
        }
    }
}

__global__ void __launch_bounds__(NTHREADS, 1)
swin_window_attn_kernel(const Params P, const __grid_constant__ CUtensorMap xmap, const __grid_constant__ CUtensorMap xmap4,
                        const __grid_constant__ CUtensorMap xmap3,
                        const __grid_constant__ CUtensorMap omap, const __grid_constant__ CUtensorMap wmap,
                        const __grid_constant__ CUtensorMap smap, const __grid_constant__ CUtensorMap omapb,
                        const __grid_constant__ CUtensorMap xmapa, const __grid_constant__ CUtensorMap xmapb,
                        const __grid_constant__ CUtensorMap smap3, const __grid_constant__ CUtensorMap wraw) {
    extern __shared__ __align__(1024) uint8_t smem[];
    constexpr uint32_t sbase = 1024;
    if (smem_u32(smem) != sbase) return;
    const int tid = threadIdx.x;
    const int wg = __shfl_sync(0xffffffffu, tid >> 7, 0);
    const int warp = __shfl_sync(0xffffffffu, (tid >> 5) & 3, 0);
    const int lane = tid & 31;
    const int g = lane >> 2, c = lane & 3;

    TR(26, wg);
    const bool attn = (int)blockIdx.x < 2 * P.npair;
    const int pair = blockIdx.x >> 1, half = blockIdx.x & 1;
    const int nwin = P.nq + (pair < P.nr ? 1 : 0);
    const int ntiles = (nwin * TOK + 63) >> 6;
    const uint32_t bars = sbase + SM_BAR;
    const int t0 = min(warp * 16 + g, TOK - 1), t1 = min(warp * 16 + g + 8, TOK - 1);
    int ridx[26];
    uint32_t rc, w2[16];
    uint4 w1[4];
    if (attn && (wg == 1 || wg == 2)) {
        rc = reinterpret_cast<const uint32_t*>(P.rel_coords)[min(tid - 128, 168)];
#pragma unroll
        for (int i = 0; i < 4; i++) w1[i] = reinterpret_cast<const uint4*>(P.cpb_w1)[i];
#pragma unroll
        for (int u = 0; u < 16; u++) w2[u] = reinterpret_cast<const uint32_t*>(P.cpb_w2)[2 * u + half];
#pragma unroll
        for (int rh = 0; rh < 2; rh++) {
            const int* ri = P.rel_idx + (rh ? t1 : t0) * TOK;
#pragma unroll
            for (int j = 0; j < 12; j++) ridx[13 * rh + j] = ri[8 * (j >> 1) + 2 * c + (j & 1)];
            ridx[13 * rh + 12] = ri[48];
        }
    }
    {
        if (tid == 416) {
            const CUtensorMap* maps[4] = {attn ? &smap : &omap, &smap3, &xmapa, &xmapb};
#pragma unroll
            for (int i = 0; i < 4; i++) asm volatile("prefetch.tensormap [%0];\n" :: "l"(reinterpret_cast<uint64_t>(maps[i])) : "memory");
        }
        if (tid == 384) {
            for (int b = 0; b < 4; b++) {
                mbar_init(bars + B_XFULL + b * 8, 2);
                mbar_init(bars + B_QKRAW + b * 8, 4);
                mbar_init(bars + B_VRAW + b * 8, 4);
                mbar_init(bars + B_VFREE + b * 8, 2);
                mbar_init(bars + B_QKFREE + b * 8, 4);
                mbar_init(bars + B_ODONE + b * 8, 4);
            }
            mbar_init(bars + B_MFULL, 1);
            sts32(bars + B_MSTATE, 0);
            mbar_init(bars + B_MCONS, 4);
            mbar_init(bars + B_WFULL, 2);
            mbar_init(bars + B_WRAW, 1);
            mbar_init(bars + B_XCONS, 4);
            for (int b = 0; b < 4; b++) mbar_init(bars + B_STORED + b * 8, 1);
            for (int b = 0; b < 6; b++) {
                mbar_init(sbase + SM_PBAR + b * 8, 1);
                mbar_init(sbase + SM_PBAR + 48 + b * 8, PSTORE ? 1 : 4);
                mbar_init(sbase + SM_PBAR + 104 + b * 8, 4);
            }
            mbar_init(sbase + SM_PBAR + 96, 13);
            asm volatile("fence.mbarrier_init.release.cluster;\n" ::: "memory");
        }
        if (wg == 3) {
            if (attn) *reinterpret_cast<uint4*>(smem + SM_V + warp * V_STRIDE + (lane < 16 ? lane * 16 : V_STRIDE - 64 + (lane & 3) * 16)) = make_uint4(0, 0, 0, 0);
            fence_async_smem();
        }
        __syncthreads();
        TR(26, 4 + wg);
            if (attn && tid == 0) {
                mbar_arrive_expect_tx(bars + B_WRAW, 2 * 192 * O_PITCH);
#pragma unroll
                for (int i = 0; i < 4; i++) {
                    const int q = (i + pair) & 3;
                    tma_3d(sbase + q * 96 * O_PITCH, &wraw, bars + B_WRAW, 0, 2 * (q >> 1) + half, (q & 1) * 96);
                }
                int wh = 0, ww = pair;
#pragma unroll
                for (int j = 0; j < NEARLY; j++) {
                    if (ww < NWS - 1) {
                        const uint32_t bar = bars + B_XFULL + (j ? j - 1 : 0) * 8;
                        if (j >= 2) mbar_arrive(bar);
                        mbar_arrive_expect_tx(bar, 3 * XCH);
#pragma unroll
                        for (int ch = 0; ch < 3; ch++)
                            tma_3d(sbase + SM_QK + ((j + 3) & 3) * XCH + ch * QK_CHUNK, &xmap, bar, ch * 64, 7 * ww + 3, 7 * wh + 3);
                    }
                    ww += P.npair; if (ww >= NWS) { ww -= NWS; wh++; }
                    if (j == 1) {
                        mbar_arrive_expect_tx(bars + B_MFULL, 4816);
                        asm volatile("cp.async.bulk.shared::cluster.global.mbarrier::complete_tx::bytes [%0], [%1], 4816, [%2];\n"
                                     :: "r"(sbase + SM_MASK), "l"(reinterpret_cast<const char*>(P.mask) + (((uint32_t)pair * 4802u) & ~15u)),
                                        "r"(bars + B_MFULL) : "memory");
                        mbar_arrive_expect_tx(bars + B_WFULL, 5 * W_ATOM);
#pragma unroll
                        for (int a = 1; a < 6; a++)
                            tma_2d(sbase + SM_WV + a * W_ATOM, &wmap, bars + B_WFULL, 384 + half * 96 + a * 16, 0);
                    }
                }
            }
        __syncwarp();
        TR(26, 13);
    }

    auto permute_w = [&]() {
        uint4 w[3][4];
        TR(26, 16 + wg);
        mbar_wait(bars + B_WRAW, 0);
        TR(26, 20 + wg);
#pragma unroll
        for (int it = 0; it < 3; it++) {
            const int o = ((tid >> 5) * 3 + it) * 4 + (lane >> 3);
            const uint8_t* src = smem + ((o / 6) * 8 + (lane & 7)) * O_PITCH + (o % 6) * 16;
#pragma unroll
            for (int m = 0; m < 4; m++) w[it][m] = *reinterpret_cast<const uint4*>(src + (m >> 1) * 192 * O_PITCH + (m & 1) * 96);
        }
        asm volatile("bar.sync 2, 384;\n" ::: "memory");
        if (tid == 0) {
            fence_async_smem();
            TR(26, 24);
            mbar_arrive_expect_tx(bars + B_WFULL, W_ATOM);
            tma_2d(sbase + SM_WV, &wmap, bars + B_WFULL, 384 + half * 96, 0);
        }
#pragma unroll
        for (int it = 0; it < 3; it++) {
            const int o = ((tid >> 5) * 3 + it) * 4 + (lane >> 3);
            const uint32_t d = sbase + (o % 6) * 2 * W_ATOM + ((o / 6) * 8 + (lane & 7)) * 32 + ((lane >> 2) & 1) * 16;
            sts128(d, bf2h(w[it][0].x), bf2h(w[it][1].x), bf2h(w[it][2].x), bf2h(w[it][3].x));
            sts128(d ^ 16, bf2h(w[it][0].y), bf2h(w[it][1].y), bf2h(w[it][2].y), bf2h(w[it][3].y));
            sts128(d + W_ATOM, bf2h(w[it][0].z), bf2h(w[it][1].z), bf2h(w[it][2].z), bf2h(w[it][3].z));
            sts128((d ^ 16) + W_ATOM, bf2h(w[it][0].w), bf2h(w[it][1].w), bf2h(w[it][2].w), bf2h(w[it][3].w));
        }
    };
    static_assert(2 * 192 * O_PITCH <= 13 * W_ATOM, "raw weights");
    const uint32_t nfinish = gridDim.x + 2 * P.npair;
#define PROJ_SCHEDULE                                                                                   \
    int bid = blockIdx.x;                                                                               \
    asm volatile("" : "+r"(bid));                      \
    const bool at = bid < 2 * P.npair;                                                                  \
    const int tile0 = at ? P.t1 + bid : bid - 2 * P.npair;                                              \
    const int tstep = at ? 2 * P.npair : (int)gridDim.x - 2 * P.npair;                                  \
    const int tend = at ? TILES : P.t1;
    if (wg == 3) {
        asm volatile("setmaxnreg.dec.sync.aligned.u32 %0;\n" :: "n"(REG_H));
        if (warp == 1 && attn) {
            const uint16_t mlast = reinterpret_cast<const uint16_t*>(P.mask)[NWINDOWS * TOK * TOK - 1];
            const uint32_t ma = sbase + SM_MASK + lane * 16, mb = sbase + SM_MASK + min(288 + lane, 300) * 16;
            uint32_t ph = 0;
#pragma unroll 1
            for (int k = 0; k < nwin; k++) {
                mbar_wait(bars + B_MFULL, k & 1);
                uint32_t acc = 0;
#pragma unroll
                for (int i = 0; i < 10; i += MRND) {
                    uint32_t w[MRND][4];
#pragma unroll
                    for (int j = 0; j < MRND; j++) if (i + j < 10) lds128(w[j], i + j < 9 ? ma + (i + j) * 512 : mb);
#pragma unroll
                    for (int j = 0; j < MRND; j++) if (i + j < 10) acc |= w[j][0] | w[j][1] | w[j][2] | w[j][3];
                    asm volatile("" : "+r"(acc) :: "memory");
                }
                const uint32_t nz = __any_sync(0xffffffffu, (acc & 0x7FFF7FFFu) != 0) ? 1 : 0;
                if (lane == 0) asm volatile("st.volatile.shared.b32 [%0], %1;\n" :: "r"(bars + B_MSTATE), "r"(2 * k + 2 - nz) : "memory");
                if (nz) { mbar_wait(bars + B_MCONS, ph); ph ^= 1; fence_async_smem(); }
                if (k + 1 < nwin && elect_one()) {
                    const int win = pair + (k + 1) * P.npair;
                    uint32_t bytes = 4816;
                    if (win == NWINDOWS - 1) {
                        bytes = 4800;
                        asm volatile("st.shared.u16 [%0], %1;\n" :: "r"(sbase + SM_MASK + 4800), "h"(mlast) : "memory");
                    }
                    TR(25, k + 1);
                    mbar_arrive_expect_tx(bars + B_MFULL, bytes);
                    asm volatile("cp.async.bulk.shared::cluster.global.mbarrier::complete_tx::bytes [%0], [%1], %2, [%3];\n"
                                 :: "r"(sbase + SM_MASK),
                                    "l"(reinterpret_cast<const char*>(P.mask) + (((uint32_t)win * 4802u) & ~15u)),
                                    "r"(bytes), "r"(bars + B_MFULL) : "memory");
                    if (MPF && half == (k & 1) && k + 1 + MPF < nwin)
                        asm volatile("cp.async.bulk.prefetch.L2.global [%0], %1;\n"
                                     :: "l"(reinterpret_cast<const char*>(P.mask) + (((uint32_t)(win + MPF * P.npair) * 4802u) & ~15u)),
                                        "r"(4800) : "memory");
                }
                __syncwarp();
            }
        }
        if (!elect_one()) return;
        if (warp == 0) {
          if (attn) {
            const int kmax = (64 * ntiles + 63) / TOK;
            int wh = 0, ww = pair;
            int ph2 = (pair + PF_DIST * P.npair) / NWS, pw2 = pair + PF_DIST * P.npair - ph2 * NWS;
#pragma unroll 1
            for (int k = -4; k + 4 <= kmax; k++) {
                const int row0 = (k + 4) * TOK;
                const uint32_t dst = sbase + SM_QK + ((k + 3) & 3) * XCH, bar = bars + B_XFULL + ((row0 >> 6) & 3) * 8;
                const bool alone = (row0 & 63) >= 64 - TOK && (row0 & 63) < TOK;
                const int x0 = 7 * ww + 3, y0 = 7 * wh + 3;
                const bool done = k < NEARLY - 4 && ww < NWS - 1;
                if (k >= 0) mbar_wait(bars + B_QKFREE + ((k + 3) & 3) * 8, (k >> 2) & 1);
                if (alone && !done) mbar_arrive(bar);
                if (row0 >= 64 * ntiles || ((EXP & 32) && k >= 0)) {
                    mbar_arrive(bar);
                    continue;
                }
                TR(20, k + 4);
                const bool inner = wh < NWS - 1 && ww < NWS - 1;
                if (done) {
                } else if (XSPLIT && inner && (row0 & 63) >= 64 - 21) {
                    const uint32_t bar2 = bars + B_XFULL + (((row0 >> 6) + 1) & 3) * 8;
                    mbar_arrive_expect_tx(bar, 3 * 21 * 128);
#pragma unroll
                    for (int ch = 0; ch < 3; ch++) tma_3d(dst + ch * QK_CHUNK, &xmapa, bar, ch * 64, x0, y0);
                    asm volatile("mbarrier.expect_tx.relaxed.cta.shared::cta.b64 [%0], %1;\n" :: "r"(bar2), "r"(3 * 28 * 128) : "memory");
#pragma unroll
                    for (int ch = 0; ch < 3; ch++) tma_3d(dst + ch * QK_CHUNK + 21 * 128, &xmapb, bar2, ch * 64, x0, y0 + 3);
                } else if (inner) {
                    mbar_arrive_expect_tx(bar, 3 * XCH);
#pragma unroll
                    for (int ch = 0; ch < 3; ch++) tma_3d(dst + ch * QK_CHUNK, &xmap, bar, ch * 64, x0, y0);
                } else if (ww < NWS - 1) {
                    mbar_arrive_expect_tx(bar, 3 * XCH);
#pragma unroll
                    for (int ch = 0; ch < 3; ch++) {
                        tma_3d(dst + ch * QK_CHUNK, &xmapb, bar, ch * 64, x0, y0);
                        tma_3d(dst + ch * QK_CHUNK + 28 * 128, &xmapa, bar, ch * 64, x0, 0);
                    }
                } else {
                    mbar_arrive_expect_tx(bar, 3 * XCH);
                    const int x1 = (ww == NWS - 1) ? 0 : x0 + 4;
#pragma unroll 1
                    for (int i = 0; i < 7; i++) {
                        const int y = (y0 + i >= IMG) ? y0 + i - IMG : y0 + i;
#pragma unroll
                        for (int ch = 0; ch < 3; ch++) {
                            tma_3d(dst + ch * QK_CHUNK + i * 896, &xmap4, bar, ch * 64, x0, y);
                            tma_3d(dst + ch * QK_CHUNK + i * 896 + 512, &xmap3, bar, ch * 64, x1, y);
                        }
                    }
                }
                if (NOPF) {
                } else if (half == 0) {
                    if (ph2 < NWS) {
#pragma unroll
                        for (int ch = 0; ch < 3; ch++)
                            asm volatile("cp.async.bulk.prefetch.tensor.3d.L2.global.tile [%0, {%1, %2, %3}];\n"
                                         :: "l"(reinterpret_cast<uint64_t>(&xmap)), "r"(ch * 64), "r"(7 * pw2 + 3), "r"(7 * ph2 + 3)
                                         : "memory");
                    }
                }
                if (k + 5 < nwin) {
                    ww += P.npair; if (ww >= NWS) { ww -= NWS; wh++; }
                }
                pw2 += P.npair; if (pw2 >= NWS) { pw2 -= NWS; ph2++; }
            }
            mbar_wait(sbase + SM_PBAR + 96, 0);
            fence_async_smem();
          }
            PROJ_SCHEDULE
            int st = 0, ready = -1;
            uint32_t ph = 1;
#pragma unroll 1
            for (int t = tile0; t < tend; t += tstep) {
                const int p0 = (t < TILES_A) ? SEG_B + 64 * t : 64 * (t - TILES_A);
                const int w1 = (t < TILES_A) ? min((64 * t + 63) / (7 * IMG), NWS - 1) : NWS - 1;
                if (ready < w1) {
                    ready = max(ready, w1 - 2);
#pragma unroll 1
                    while (ready < w1) {
                        ready++;
#pragma unroll 1
                        for (uint32_t n = 0; n < (1u << 22); n++) {
                            uint32_t a;
                            asm volatile("ld.acquire.gpu.global.u32 %0, [%1];\n" : "=r"(a) : "l"(g_cnt + ready) : "memory");
                            if (a >= P.need) break;
                            __nanosleep(64);
                        }
                    }
                    asm volatile("fence.proxy.async.global;\n" ::: "memory");
                }
                mbar_wait(sbase + SM_PBAR + 48 + st * 8, ph);
                mbar_arrive_expect_tx(sbase + SM_PBAR + st * 8, STAGE_BYTES);
#pragma unroll
                for (int ch = 0; ch < 3; ch++)
                    tma_2d(sbase + SM_STAGE + st * STAGE_BYTES + ch * 8192, &omap, sbase + SM_PBAR + st * 8, ch * 64, p0);
                if (++st == 6) { st = 0; ph ^= 1; }
            }
            finish(nfinish);
        } else if (!attn) {
        } else if (warp == 1) {
        } else if (warp == 2) {
            int wh = 0, ww = pair;
#pragma unroll 1
            for (int k = 0; k < nwin; k++) {
                mbar_wait(bars + B_STORED + (k & 1) * 8, (k >> 1) & 1);
                mbar_arrive(bars + B_PUBD + (k & 1) * 8);
                asm volatile("red.release.gpu.global.add.u32 [%0], 1;\n" :: "l"(g_cnt + wh) : "memory");
                TR(24, k);
                ww += P.npair; if (ww >= NWS) { ww -= NWS; wh++; }
            }
            finish(nfinish);
        } else {
            for (int t = 0; t < 3; t++) mbar_arrive_n(bars + B_VFREE + t * 8, 2);
            int wh = 0, ww = pair;
#pragma unroll 1
            for (int k = 0; k < nwin; k++) {
                const uint32_t src = sbase + SM_V + (k & 3) * V_STRIDE;
                const int x0 = 7 * ww + 3, y0 = 7 * wh + 3;
                mbar_wait(bars + B_ODONE + (k & 3) * 8, (k >> 2) & 1);
                fence_async_smem();
                TR(22, k);
#if !(EXP & 4)
                tma_store_4d(&smap, src, 0, half, x0, y0);
                tma_store_4d(&smap3, src + 28 * O_PITCH + 64, 0, half, x0, wh == NWS - 1 ? 0 : y0 + 4);
#endif
                if (ww == NWS - 1) {
#pragma unroll 1
                    for (int i = 0; i < 7; i++) {
                        char* const d = reinterpret_cast<char*>(P.out) + (uint32_t)((y0 + i >= IMG ? y0 + i - IMG : y0 + i) * IMG) * 384u + half * 192;
#pragma unroll
                        for (int j = 0; j < 3; j++)
                            asm volatile("cp.async.bulk.global.shared::cta.bulk_group [%0], [%1], 192;\n"
                                         :: "l"(d + j * 384), "r"(src + (7 * i + 4 + j) * O_PITCH + (i >= 4 ? 64 : 0)) : "memory");
                    }
                }
                asm volatile("cp.async.bulk.commit_group;\n" ::: "memory");
                asm volatile("cp.async.bulk.wait_group.read 0;\n" ::: "memory");
                {
                    const int row0 = (k + 4) * TOK;
                    mbar_arrive_n(bars + B_VFREE + ((row0 >> 6) & 3) * 8, ((row0 & 63) >= 64 - TOK && (row0 & 63) < TOK) ? 2 : 1);
                }
                TR(23, k);
                asm volatile("cp.async.bulk.wait_group 0;\n" ::: "memory");
                asm volatile("fence.proxy.async.global;\n" ::: "memory");
                mbar_wait(bars + B_PUBD + (k & 1) * 8, ((k >> 1) + 1) & 1);
                mbar_arrive(bars + B_STORED + (k & 1) * 8);
                ww += P.npair; if (ww >= NWS) { ww -= NWS; wh++; }
            }
            mbar_arrive(sbase + SM_PBAR + 96);
        }
        if (PSTORE && warp == 1) {
            PROJ_SCHEDULE
            int st = 0, prev = -1;
            uint32_t ph = 0;
            if (bid == gridDim.x - 1) { g_guard[2] = 0; __threadfence(); }
#pragma unroll 1
            for (int t = tile0; t < tend; t += tstep) {
                const int p0 = (t < TILES_A) ? SEG_B + 64 * t : 64 * (t - TILES_A);
                mbar_wait(sbase + SM_PBAR + 104 + st * 8, ph);
                fence_async_smem();
#pragma unroll
                for (int ch = 0; ch < 3; ch++)
                    asm volatile("cp.async.bulk.tensor.2d.global.shared::cta.tile.bulk_group [%0, {%2, %3}], [%1];\n"
                                 :: "l"(reinterpret_cast<uint64_t>(t < TILES_A ? &omap : &omapb)),
                                    "r"(sbase + SM_STAGE + st * STAGE_BYTES + ch * 8192), "r"(ch * 64), "r"(p0) : "memory");
                asm volatile("cp.async.bulk.commit_group;\n" ::: "memory");
                if (prev >= 0) {
                    asm volatile("cp.async.bulk.wait_group.read 1;\n" ::: "memory");
                    mbar_arrive(sbase + SM_PBAR + 48 + prev * 8);
                }
                prev = st;
                if (++st == 6) { st = 0; ph ^= 1; }
            }
            asm volatile("cp.async.bulk.wait_group 0;\n" ::: "memory");
            asm volatile("red.relaxed.gpu.global.add.u32 [%0], %1;\n" :: "l"(g_guard), "r"(bid == 0 ? 257 - gridDim.x : 1) : "memory");
            TR(30, 0);
        }
        return;
    }
    bool bad = false;
    if (!attn) {
        asm volatile("setmaxnreg.inc.sync.aligned.u32 160;\n");
        uint32_t lo = 0x7F807F80u, hi = 0;
#pragma unroll 1
        for (int i = (blockIdx.x - 2 * P.npair) * 384 + tid; i < 192 * 96; i += (gridDim.x - 2 * P.npair) * 384) {
            const bool o = i >= 192 * 72;
            const uint4 w = o ? reinterpret_cast<const uint4*>(P.wo)[i - 192 * 72] : reinterpret_cast<const uint4*>(P.wqkv)[i];
            const uint32_t m = __vmaxu2(__vmaxu2(w.x & 0x7FFF7FFFu, w.y & 0x7FFF7FFFu), __vmaxu2(w.z & 0x7FFF7FFFu, w.w & 0x7FFF7FFFu));
            lo = __vminu2(lo, m);
            hi = __vmaxu2(hi, m + (o ? 0x02000200u : 0u));
        }
        bad = __vminu2(lo, 0x38803880u) != 0x38803880u || __vmaxu2(hi, 0x42004200u) != 0x42004200u;
    } else if (wg == 0) {
        asm volatile("setmaxnreg.inc.sync.aligned.u32 %0;\n" :: "n"(REG_G));
        float qs = 1.f;
        if (c < 2) qs = round_bf16(expf(round_bf16(fminf(fmaxf(__bfloat162float(P.logit_scale[2 * half + c]), -100.f), 4.6052f)))) * LOG2E;
        uint32_t xa[8][4];
        uint32_t qk[2][48], vv[24];
        uint32_t rho = warp * 16 + (lane & 15), rq = warp * 16 + g;
        uint32_t rx = rho + 3 * TOK - (rho >= TOK ? 4 * TOK : 0);
        uint32_t hi = lane >> 4, lane0 = lane == 0, c2 = 2 * c;
        asm volatile("" : "+r"(hi), "+r"(lane0), "+r"(c2));
        auto row_addr = [&](uint32_t (&ax)[4], uint32_t r) {
            ax[0] = sbase + SM_QK + r * 128 + (((r & 7) ^ hi) << 4);
#pragma unroll
            for (int i = 1; i < 4; i++) ax[i] = ax[0] ^ (32 * i);
        };
#define XADDR(ax, s) ((ax)[((s) & 3) ^ (((s) >> 1) & 2)] + ((s) >> 2) * QK_CHUNK)
        uint64_t descW = make_desc(sbase, W_ATOM, 256, 3);
        const uint32_t zero = (uint32_t)P.z1;
        const uint32_t vbase = sbase + SM_V + (lane >> 4) * GRP;
        uint32_t ones = 0x3C003C00u | zero, ones2 = ones | (zero >> 1);
        asm volatile("" : "+r"(ones), "+r"(ones2));
        const uint32_t mh[2] = {0xFFFF0000u, 0xFFFF0000u}, ml[2] = {0x10000u, 0x10000u};
        uint32_t raw[48], xb[4][4];
        auto cvt = [&](auto& dst, int d0, const uint32_t (&raw)[48], int s0) {
#pragma unroll
            for (int s = 0; s < 4; s++) {
#pragma unroll
                for (int i = 0; i < 4; i++)
                    dst[d0 + s][i] = pack_f16(__uint_as_float(raw[4 * (s0 + s) + i] * ml[i & 1]), __uint_as_float(raw[4 * (s0 + s) + i] & mh[i & 1]));
                reg_fence(dst[d0 + s]);
            }
        };
        uint32_t ax[4];
        auto load_x = [&](int s0) {
#pragma unroll
            for (int s = s0; s < s0 + 4; s++) ldsm_x4(reinterpret_cast<uint32_t (&)[4]>(raw[4 * s]), XADDR(ax, s));
        };
        auto next_x = [&]() {
            row_addr(ax, rx);
            rx += 64;
            if (rx >= 4 * TOK) rx -= 4 * TOK;
        };
        permute_w();
        TR(26, 10);
        mbar_wait(bars + B_XFULL, 0);
        next_x();
        load_x(0); load_x(4); load_x(8);
        cvt(xa, 0, raw, 0); cvt(xa, 4, raw, 4); cvt(xb, 0, raw, 8);
        __syncwarp();
        mbar_arrive_if(bars + B_QKFREE + 24, lane0);
        TR(26, 8);
        asm volatile("bar.sync 7, 384;\n" ::: "memory");
        fence_async_smem();
        TR(26, 9);
        wgmma_fence();
        mma_qk_first<SM_WA, 0>(qk[0], xa, descW);
        mma_qk_next<SM_WA + 2048, 4>(qk[0], xa, descW);
        mma_qk_next<SM_WA + 4096, 0>(qk[0], xb, descW);
        wgmma_commit();
        TR(26, 11);
        asm volatile("bar.sync 11, 384;\n" ::: "memory");
        fence_async_smem();
        TR(26, 12);
        wgmma_fence();
        mma_v_first<SM_WV, 0>(vv, xa, descW);
        mma_v_next<SM_WV + 2048, 4>(vv, xa, descW);
        wgmma_commit();
        wgmma_wait<0>();
        uint32_t xok = 0, range = 0;
        auto body = [&](auto U_, int t) {
            constexpr int U = decltype(U_)::value;
            uint32_t (&cur)[48] = qk[U];
            uint32_t (&nxt)[48] = qk[U ^ 1];
            descW += P.z1;
            const uint32_t bt = bars + (t & 3) * 8, pt = (t >> 2) & 1;
            TR(1, t);
            wgmma_fence();
            mma_v_next<SM_WV + 4096, 0>(vv, xb, descW);
            wgmma_commit();
            next_x();
            mbar_wait_unless(xok, bars + ((t + 1) & 3) * 8 + B_XFULL, ((t + 1) >> 2) & 1);
            TR(2, t);
            load_x(0);
            load_x(4);
            uint32_t av = vbase + rho * 16 + ((rho * 1338) >> 16) * (V_STRIDE - GRP);
            uint32_t aq[2];
            aq[0] = sbase + SM_QK + rq * 128 + (((rq & 7) ^ c2) << 4);
            aq[1] = aq[0] + 1024;
            if (rq >= 4 * TOK - 8) aq[1] = (aq[1] - QK_CHUNK) ^ 64;
            rho += 64;
            if (rho >= 4 * TOK) rho -= 4 * TOK;
            rq += 64;
            if (rq >= 4 * TOK) rq -= 4 * TOK;
            asm volatile("" : "+r"(av), "+r"(aq[0]), "+r"(aq[1]), "+r"(rho), "+r"(rq));
            cvt(xa, 0, raw, 0);
            wgmma_fence();
            mma_qk_first<SM_WA, 0>(nxt, xa, descW);
            wgmma_commit();
            load_x(8);
            __syncwarp();
            mbar_arrive_if(bars + B_XCONS, lane0);
            const uint32_t vok = mbar_test(bt + B_VFREE, pt);
            cvt(xa, 4, raw, 4);
            TR(5, t);
            wgmma_fence();
            mma_qk_next<SM_WA + 2048, 4>(nxt, xa, descW);
            wgmma_commit();
            wgmma_wait<2>();
            reg_fence(cur);
            reg_fence(vv);
            TR(6, t);
            mbar_wait_unless(vok, bt + B_VFREE, pt);
            if (U == 0 && t == 2) asm volatile("bar.sync 3, 384;\n" ::: "memory");
#pragma unroll
            for (int p = 0; p < 6; p++)
                stsm_x4(av + (p < 3 ? 2 * p : 2 * p + 1) * GRP, vv[4 * p], vv[4 * p + 1], vv[4 * p + 2], vv[4 * p + 3]);
            stsm_x2(av + 6 * GRP, ones, ones2);
            __syncwarp();
            mbar_arrive_if(bt + B_VRAW, lane0);
            const uint32_t cok = mbar_test(bars + B_XCONS, U);
            TR(4, t);
            cvt(xb, 0, raw, 8);
            uint32_t ss[4];
#pragma unroll
            for (int i = 0; i < 4; i++) ss[i] = hmul2_f16(cur[i], cur[i]);
#pragma unroll
            for (int i = 4; i < ((EXP & 16) ? 4 : 48); i++) ss[i & 3] = hfma2_f16(cur[i], cur[i], ss[i & 3]);
            ss[0] = hadd2_f16(ss[0], ss[2]);
            ss[1] = hadd2_f16(ss[1], ss[3]);
            const float s0 = f16lo(ss[0]) + f16hi(ss[0]) + 1e-12f, s1 = f16lo(ss[1]) + f16hi(ss[1]) + 1e-12f;
            range = __viaddmax_u32(__float_as_uint(s0), 0u - SS_MIN, __viaddmax_u32(__float_as_uint(s1), 0u - SS_MIN, range));
            const float f0 = rsqrt_ftz(s0) * qs, f1 = rsqrt_ftz(s1) * qs;
            uint32_t f2[2] = {pack_f16_sat(f0, f0), pack_f16_sat(f1, f1)};
            reg_fence(f2);
            sched_fence16(zero, xb, f2[0], f2[1]);
            wgmma_fence();
            mma_v_first<SM_WV, 0>(vv, xa, descW);
            wgmma_commit();
            mbar_wait_unless_dep(cok, bars + B_XCONS, U, zero, f2[0], f2[1], aq[0], aq[1]);
            TR(7, t);
#pragma unroll
            for (int u = 0; u < 6; u++)
#pragma unroll
                for (int r = 0; r < 2; r++)
                    sts128((aq[r] ^ ((u & 1) * 16 + (u & 2) * 32)) + (u >> 1) * QK_CHUNK,
                           hmul2_f16(cur[8 * u + r], f2[r]), hmul2_f16(cur[8 * u + 2 + r], f2[r]),
                           hmul2_f16(cur[8 * u + 4 + r], f2[r]), hmul2_f16(cur[8 * u + 6 + r], f2[r]));
            __syncwarp();
            mbar_arrive_if(bt + B_QKRAW, lane0);
            TR(3, t);
            wgmma_fence();
            mma_v_next<SM_WV + 2048, 4>(vv, xa, descW);
            wgmma_commit();
            xok = mbar_test(bars + ((t + 2) & 3) * 8 + B_XFULL, ((t + 2) >> 2) & 1);
            mma_qk_next<SM_WA + 4096, 0>(nxt, xb, descW);
            wgmma_commit();
            TR(0, t + 1);
            wgmma_wait<1>();
        };
        for (int t = 0;; t += 2) {
            body(std::integral_constant<int, 0>(), t);
            if (t + 1 >= ntiles) { wgmma_wait<0>(); reg_fence(qk[1]); break; }
            body(std::integral_constant<int, 1>(), t + 1);
            if (t + 2 >= ntiles) { wgmma_wait<0>(); reg_fence(qk[0]); break; }
        }
        reg_fence(vv);
        bad = range >= F32_INF - SS_MIN;
        wg_bar(2);
        asm volatile("setmaxnreg.dec.sync.aligned.u32 160;\n");
    } else {
        if (REG_A > 128) asm volatile("setmaxnreg.inc.sync.aligned.u32 %0;\n" :: "n"(REG_A));
        if (REG_A < 128) asm volatile("setmaxnreg.dec.sync.aligned.u32 %0;\n" :: "n"(REG_A));
        {
            const float c0 = bf16lo(rc), c1 = bf16hi(rc);
            float a0 = 0.f, a1 = 0.f;
#pragma unroll
            for (int u = 0; u < 16; u++) {
                const uint32_t p = reinterpret_cast<const uint32_t*>(w1)[u >> 1], q = reinterpret_cast<const uint32_t*>(w1)[8 + (u >> 1)];
                float h = round_bf16(c0 * ((u & 1) ? bf16hi(p) : bf16lo(p)) + c1 * ((u & 1) ? bf16hi(q) : bf16lo(q)));
                h = fmaxf(h, 0.f);
                a0 += h * bf16lo(w2[u]);
                a1 += h * bf16hi(w2[u]);
            }
            const float s0 = round_bf16(__fdividef(1.f, 1.f + expf(-round_bf16(a0))));
            const float s1 = round_bf16(__fdividef(1.f, 1.f + expf(-round_bf16(a1))));
            if (tid - 128 < 169) sts32(sbase + SM_TAB + (tid - 128) * 4, pack_f16(16.f * LOG2E * s0, 16.f * LOG2E * s1));
        }
        permute_w();
        asm volatile("bar.arrive 7, 384;\n" ::: "memory");
        {
            mbar_wait(bars + B_WFULL, 0);
#pragma unroll 1
            for (int i = 0; i < 9 - 9 * T_NOWV; i++) {
                uint4* q = reinterpret_cast<uint4*>(smem + SM_WV + (tid - 128) * 16 + i * 4096);
                const uint4 w = *q;
                *q = make_uint4(bf2h(w.x), bf2h(w.y), bf2h(w.z), bf2h(w.w));
            }
            asm volatile("bar.arrive 11, 384;\n" ::: "memory");
        }
        asm volatile("bar.sync 1, 256;\n" ::: "memory");
        uint32_t bias[28];
        {
            const uint32_t* tab = reinterpret_cast<const uint32_t*>(smem + SM_TAB);
#pragma unroll
            for (int rh = 0; rh < 2; rh++) {
#pragma unroll
                for (int j = 0; j < 6; j++) {
                    const uint32_t lo = tab[min(max(ridx[13 * rh + 2 * j], 0), 168)];
                    const uint32_t hi = tab[min(max(ridx[13 * rh + 2 * j + 1], 0), 168)];
                    bias[2 * j + rh]      = prmt(lo, hi, 0x5410);
                    bias[14 + 2 * j + rh] = prmt(lo, hi, 0x7632);
                }
                const uint32_t l = (c == 0) ? tab[min(max(ridx[13 * rh + 12], 0), 168)] : 0xFC00FC00u;
                bias[12 + rh] = (l & 0xFFFFu) | 0xFC000000u;
                bias[26 + rh] = (l >> 16) | 0xFC000000u;
            }
        }
        reg_fence(bias);
        asm volatile("bar.arrive 3, 384;\n" ::: "memory");
        const bool ov = warp * 16 + (lane & 15) < TOK;
        const int orow = warp * 16 + (lane & 15);
        const uint32_t orel = sbase + (ov ? SM_V + orow * O_PITCH + (orow >= 28 ? 64 : 0) : SM_DUMP + (lane & 7) * 16) + (lane >> 4) * 16;
        const uint32_t omul = ov ? V_STRIDE : 0;
        const uint64_t descK0 = make_desc(sbase + SM_QK, 16, 1024, 1);
        const uint64_t descV0 = make_desc(sbase + SM_V, 128, GRP, 0);
        const uint32_t mrel = sbase + SM_MASK + t0 * 98 + c * 4;
        const uint32_t mrow = (warp < 3) ? 784 : 0;
        const uint32_t pmask = (c == 0) ? 0xFFFFu : 0u;

        uint32_t mstate = 0;
        const uint32_t barw = bars + (wg - 1) * 8;
        const uint64_t descKw = descK0 + (uint64_t)((wg - 1) * (XCH >> 4)), descVw = descV0 + (uint64_t)((wg - 1) * (V_STRIDE >> 4));
        uint32_t oa = orel + (wg - 1) * omul;
        const uint32_t oflip = oa ^ (oa + 2 * omul);
        uint32_t qok = 0;
        const uint32_t zero = (uint32_t)P.z1;
        auto window = [&](auto IT_, int k) {
            constexpr int IT = decltype(IT_)::value;
            const uint32_t bar = barw + 16 * IT;
            const int tl = (k * TOK + TOK - 1) >> 6, tn = ((k + 2) * TOK + TOK - 1) >> 6;
            const uint32_t bt = bars + (tl & 3) * 8, pt = (tl >> 2) & 1;
            TR(8, k);
            uint32_t sc0[14], sc1[14];
#pragma unroll
            for (int i = 0; i < 14; i++) { sc0[i] = bias[i]; sc1[i] = bias[14 + i]; }
            if (mstate < 2 * k + 2) {
#pragma unroll 1
                for (uint32_t n = 0; n < (1u << 22) && mstate <= 2 * k; n++) mstate = lds32v(bars + B_MSTATE);
                if (mstate == 2 * k + 1) {
                    mbar_wait(bars + B_MFULL, k & 1);
                    const uint32_t ma = mrel + ((2 * (pair + k * P.npair)) & 14);
#pragma unroll
                    for (int i = 0; i < 14; i++) {
                        const uint32_t lo = lds16(ma + (i & 1) * mrow + (i >> 1) * 16);
                        const uint32_t hi = i < 12 ? lds16(ma + (i & 1) * mrow + (i >> 1) * 16 + 2) : 0u;
                        const uint32_t mk = pack_f16(__uint_as_float(lo << 16), __uint_as_float(hi << 16));
                        sc0[i] = hfma2_f16(mk, 0x3DC53DC5u, sc0[i]);
                        sc1[i] = hfma2_f16(mk, 0x3DC53DC5u, sc1[i]);
                    }
                    __syncwarp();
                    if (lane == 0) mbar_arrive(bars + B_MCONS);
                }
            }
            reg_fence(sc0);
            reg_fence(sc1);
            TR(10, k);
            mbar_wait_unless(qok, bt + B_QKRAW, pt);
            fence_async_smem();
            TR(11, k);
            wgmma_fence();
#if !(EXP & 128)
            mma_s0_f16<2 * IT * XCH, 2 * IT * XCH>(sc0, descKw, descKw);
            mma_s1_f16<2 * IT * XCH, 2 * IT * XCH>(sc1, descKw, descKw);
#endif
            wgmma_commit();
            const uint32_t vok = mbar_test(bt + B_VRAW, pt);
            uint32_t m[2];
            auto rowmax = [&](const uint32_t (&S)[14], int h) {
                uint32_t a[2];
#pragma unroll
                for (int o = 0; o < 2; o++)
                    a[o] = hmax2_f16(hmax2_f16(hmax2_f16(hmax2_f16(S[o], S[2 + o]), S[4 + o]), hmax2_f16(hmax2_f16(S[6 + o], S[8 + o]), S[10 + o])), S[12 + o]);
                m[h] = hmax2_f16(prmt(a[0], a[1], 0x5410), prmt(a[0], a[1], 0x7632));
            };
            wgmma_wait<0>();
            reg_fence(sc0);
            reg_fence(sc1);
            if (lane == 0) mbar_arrive(bar + B_QKFREE);
            TR(12, k);
            rowmax(sc0, 0);
            rowmax(sc1, 1);
#pragma unroll
            for (int i = 0; i < 2; i++) m[i] = hmax2_f16(m[i], __shfl_xor_sync(0xffffffffu, m[i], 1));
#pragma unroll
            for (int i = 0; i < 2; i++) m[i] = hmax2_f16(m[i], __shfl_xor_sync(0xffffffffu, m[i], 2));
            auto probs = [&](const uint32_t (&S)[14], uint32_t mm, uint32_t (&pa)[4][4]) {
#pragma unroll
                for (int j = 0; j < 6; j++) {
                    pa[j >> 1][(j & 1) * 2]     = ex2_f16x2(hsub2_bc<0>(S[2 * j], mm));
                    pa[j >> 1][(j & 1) * 2 + 1] = ex2_f16x2(hsub2_bc<1>(S[2 * j + 1], mm));
                }
                pa[3][0] = ex2_f16lo(hsub2_bc<0>(S[12], mm)) & pmask;
                pa[3][1] = ex2_f16lo(hsub2_bc<1>(S[13], mm)) & pmask;
                pa[3][2] = 0u; pa[3][3] = 0u;
                reg_fence(pa);
            };
            uint32_t pa0[4][4], pa1[4][4];
            uint32_t o0[14], o1[14];
            TR(13, k);
            mbar_wait_unless(vok, bt + B_VRAW, pt);
            fence_async_smem();
            TR(14, k);
            probs(sc0, m[0], pa0);
            wgmma_fence();
            mma_pv<2 * IT * V_STRIDE, 0>(o0, pa0, descVw);
            wgmma_commit();
            probs(sc1, m[1], pa1);
            wgmma_fence();
            mma_pv<2 * IT * V_STRIDE + 6 * GRP, 0>(o1, pa1, descVw);
            wgmma_commit();
            uint32_t w[24];
            wgmma_wait<1>();
            reg_fence(o0);
            {
                const float il0 = rcp_ftz(f16lo(o0[12])), il1 = rcp_ftz(f16lo(o0[13]));
                const uint32_t l0 = pack_f16(il0, il0), l1 = pack_f16(il1, il1);
#pragma unroll
                for (int j = 0; j < 12; j++) w[j] = hmul2_f16(o0[j], (j & 1) ? l1 : l0);
            }
            wgmma_wait<0>();
            reg_fence(o1);
            TR(15, k);
            asm volatile("{\n.reg .pred p;\nsetp.eq.u32 p, %0, 1;\n@p bar.sync 4, 128;\n@!p bar.sync 5, 128;\n}\n"
                         :: "r"(wg) : "memory");
            qok = mbar_test(bars + (tn & 3) * 8 + B_QKRAW, (tn >> 2) & 1);
            mstate = lds32v(bars + B_MSTATE);
            {
                const float il2 = rcp_ftz(f16lo(o1[0])), il3 = rcp_ftz(f16lo(o1[1]));
                const uint32_t l2 = pack_f16(il2, il2), l3 = pack_f16(il3, il3);
#pragma unroll
                for (int j = 0; j < 12; j++) w[12 + j] = hmul2_f16(o1[j + 2], (j & 1) ? l3 : l2);
#pragma unroll
                for (int p = 0; p < 6; p++) stsm_x4(oa + p * 32, w[4 * p], w[4 * p + 1], w[4 * p + 2], w[4 * p + 3]);
            }
            __syncwarp();
            if (lane == 0) mbar_arrive(bar + B_ODONE);
            TR(16, k);
            oa ^= oflip;
            asm volatile("" : "+r"(oa));
        };
        for (int k = wg - 1;; k += 4) {
            window(std::integral_constant<int, 0>(), k);
            if (k + 2 >= nwin) break;
            window(std::integral_constant<int, 1>(), k + 2);
            if (k + 4 >= nwin) break;
        }
        (void)zero;
        asm volatile("setmaxnreg.inc.sync.aligned.u32 160;\n");
    }

    TR(27, wg);
    uint32_t tag, seen;
    asm volatile("ld.relaxed.gpu.global.v2.u32 {%0, %1}, [%2];\n" : "=r"(tag), "=r"(seen) : "l"(g_guard) : "memory");
    if (attn) {
        __syncwarp();
        if (lane == 0) mbar_arrive(sbase + SM_PBAR + 96);
    }
    if (!attn || wg == 0) {
#pragma unroll 3
        for (int row = tid >> 2; row < 192; row += attn ? 32 : 96) {
            uint4 w[6];
#pragma unroll
            for (int a = 0; a < 6; a++) w[a] = *reinterpret_cast<const uint4*>(P.wo + row * 192 + 32 * a + 8 * c);
            float s = 0.f;
#pragma unroll
            for (int a = 0; a < 6; a++)
                s += ((bf16lo(w[a].x) + bf16hi(w[a].x)) + (bf16lo(w[a].y) + bf16hi(w[a].y))) +
                     ((bf16lo(w[a].z) + bf16hi(w[a].z)) + (bf16lo(w[a].w) + bf16hi(w[a].w)));
            s += __shfl_xor_sync(0xffffffffu, s, 1);
            s += __shfl_xor_sync(0xffffffffu, s, 2);
            s *= (1.f / 192.f);
            const uint32_t d = sbase + SM_WO + row * 64 + ((c ^ ((row >> 1) & 3)) << 4);
#pragma unroll
            for (int a = 0; a < 6; a++)
                sts128(d + a * 12288, pack_f16(bf16lo(w[a].x) - s, bf16hi(w[a].x) - s), pack_f16(bf16lo(w[a].y) - s, bf16hi(w[a].y) - s),
                       pack_f16(bf16lo(w[a].z) - s, bf16hi(w[a].z) - s), pack_f16(bf16lo(w[a].w) - s, bf16hi(w[a].w) - s));
        }
        fence_async_smem();
    }
    tag |= 255;
    if (bad) g_guard[1] = tag;
    bad |= seen == tag;
    asm volatile("bar.sync 6, 384;\n" ::: "memory");
    TR(27, 4 + wg);
    {
        PROJ_SCHEDULE
        uint64_t descW = make_desc(sbase + SM_WO, 12288, 512, 2);
        const uint64_t descA = make_desc(sbase + SM_STAGE + wg * STAGE_BYTES, 16, 1024, 1);
        const uint32_t bar = sbase + SM_PBAR + wg * 8;
        const uint32_t yrel = sbase + SM_STAGE + wg * STAGE_BYTES + (warp * 16 + (lane & 15)) * 128 + (((lane & 7) ^ (lane >> 4)) << 4);
        float acc[96];
#pragma unroll
        for (int i = 0; i < 96; i++) acc[i] = 0.f;
        uint32_t it = 0;
        for (int tile = tile0 + wg * tstep; tile < tend; tile += 3 * tstep, it++) {
            descW += P.z1;
            mbar_wait(bar + (it & 1) * 24, (it >> 1) & 1);
            TR(28, it * 3 + wg);
            if (it > 0 || wg > 0) asm volatile("bar.sync %0, 256;\n" :: "r"(8 + wg) : "memory");
            wgmma_fence();
            mma_proj<0, 0>(acc, descA + (uint64_t)((it & 1) * (3 * STAGE_BYTES >> 4)), descW);
            wgmma_commit();
            if (tile + tstep < tend) asm volatile("bar.arrive %0, 256;\n" :: "r"(wg == 2 ? 8 : 9 + wg) : "memory");
            wgmma_wait<0>();
            reg_fence(acc);
            float a[4];
#pragma unroll
            for (int i = 0; i < 4; i++) a[i] = acc[i] * acc[i];
#pragma unroll
            for (int j = 1; j < 24; j++)
#pragma unroll
                for (int i = 0; i < 4; i++) a[i] = fmaf(acc[4 * j + i], acc[4 * j + i], a[i]);
            float s0 = a[0] + a[1], s1 = a[2] + a[3];
            s0 += __shfl_xor_sync(0xffffffffu, s0, 1);
            s1 += __shfl_xor_sync(0xffffffffu, s1, 1);
            s0 += __shfl_xor_sync(0xffffffffu, s0, 2);
            s1 += __shfl_xor_sync(0xffffffffu, s1, 2);
            if (max(__float_as_uint(s0) - VAR_MIN, __float_as_uint(s1) - VAR_MIN) >= F32_INF - VAR_MIN) {
                const int rem = ((tile < TILES_A) ? NPIX - SEG_B - 64 * tile : SEG_B - 64 * (tile - TILES_A)) - warp * 16 - g;
                if ((__float_as_uint(s0) - VAR_MIN >= F32_INF - VAR_MIN && rem > 0) ||
                    (__float_as_uint(s1) - VAR_MIN >= F32_INF - VAR_MIN && rem > 8)) {
                    bad = true;
                    g_guard[1] = tag;
                }
            }
            const float rs0 = rsqrt_ftz(fmaf(s0, 1.f / 192.f, 1e-5f));
            const float rs1 = rsqrt_ftz(fmaf(s1, 1.f / 192.f, 1e-5f));
            const uint32_t ya = yrel + (it & 1) * 3 * STAGE_BYTES;
#pragma unroll
            for (int p = 0; p < 12; p++)
                stsm_x4((ya ^ (32 * (p & 3))) + (p >> 2) * 8192,
                        pack_bf16(acc[8 * p] * rs0, acc[8 * p + 1] * rs0), pack_bf16(acc[8 * p + 2] * rs1, acc[8 * p + 3] * rs1),
                        pack_bf16(acc[8 * p + 4] * rs0, acc[8 * p + 5] * rs0), pack_bf16(acc[8 * p + 6] * rs1, acc[8 * p + 7] * rs1));
            __syncwarp();
            if (lane == 0) mbar_arrive(bar + 104 + (it & 1) * 24);
            TR(29, it * 3 + wg);
        }
    }

    {
        uint32_t any;
        asm volatile("{\n.reg .pred p, q;\nsetp.ne.u32 q, %1, 0;\nbarrier.cta.red.or.pred.aligned p, %2, 128, q;\nselp.u32 %0, 1, 0, p;\n}\n"
                     : "=r"(any) : "r"((uint32_t)bad), "r"(12 + wg) : "memory");
        if (!any) return;
    }
    redo(P, smem + wg * FB_BYTES, tag, 12 + wg);
}

}

typedef CUresult (*PFN_encodeTiled)(CUtensorMap*, CUtensorMapDataType, cuuint32_t, void*, const cuuint64_t*,
                                    const cuuint64_t*, const cuuint32_t*, const cuuint32_t*, CUtensorMapInterleave,
                                    CUtensorMapSwizzle, CUtensorMapL2promotion, CUtensorMapFloatOOBfill);

extern "C" void kernel_launch(void* const* d_in, const int* in_sizes, int n_in, void* d_out, int out_size) {
    swin::Params P;
    P.x           = (const __nv_bfloat16*)d_in[0];
    P.wqkv        = (const __nv_bfloat16*)d_in[1];
    P.wo          = (const __nv_bfloat16*)d_in[2];
    P.logit_scale = (const __nv_bfloat16*)d_in[3];
    P.cpb_w1      = (const __nv_bfloat16*)d_in[4];
    P.cpb_w2      = (const __nv_bfloat16*)d_in[5];
    P.rel_coords  = (const __nv_bfloat16*)d_in[6];
    P.rel_idx     = (const int*)d_in[7];
    P.mask        = (const __nv_bfloat16*)d_in[8];
    P.out         = (__nv_bfloat16*)d_out;
    P.z1 = 0;
    static PFN_encodeTiled encode = nullptr;
    if (!encode) {
        cudaFuncSetAttribute(swin::swin_window_attn_kernel, cudaFuncAttributeMaxDynamicSharedMemorySize, swin::SM_TOTAL);
        cudaDriverEntryPointQueryResult qr;
        cudaGetDriverEntryPoint("cuTensorMapEncodeTiled", (void**)&encode, cudaEnableDefault, &qr);
    }
    CUtensorMap xmap, xmap4, xmap3, omap, wmap, smap, omapb, xmapa, xmapb, smap3, wraw;
    const cuuint32_t estr[4] = {1, 1, 1, 1};
    auto make = [&](CUtensorMap* m, const void* base, int rank, const cuuint64_t* gdim, const cuuint64_t* gstr,
                    const cuuint32_t* box, CUtensorMapSwizzle swz = CU_TENSOR_MAP_SWIZZLE_128B) {
        CUresult r = encode(m, CU_TENSOR_MAP_DATA_TYPE_BFLOAT16, rank, const_cast<void*>(base), gdim, gstr, box, estr,
               CU_TENSOR_MAP_INTERLEAVE_NONE, swz, CU_TENSOR_MAP_L2_PROMOTION_L2_128B,
               CU_TENSOR_MAP_FLOAT_OOB_FILL_NONE);
        (void)r;
    };
    {
        const cuuint64_t gdim[3] = {192, swin::IMG, swin::IMG}, gstr[2] = {384, swin::IMG * 384};
        const cuuint32_t box[3] = {64, 7, 7}, box4[3] = {64, 4, 1}, box3[3] = {64, 3, 1};
        make(&xmap, P.x, 3, gdim, gstr, box);
        make(&xmap4, P.x, 3, gdim, gstr, box4);
        make(&xmap3, P.x, 3, gdim, gstr, box3);
        const cuuint32_t boxa[3] = {64, 7, 3}, boxb[3] = {64, 7, 4};
        make(&xmapa, P.x, 3, gdim, gstr, boxa);
        make(&xmapb, P.x, 3, gdim, gstr, boxb);
    }
    {
        const cuuint64_t gdim[2] = {192, (cuuint64_t)swin::NPIX}, gstr[1] = {384};
        const cuuint32_t box64[2] = {64, 64};
        make(&omap, d_out, 2, gdim, gstr, box64);
        const cuuint64_t gdimb[2] = {192, (cuuint64_t)swin::SEG_B};
        make(&omapb, d_out, 2, gdimb, gstr, box64);
    }
    {
        const cuuint64_t gdim[2] = {576, 192}, gstr[1] = {1152};
        const cuuint32_t box[2] = {16, 192};
        make(&wmap, P.wqkv, 2, gdim, gstr, box, CU_TENSOR_MAP_SWIZZLE_32B);
        const cuuint64_t gdim3[3] = {96, 6, 192}, gstr3[2] = {192, 1152};
        const cuuint32_t box3[3] = {104, 1, 96};
        make(&wraw, P.wqkv, 3, gdim3, gstr3, box3, CU_TENSOR_MAP_SWIZZLE_NONE);
    }
    {
        const cuuint64_t gdim[4] = {96, 2, swin::IMG, swin::IMG}, gstr[3] = {192, 384, swin::IMG * 384};
        const cuuint32_t box4[4] = {104, 1, 7, 4}, box3[4] = {104, 1, 7, 3};
        make(&smap, d_out, 4, gdim, gstr, box4, CU_TENSOR_MAP_SWIZZLE_NONE);
        make(&smap3, d_out, 4, gdim, gstr, box3, CU_TENSOR_MAP_SWIZZLE_NONE);
    }
    P.npair = NPAIR; P.need = swin::ROW_DONE; P.nq = swin::NWINDOWS / NPAIR; P.nr = swin::NWINDOWS % NPAIR;
    P.t1 = swin::TILES - NTAIL;
    swin::swin_window_attn_kernel<<<132, swin::NTHREADS, swin::SM_TOTAL>>>(P, xmap, xmap4, xmap3, omap, wmap, smap, omapb, xmapa, xmapb, smap3, wraw);
}
```

```cpp
#include <cuda_runtime.h>
#include <cuda.h>
#include <cuda_bf16.h>
#include <stdint.h>
#include <type_traits>

namespace swin {

#define NPAIR 53
#define QFP32 0
#define PF_DIST 3
#define EXP 0
#define QSPLIT 3
#define SSPLIT 0
#define LATEMASK 0
#define CLUSTER 0
#define NOPF 0
#define NTAIL 216
#define PSTORE 1
#define PORDER 1
#define GORD 0
#define GMERGE 0
#define XSPLIT 1
#define EARLYW 1
#define NEARLY 4
#define W1 1
#define W2 2
#define W3 2
#define T_ONEBUF 0
#define T_NOWV 0
#define MPF 3
#define MRND 5
#define PX_L 3
#define PX_S 3
#define PX_W 0
#define PCHUNK 1
#define SPREAD 1
#define PSM 2
#define PDF 0
#define PWRAP -1
#define POLLER 1
#define PUBN 2
#define PUBT 4
#define HINT 0
#define HINT_A ""
#define HINT_B ""
#define REG_G 232
#define REG_A 120
#define REG_H 32
constexpr int IMG      = 511;
constexpr int NWS      = 73;
constexpr int NWINDOWS = NWS * NWS;
constexpr int TOK      = 49;
constexpr int NPIX     = IMG * IMG;
constexpr int NTHREADS = 512;

constexpr int W_ATOM = 6144;
constexpr int SM_WA = 0, SM_WB = 6 * W_ATOM, SM_WV = 12 * W_ATOM;
constexpr int GRP   = TOK * 16;
constexpr int XCH   = TOK * 128;
constexpr int SM_V  = 18 * W_ATOM, V_STRIDE = 10240, O_PITCH = 208;
constexpr int SM_QK = SM_V + 4 * V_STRIDE, QK_CHUNK = 4 * XCH;
constexpr int SM_MASK = SM_QK + 3 * QK_CHUNK;
constexpr int SM_TAB  = SM_V + 3 * V_STRIDE + 256;
constexpr int SM_DUMP = SM_MASK + 4816;
constexpr int SM_BAR  = SM_DUMP + 320;
constexpr int B_XFULL = 0, B_WRAW = 32, B_XCONS = 40, B_ROWS = 384, B_QKRAW = 64, B_QKFREE = 96, B_VFREE = 128, B_ODONE = 160,
              B_VRAW = 224, B_MFULL = 256, B_MSTATE = 264, B_MCONS = 272, B_WFULL = 280, B_STORED = 288, B_PUBD = 304;
constexpr int SM_A_END = SM_BAR + 320;
static_assert(SM_QK % 1024 == 0 && TOK * O_PITCH + 64 - 16 <= V_STRIDE && (28 * O_PITCH + 64) % 128 == 0, "layout");
constexpr int SM_WO    = 0;
constexpr int SM_STAGE = 73728;
constexpr int STAGE_BYTES = 24576;
constexpr int SM_PBAR  = SM_A_END;
constexpr int SM_TOTAL = SM_PBAR + 152;
static_assert(SM_STAGE + 6 * STAGE_BYTES <= SM_BAR, "smem");
static_assert(SM_TOTAL <= 232448, "smem");
static_assert(SM_BAR % 8 == 0, "barrier alignment");

constexpr int SEG_B   = 3 * IMG;
constexpr int TILES_A = (NPIX - SEG_B + 63) / 64;
constexpr int TILES   = TILES_A + (SEG_B + 63) / 64;
constexpr uint32_t ROW_DONE = NWS * 2;

__device__ uint32_t g_cnt[NWS + 7];
__device__ uint32_t g_done;
__device__ __align__(16) uint32_t g_guard[4];
constexpr uint32_t F32_INF = 0x7F800000u;
constexpr uint32_t SS_MIN  = 0x3B800000u;
constexpr uint32_t VAR_MIN = 0x3D400000u;

#define TR(ev, idx)
constexpr float LOG2E = 1.4426950408889634f;

__device__ __forceinline__ uint32_t smem_u32(const void* p) {
    return (uint32_t)__cvta_generic_to_shared(p);
}
__device__ __forceinline__ uint64_t make_desc(uint32_t saddr, uint32_t lbo, uint32_t sbo, uint32_t swz = 0) {
    return (uint64_t)((saddr & 0x3FFFF) >> 4) | ((uint64_t)(lbo >> 4) << 16) | ((uint64_t)(sbo >> 4) << 32) |
           ((uint64_t)swz << 62);
}
__host__ __device__ constexpr uint64_t make_desc_c(uint32_t saddr, uint32_t lbo, uint32_t sbo, uint32_t swz) {
    return (uint64_t)(saddr >> 4) | ((uint64_t)(lbo >> 4) << 16) | ((uint64_t)(sbo >> 4) << 32) | ((uint64_t)swz << 62);
}
__device__ __forceinline__ void wgmma_fence()  { asm volatile("wgmma.fence.sync.aligned;\n" ::: "memory"); }
__device__ __forceinline__ void wgmma_commit() { asm volatile("wgmma.commit_group.sync.aligned;\n" ::: "memory"); }
template <int N> __device__ __forceinline__ void wgmma_wait() {
    asm volatile("wgmma.wait_group.sync.aligned %0;\n" :: "n"(N) : "memory");
}
__device__ __forceinline__ void fence_async_smem() { asm volatile("fence.proxy.async.shared::cta;\n" ::: "memory"); }
__device__ __forceinline__ void wg_bar(int id) { asm volatile("bar.sync %0, 128;\n" :: "r"(id) : "memory"); }

template <int N> __device__ __forceinline__ void reg_fence(float (&v)[N]) {
#pragma unroll
    for (int i = 0; i < N; i++) asm volatile("" : "+f"(v[i]) :: "memory");
}
template <int N> __device__ __forceinline__ void reg_fence(uint32_t (&v)[N]) {
#pragma unroll
    for (int i = 0; i < N; i++) asm volatile("" : "+r"(v[i]) :: "memory");
}
template <int N, int M> __device__ __forceinline__ void reg_fence(uint32_t (&v)[N][M]) {
#pragma unroll
    for (int i = 0; i < N; i++) reg_fence(v[i]);
}

__device__ __forceinline__ uint32_t pack_bf16(float lo, float hi) {
    uint32_t r;
    asm("cvt.rn.bf16x2.f32 %0, %1, %2;\n" : "=r"(r) : "f"(hi), "f"(lo));
    return r;
}
__device__ __forceinline__ uint32_t pack_f16(float lo, float hi) {
    uint32_t r;
    asm("cvt.rn.f16x2.f32 %0, %1, %2;\n" : "=r"(r) : "f"(hi), "f"(lo));
    return r;
}
__device__ __forceinline__ uint32_t pack_f16_sat(float lo, float hi) {
    uint32_t r;
    asm("cvt.rn.satfinite.f16x2.f32 %0, %1, %2;\n" : "=r"(r) : "f"(hi), "f"(lo));
    return r;
}
__device__ __forceinline__ uint32_t hmul2_f16(uint32_t a, uint32_t b) {
    uint32_t r;
    asm("mul.rn.f16x2 %0, %1, %2;\n" : "=r"(r) : "r"(a), "r"(b));
    return r;
}
__device__ __forceinline__ uint32_t hadd2_f16(uint32_t a, uint32_t b) {
    uint32_t r;
    asm("add.rn.f16x2 %0, %1, %2;\n" : "=r"(r) : "r"(a), "r"(b));
    return r;
}
__device__ __forceinline__ uint32_t hfma2_f16(uint32_t a, uint32_t b, uint32_t c) {
    uint32_t r;
    asm("fma.rn.f16x2 %0, %1, %2, %3;\n" : "=r"(r) : "r"(a), "r"(b), "r"(c));
    return r;
}
__device__ __forceinline__ uint32_t hmax2_f16(uint32_t a, uint32_t b) {
    uint32_t r;
    asm("max.f16x2 %0, %1, %2;\n" : "=r"(r) : "r"(a), "r"(b));
    return r;
}
template <int H> __device__ __forceinline__ uint32_t hsub2_bc(uint32_t a, uint32_t b) {
    uint32_t r;
    if (H == 0) asm("{\n.reg .b16 l, h;\n.reg .b32 t;\nmov.b32 {l, h}, %2;\nmov.b32 t, {l, l};\nsub.rn.f16x2 %0, %1, t;\n}\n" : "=r"(r) : "r"(a), "r"(b));
    else        asm("{\n.reg .b16 l, h;\n.reg .b32 t;\nmov.b32 {l, h}, %2;\nmov.b32 t, {h, h};\nsub.rn.f16x2 %0, %1, t;\n}\n" : "=r"(r) : "r"(a), "r"(b));
    return r;
}
__device__ __forceinline__ uint32_t ex2_f16x2(uint32_t a) {
    uint32_t r;
    asm("ex2.approx.f16x2 %0, %1;\n" : "=r"(r) : "r"(a));
    return r;
}
__device__ __forceinline__ uint32_t ex2_f16lo(uint32_t a) {
    uint32_t r;
    asm("{\n.reg .b16 l, h;\nmov.b32 {l, h}, %1;\nex2.approx.f16 l, l;\nmov.b32 %0, {l, h};\n}\n" : "=r"(r) : "r"(a));
    return r;
}
__device__ __forceinline__ uint32_t lds16(uint32_t addr) {
    uint32_t v;
    asm volatile("ld.shared.u16 %0, [%1];\n" : "=r"(v) : "r"(addr) : "memory");
    return v;
}
__device__ __forceinline__ float f16lo(uint32_t v) {
    float r;
    asm("{\n.reg .b16 l, h;\nmov.b32 {l, h}, %1;\ncvt.f32.f16 %0, l;\n}\n" : "=f"(r) : "r"(v));
    return r;
}
__device__ __forceinline__ float f16hi(uint32_t v) {
    float r;
    asm("{\n.reg .b16 l, h;\nmov.b32 {l, h}, %1;\ncvt.f32.f16 %0, h;\n}\n" : "=f"(r) : "r"(v));
    return r;
}
__device__ __forceinline__ uint32_t bf2h(uint32_t v) {
    return pack_f16(__uint_as_float(v << 16), __uint_as_float(v & 0xFFFF0000u));
}
__device__ __forceinline__ float bf16lo(uint32_t v) { return __uint_as_float(v << 16); }
__device__ __forceinline__ float bf16hi(uint32_t v) { return __uint_as_float(v & 0xFFFF0000u); }
__device__ __forceinline__ uint32_t hadd2_bf16(uint32_t a, uint32_t b) {
    uint32_t r;
    asm("add.rn.bf16x2 %0, %1, %2;\n" : "=r"(r) : "r"(a), "r"(b));
    return r;
}
__device__ __forceinline__ uint32_t hmul2_bf16(uint32_t a, uint32_t b) {
    uint32_t r;
    asm("mul.rn.bf16x2 %0, %1, %2;\n" : "=r"(r) : "r"(a), "r"(b));
    return r;
}
__device__ __forceinline__ uint32_t hsub2_bf16(uint32_t a, uint32_t b) {
    uint32_t r;
    asm("sub.rn.bf16x2 %0, %1, %2;\n" : "=r"(r) : "r"(a), "r"(b));
    return r;
}
__device__ __forceinline__ uint32_t hfma2_bf16(uint32_t a, uint32_t b, uint32_t c) {
    uint32_t r;
    asm("fma.rn.bf16x2 %0, %1, %2, %3;\n" : "=r"(r) : "r"(a), "r"(b), "r"(c));
    return r;
}
__device__ __forceinline__ uint32_t hmax2_bf16(uint32_t a, uint32_t b) {
    uint32_t r;
    asm("max.bf16x2 %0, %1, %2;\n" : "=r"(r) : "r"(a), "r"(b));
    return r;
}
__device__ __forceinline__ uint32_t ex2_bf16x2(uint32_t a) {
    uint32_t r;
    asm("ex2.approx.ftz.bf16x2 %0, %1;\n" : "=r"(r) : "r"(a));
    return r;
}
__device__ __forceinline__ uint32_t ex2_bf16lo(uint32_t a) {
    uint32_t r;
    asm("{\n.reg .b16 l, h;\nmov.b32 {l, h}, %1;\nex2.approx.ftz.bf16 l, l;\ncvt.u32.u16 %0, l;\n}\n" : "=r"(r) : "r"(a));
    return r;
}
__device__ __forceinline__ uint32_t mbar_test(uint32_t bar, uint32_t parity) {
    uint32_t ok;
    asm volatile("{\n.reg .pred p;\nmbarrier.test_wait.parity.shared::cta.b64 p, [%1], %2;\nselp.u32 %0, 1, 0, p;\n}\n"
                 : "=r"(ok) : "r"(bar), "r"(parity) : "memory");
    return ok;
}
__device__ __forceinline__ uint32_t prmt(uint32_t a, uint32_t b, uint32_t sel) {
    uint32_t r;
    asm("prmt.b32 %0, %1, %2, %3;\n" : "=r"(r) : "r"(a), "r"(b), "r"(sel));
    return r;
}
__device__ __forceinline__ float round_bf16(float x) { return __bfloat162float(__float2bfloat16_rn(x)); }

__device__ __forceinline__ void mbar_init(uint32_t bar, uint32_t count) {
    asm volatile("mbarrier.init.shared::cta.b64 [%0], %1;\n" :: "r"(bar), "r"(count) : "memory");
}
__device__ __forceinline__ void mbar_wait(uint32_t bar, uint32_t parity) {
    asm volatile(
        "{\n"
        ".reg .pred p;\n"
        ".reg .u32 n;\n"
        "mov.u32 n, 0;\n"
        "WAIT_%=:\n"
        "mbarrier.try_wait.parity.shared::cta.b64 p, [%0], %1" HINT_A ";\n"
        "@p bra DONE_%=;\n"
        "add.u32 n, n, 1;\n"
        "setp.lt.u32 p, n, 4194304;\n"
        "@p bra WAIT_%=;\n"
        "exit;\n"
        "DONE_%=:\n"
        "}\n" :: "r"(bar), "r"(parity) : "memory");
}
__device__ __forceinline__ void mbar_wait4(uint32_t b0, uint32_t p0, uint32_t b1, uint32_t p1, uint32_t b2, uint32_t p2,
                                           uint32_t b3, uint32_t p3) {
    asm volatile(
        "{\n"
        ".reg .pred p, q, r, s;\n"
        ".reg .u32 n;\n"
        "mov.u32 n, 0;\n"
        "WAIT_%=:\n"
        "mbarrier.try_wait.parity.shared::cta.b64 p, [%0], %1;\n"
        "mbarrier.try_wait.parity.shared::cta.b64 q, [%2], %3;\n"
        "mbarrier.try_wait.parity.shared::cta.b64 r, [%4], %5;\n"
        "mbarrier.try_wait.parity.shared::cta.b64 s, [%6], %7;\n"
        "and.pred p, p, q;\n"
        "and.pred r, r, s;\n"
        "and.pred p, p, r;\n"
        "@p bra DONE_%=;\n"
        "add.u32 n, n, 1;\n"
        "setp.lt.u32 p, n, 4194304;\n"
        "@p bra WAIT_%=;\n"
        "exit;\n"
        "DONE_%=:\n"
        "}\n" :: "r"(b0), "r"(p0), "r"(b1), "r"(p1), "r"(b2), "r"(p2), "r"(b3), "r"(p3) : "memory");
}
__device__ __forceinline__ void mbar_wait2(uint32_t b0, uint32_t p0, uint32_t b1, uint32_t p1) {
    asm volatile(
        "{\n"
        ".reg .pred p, q;\n"
        ".reg .u32 n;\n"
        "mov.u32 n, 0;\n"
        "WAIT_%=:\n"
        "mbarrier.try_wait.parity.shared::cta.b64 p, [%0], %1;\n"
        "mbarrier.try_wait.parity.shared::cta.b64 q, [%2], %3;\n"
        "and.pred p, p, q;\n"
        "@p bra DONE_%=;\n"
        "add.u32 n, n, 1;\n"
        "setp.lt.u32 p, n, 4194304;\n"
        "@p bra WAIT_%=;\n"
        "exit;\n"
        "DONE_%=:\n"
        "}\n" :: "r"(b0), "r"(p0), "r"(b1), "r"(p1) : "memory");
}
__device__ __forceinline__ void mbar_wait_unless(uint32_t ok, uint32_t bar, uint32_t parity) {
    asm volatile(
        "{\n"
        ".reg .pred p;\n"
        ".reg .u32 n;\n"
        "setp.ne.u32 p, %2, 0;\n"
        "vote.sync.all.pred p, p, 0xffffffff;\n"
        "@p bra DONE_%=;\n"
        "mov.u32 n, 0;\n"
        "WAIT_%=:\n"
        "mbarrier.try_wait.parity.shared::cta.b64 p, [%0], %1" HINT_B ";\n"
        "@p bra DONE_%=;\n"
        "add.u32 n, n, 1;\n"
        "setp.lt.u32 p, n, 4194304;\n"
        "@p bra WAIT_%=;\n"
        "exit;\n"
        "DONE_%=:\n"
        "}\n" :: "r"(bar), "r"(parity), "r"(ok) : "memory");
}
__device__ __forceinline__ void mbar_wait_unless_dep(uint32_t ok, uint32_t bar, uint32_t parity, uint32_t zero, uint32_t& a,
                                                     uint32_t& b, uint32_t& c, uint32_t& d) {
    asm volatile(
        "{\n"
        ".reg .pred p;\n"
        ".reg .u32 n;\n"
        "setp.ne.u32 p, %6, 0;\n"
        "vote.sync.all.pred p, p, 0xffffffff;\n"
        "@p bra DONE_%=;\n"
        "mov.u32 n, 0;\n"
        "WAIT_%=:\n"
        "setp.ne.u32 p, %7, 0;\n"
        "@p ld.shared.v4.b32 {%0, %1, %2, %3}, [%7];\n"
        "mbarrier.try_wait.parity.shared::cta.b64 p, [%4], %5;\n"
        "@p bra DONE_%=;\n"
        "add.u32 n, n, 1;\n"
        "setp.lt.u32 p, n, 4194304;\n"
        "@p bra WAIT_%=;\n"
        "exit;\n"
        "DONE_%=:\n"
        "}\n" : "+r"(a), "+r"(b), "+r"(c), "+r"(d) : "r"(bar), "r"(parity), "r"(ok), "r"(zero) : "memory");
}
__device__ __forceinline__ void mbar_wait2_unless(uint32_t ok, uint32_t b0, uint32_t p0, uint32_t b1, uint32_t p1) {
    asm volatile(
        "{\n"
        ".reg .pred p, q;\n"
        ".reg .u32 n;\n"
        "setp.ne.u32 p, %4, 0;\n"
        "vote.sync.all.pred p, p, 0xffffffff;\n"
        "@p bra DONE_%=;\n"
        "mov.u32 n, 0;\n"
        "WAIT_%=:\n"
        "mbarrier.try_wait.parity.shared::cta.b64 p, [%0], %1" HINT_B ";\n"
        "mbarrier.try_wait.parity.shared::cta.b64 q, [%2], %3" HINT_B ";\n"
        "and.pred p, p, q;\n"
        "@p bra DONE_%=;\n"
        "add.u32 n, n, 1;\n"
        "setp.lt.u32 p, n, 4194304;\n"
        "@p bra WAIT_%=;\n"
        "exit;\n"
        "DONE_%=:\n"
        "}\n" :: "r"(b0), "r"(p0), "r"(b1), "r"(p1), "r"(ok) : "memory");
}
__device__ __forceinline__ void mbar_wait4_unless(uint32_t ok, uint32_t b0, uint32_t p0, uint32_t b1, uint32_t p1, uint32_t b2,
                                                  uint32_t p2, uint32_t b3, uint32_t p3) {
    asm volatile(
        "{\n"
        ".reg .pred p, q, r, s;\n"
        ".reg .u32 n;\n"
        "setp.ne.u32 p, %8, 0;\n"
        "vote.sync.all.pred p, p, 0xffffffff;\n"
        "@p bra DONE_%=;\n"
        "mov.u32 n, 0;\n"
        "WAIT_%=:\n"
        "mbarrier.try_wait.parity.shared::cta.b64 p, [%0], %1;\n"
        "mbarrier.try_wait.parity.shared::cta.b64 q, [%2], %3;\n"
        "mbarrier.try_wait.parity.shared::cta.b64 r, [%4], %5;\n"
        "mbarrier.try_wait.parity.shared::cta.b64 s, [%6], %7;\n"
        "and.pred p, p, q;\n"
        "and.pred r, r, s;\n"
        "and.pred p, p, r;\n"
        "@p bra DONE_%=;\n"
        "add.u32 n, n, 1;\n"
        "setp.lt.u32 p, n, 4194304;\n"
        "@p bra WAIT_%=;\n"
        "exit;\n"
        "DONE_%=:\n"
        "}\n" :: "r"(b0), "r"(p0), "r"(b1), "r"(p1), "r"(b2), "r"(p2), "r"(b3), "r"(p3), "r"(ok) : "memory");
}
__device__ __forceinline__ void sched_fence(uint32_t zero, uint32_t a, uint32_t b, uint32_t c, uint32_t d, uint32_t e = 0,
                                            uint32_t f = 0, uint32_t g = 0, uint32_t h = 0, uint32_t i = 0, uint32_t j = 0,
                                            uint32_t k = 0) {
    asm volatile("{\n.reg .pred p;\n.reg .u32 n;\nsetp.eq.u32 p, %0, 0;\n@p bra.uni DONE_%=;\nmov.u32 n, %0;\nSPIN_%=:\n"
                 "nanosleep.u32 %1;\nnanosleep.u32 %2;\nnanosleep.u32 %3;\nnanosleep.u32 %4;\nnanosleep.u32 %5;\n"
                 "nanosleep.u32 %6;\nnanosleep.u32 %7;\nnanosleep.u32 %8;\nnanosleep.u32 %9;\nnanosleep.u32 %10;\n"
                 "nanosleep.u32 %11;\nsub.u32 n, n, 1;\nsetp.ne.u32 p, n, 0;\n@p bra.uni SPIN_%=;\nDONE_%=:\n}\n"
                 :: "r"(zero), "r"(a), "r"(b), "r"(c), "r"(d), "r"(e), "r"(f), "r"(g), "r"(h), "r"(i), "r"(j), "r"(k) : "memory");
}
__device__ __forceinline__ void sched_fence16(uint32_t zero, const uint32_t (&v)[4][4], uint32_t a = 0, uint32_t b = 0) {
    asm volatile("{\n.reg .pred p;\n.reg .u32 n;\nsetp.eq.u32 p, %0, 0;\n@p bra.uni DONE_%=;\nmov.u32 n, %0;\nSPIN_%=:\n"
                 "nanosleep.u32 %17;\nnanosleep.u32 %18;\n"
                 "st.shared.v4.b32 [n], {%1, %2, %3, %4};\nst.shared.v4.b32 [n + 16], {%5, %6, %7, %8};\n"
                 "st.shared.v4.b32 [n + 32], {%9, %10, %11, %12};\nst.shared.v4.b32 [n + 48], {%13, %14, %15, %16};\n"
                 "sub.u32 n, n, 1;\nsetp.ne.u32 p, n, 0;\n@p bra.uni SPIN_%=;\nDONE_%=:\n}\n"
                 :: "r"(zero), "r"(v[0][0]), "r"(v[0][1]), "r"(v[0][2]), "r"(v[0][3]), "r"(v[1][0]), "r"(v[1][1]), "r"(v[1][2]), "r"(v[1][3]),
                    "r"(v[2][0]), "r"(v[2][1]), "r"(v[2][2]), "r"(v[2][3]), "r"(v[3][0]), "r"(v[3][1]), "r"(v[3][2]), "r"(v[3][3]),
                    "r"(a), "r"(b) : "memory");
}
__device__ __forceinline__ void sched_dep(uint32_t zero, uint32_t& a, uint32_t& b, uint32_t& c, uint32_t& d) {
    asm volatile("{\n.reg .pred p;\n.reg .u32 n;\nsetp.eq.u32 p, %4, 0;\n@p bra.uni DONE_%=;\nmov.u32 n, %4;\nSPIN_%=:\n"
                 "ld.shared.v4.b32 {%0, %1, %2, %3}, [n];\n"
                 "sub.u32 n, n, 1;\nsetp.ne.u32 p, n, 0;\n@p bra.uni SPIN_%=;\nDONE_%=:\n}\n"
                 : "+r"(a), "+r"(b), "+r"(c), "+r"(d) : "r"(zero) : "memory");
}
__device__ __forceinline__ void mbar_arrive(uint32_t bar) {
    asm volatile("mbarrier.arrive.shared::cta.b64 _, [%0];\n" :: "r"(bar) : "memory");
}
__device__ __forceinline__ void mbar_arrive_n(uint32_t bar, uint32_t n) {
    asm volatile("mbarrier.arrive.shared::cta.b64 _, [%0], %1;\n" :: "r"(bar), "r"(n) : "memory");
}
__device__ __forceinline__ void mbar_arrive_expect_tx(uint32_t bar, uint32_t bytes) {
    asm volatile("mbarrier.arrive.expect_tx.shared::cta.b64 _, [%0], %1;\n" :: "r"(bar), "r"(bytes) : "memory");
}
__device__ __forceinline__ void stg128_if(bool p, void* addr, uint32_t x, uint32_t y, uint32_t z, uint32_t w) {
    asm volatile("{\n.reg .pred q;\nsetp.ne.b32 q, %5, 0;\n@q st.global.L1::no_allocate.v4.b32 [%0], {%1, %2, %3, %4};\n}\n"
                 :: "l"(addr), "r"(x), "r"(y), "r"(z), "r"(w), "r"((uint32_t)p) : "memory");
}
__device__ __forceinline__ void stsm_x4(uint32_t addr, uint32_t r0, uint32_t r1, uint32_t r2, uint32_t r3) {
    asm volatile("stmatrix.sync.aligned.m8n8.x4.shared.b16 [%0], {%1, %2, %3, %4};\n"
                 :: "r"(addr), "r"(r0), "r"(r1), "r"(r2), "r"(r3) : "memory");
}
__device__ __forceinline__ void stsm_x2(uint32_t addr, uint32_t r0, uint32_t r1) {
    asm volatile("stmatrix.sync.aligned.m8n8.x2.shared.b16 [%0], {%1, %2};\n" :: "r"(addr), "r"(r0), "r"(r1) : "memory");
}
__device__ __forceinline__ void sts128(uint32_t addr, uint32_t r0, uint32_t r1, uint32_t r2, uint32_t r3) {
    asm volatile("st.shared.v4.b32 [%0], {%1, %2, %3, %4};\n" :: "r"(addr), "r"(r0), "r"(r1), "r"(r2), "r"(r3) : "memory");
}
__device__ __forceinline__ void sts32(uint32_t addr, uint32_t v) {
    asm volatile("st.shared.b32 [%0], %1;\n" :: "r"(addr), "r"(v) : "memory");
}
__device__ __forceinline__ uint32_t lds32(uint32_t addr) {
    uint32_t v;
    asm volatile("ld.shared.b32 %0, [%1];\n" : "=r"(v) : "r"(addr) : "memory");
    return v;
}
__device__ __forceinline__ void lds128(uint32_t (&r)[4], uint32_t addr) {
    asm volatile("ld.shared.v4.b32 {%0, %1, %2, %3}, [%4];\n" : "=r"(r[0]), "=r"(r[1]), "=r"(r[2]), "=r"(r[3]) : "r"(addr) : "memory");
}
__device__ __forceinline__ uint32_t lds32v(uint32_t addr) {
    uint32_t v;
    asm volatile("ld.volatile.shared.b32 %0, [%1];\n" : "=r"(v) : "r"(addr) : "memory");
    return v;
}
__device__ __forceinline__ void ldg_nc_v4(uint32_t (&r)[4], const void* p) {
    asm volatile("ld.global.nc.L1::no_allocate.v4.u32 {%0, %1, %2, %3}, [%4];\n"
                 : "=r"(r[0]), "=r"(r[1]), "=r"(r[2]), "=r"(r[3]) : "l"(p));
}
__device__ __forceinline__ uint32_t ldg_u32(const void* p) {
    uint32_t v;
    asm volatile("ld.global.nc.L1::evict_first.u32 %0, [%1];\n" : "=r"(v) : "l"(p));
    return v;
}
__device__ __forceinline__ void ldg_u64(const void* p, uint32_t& a, uint32_t& b) {
    asm volatile("ld.global.nc.L1::evict_first.v2.u32 {%0, %1}, [%2];\n" : "=r"(a), "=r"(b) : "l"(p));
}
__device__ __forceinline__ void prefetch_l2(const void* p) {
    asm volatile("prefetch.global.L2 [%0];\n" :: "l"(p));
}
__device__ __forceinline__ void cp_async16(uint32_t dst, const void* src) {
    asm volatile("cp.async.cg.shared.global [%0], [%1], 16;\n" :: "r"(dst), "l"(src) : "memory");
}
__device__ __forceinline__ float ex2_ftz(float x) {
    float y;
    asm("ex2.approx.ftz.f32 %0, %1;\n" : "=f"(y) : "f"(x));
    return y;
}
__device__ __forceinline__ float rcp_ftz(float x) {
    float y;
    asm("rcp.approx.ftz.f32 %0, %1;\n" : "=f"(y) : "f"(x));
    return y;
}
__device__ __forceinline__ float rsqrt_ftz(float x) {
    float y;
    asm("rsqrt.approx.ftz.f32 %0, %1;\n" : "=f"(y) : "f"(x));
    return y;
}

__device__ __forceinline__ bool elect_one() {
    uint32_t p;
    asm volatile("{\n.reg .pred q;\nelect.sync _|q, 0xffffffff;\nselp.u32 %0, 1, 0, q;\n}\n" : "=r"(p));
    return p != 0;
}
__device__ __forceinline__ void ldsm_x4(uint32_t (&r)[4], uint32_t addr) {
    asm volatile("ldmatrix.sync.aligned.m8n8.x4.shared.b16 {%0, %1, %2, %3}, [%4];\n"
                 : "=r"(r[0]), "=r"(r[1]), "=r"(r[2]), "=r"(r[3]) : "r"(addr) : "memory");
}
__device__ __forceinline__ void ldsm_x2(uint32_t& r0, uint32_t& r1, uint32_t addr) {
    asm volatile("ldmatrix.sync.aligned.m8n8.x2.shared.b16 {%0, %1}, [%2];\n" : "=r"(r0), "=r"(r1) : "r"(addr) : "memory");
}
__device__ __forceinline__ void tma_2d(uint32_t dst, const CUtensorMap* map, uint32_t bar, int c0, int c1) {
    asm volatile("cp.async.bulk.tensor.2d.shared::cluster.global.mbarrier::complete_tx::bytes [%0], [%1, {%3, %4}], [%2];\n"
                 :: "r"(dst), "l"(reinterpret_cast<uint64_t>(map)), "r"(bar), "r"(c0), "r"(c1) : "memory");
}
__device__ __forceinline__ void tma_3d(uint32_t dst, const CUtensorMap* map, uint32_t bar, int c0, int c1, int c2) {
    asm volatile("cp.async.bulk.tensor.3d.shared::cluster.global.mbarrier::complete_tx::bytes [%0], [%1, {%3, %4, %5}], [%2];\n"
                 :: "r"(dst), "l"(reinterpret_cast<uint64_t>(map)), "r"(bar), "r"(c0), "r"(c1), "r"(c2) : "memory");
}
__device__ __forceinline__ void tma_store_4d(const CUtensorMap* map, uint32_t src, int c0, int c1, int c2, int c3) {
    asm volatile("cp.async.bulk.tensor.4d.global.shared::cta.tile.bulk_group [%0, {%2, %3, %4, %5}], [%1];\n"
                 :: "l"(reinterpret_cast<uint64_t>(map)), "r"(src), "r"(c0), "r"(c1), "r"(c2), "r"(c3) : "memory");
}
__device__ __forceinline__ void mbar_arrive_if(uint32_t bar, uint32_t cnt) {
    asm volatile("{\n.reg .pred q;\nsetp.ne.b32 q, %1, 0;\n@q mbarrier.arrive.shared::cta.b64 _, [%0], %1;\n}\n"
                 :: "r"(bar), "r"(cnt) : "memory");
}

template <int BOFF, int AOFF, int NA>
__device__ __forceinline__ void mma_qk_first(uint32_t (&d)[48], const uint32_t (&a)[NA][4], uint64_t descB) {
    asm volatile(
        "{\n"
        ".reg .pred p0, p1;\n"
        ".reg .b64 ta, ta0, tb, tb0;\n"
        "setp.ne.b32 p0, 0, 0;\n"
        "setp.eq.b32 p1, 0, 0;\n"
        "add.s64 tb0, %64, %65;\n"
        "add.s64 tb, tb0, 0;\n"
        "wgmma.mma_async.sync.aligned.m64n192k16.f16.f16.f16 {%0, %1, %2, %3, %4, %5, %6, %7, %8, %9, %10, %11, %12, %13, %14, %15, %16, %17, %18, %19, %20, %21, %22, %23, %24, %25, %26, %27, %28, %29, %30, %31, %32, %33, %34, %35, %36, %37, %38, %39, %40, %41, %42, %43, %44, %45, %46, %47}, {%48, %49, %50, %51}, tb, p0, 1, 1, 1;\n"
        "add.s64 tb, tb0, 32;\n"
        "wgmma.mma_async.sync.aligned.m64n192k16.f16.f16.f16 {%0, %1, %2, %3, %4, %5, %6, %7, %8, %9, %10, %11, %12, %13, %14, %15, %16, %17, %18, %19, %20, %21, %22, %23, %24, %25, %26, %27, %28, %29, %30, %31, %32, %33, %34, %35, %36, %37, %38, %39, %40, %41, %42, %43, %44, %45, %46, %47}, {%52, %53, %54, %55}, tb, p1, 1, 1, 1;\n"
        "add.s64 tb, tb0, 64;\n"
        "wgmma.mma_async.sync.aligned.m64n192k16.f16.f16.f16 {%0, %1, %2, %3, %4, %5, %6, %7, %8, %9, %10, %11, %12, %13, %14, %15, %16, %17, %18, %19, %20, %21, %22, %23, %24, %25, %26, %27, %28, %29, %30, %31, %32, %33, %34, %35, %36, %37, %38, %39, %40, %41, %42, %43, %44, %45, %46, %47}, {%56, %57, %58, %59}, tb, p1, 1, 1, 1;\n"
        "add.s64 tb, tb0, 96;\n"
        "wgmma.mma_async.sync.aligned.m64n192k16.f16.f16.f16 {%0, %1, %2, %3, %4, %5, %6, %7, %8, %9, %10, %11, %12, %13, %14, %15, %16, %17, %18, %19, %20, %21, %22, %23, %24, %25, %26, %27, %28, %29, %30, %31, %32, %33, %34, %35, %36, %37, %38, %39, %40, %41, %42, %43, %44, %45, %46, %47}, {%60, %61, %62, %63}, tb, p1, 1, 1, 1;\n"
        "}\n"
        : "=r"(d[0]), "=r"(d[1]), "=r"(d[2]), "=r"(d[3]), "=r"(d[4]), "=r"(d[5]), "=r"(d[6]), "=r"(d[7]), "=r"(d[8]), "=r"(d[9]), "=r"(d[10]), "=r"(d[11]), "=r"(d[12]), "=r"(d[13]), "=r"(d[14]), "=r"(d[15]), "=r"(d[16]), "=r"(d[17]), "=r"(d[18]), "=r"(d[19]), "=r"(d[20]), "=r"(d[21]), "=r"(d[22]), "=r"(d[23]), "=r"(d[24]), "=r"(d[25]), "=r"(d[26]), "=r"(d[27]), "=r"(d[28]), "=r"(d[29]), "=r"(d[30]), "=r"(d[31]), "=r"(d[32]), "=r"(d[33]), "=r"(d[34]), "=r"(d[35]), "=r"(d[36]), "=r"(d[37]), "=r"(d[38]), "=r"(d[39]), "=r"(d[40]), "=r"(d[41]), "=r"(d[42]), "=r"(d[43]), "=r"(d[44]), "=r"(d[45]), "=r"(d[46]), "=r"(d[47])
        : "r"(a[AOFF + 0][0]), "r"(a[AOFF + 0][1]), "r"(a[AOFF + 0][2]), "r"(a[AOFF + 0][3]), "r"(a[AOFF + 1][0]), "r"(a[AOFF + 1][1]), "r"(a[AOFF + 1][2]), "r"(a[AOFF + 1][3]), "r"(a[AOFF + 2][0]), "r"(a[AOFF + 2][1]), "r"(a[AOFF + 2][2]), "r"(a[AOFF + 2][3]), "r"(a[AOFF + 3][0]), "r"(a[AOFF + 3][1]), "r"(a[AOFF + 3][2]), "r"(a[AOFF + 3][3]), "l"(descB), "n"(BOFF >> 4));
}

template <int BOFF, int AOFF, int NA>
__device__ __forceinline__ void mma_qk_next(uint32_t (&d)[48], const uint32_t (&a)[NA][4], uint64_t descB) {
    asm volatile(
        "{\n"
        ".reg .pred p0, p1;\n"
        ".reg .b64 ta, ta0, tb, tb0;\n"
        "setp.ne.b32 p0, 0, 0;\n"
        "setp.eq.b32 p1, 0, 0;\n"
        "add.s64 tb0, %64, %65;\n"
        "add.s64 tb, tb0, 0;\n"
        "wgmma.mma_async.sync.aligned.m64n192k16.f16.f16.f16 {%0, %1, %2, %3, %4, %5, %6, %7, %8, %9, %10, %11, %12, %13, %14, %15, %16, %17, %18, %19, %20, %21, %22, %23, %24, %25, %26, %27, %28, %29, %30, %31, %32, %33, %34, %35, %36, %37, %38, %39, %40, %41, %42, %43, %44, %45, %46, %47}, {%48, %49, %50, %51}, tb, p1, 1, 1, 1;\n"
        "add.s64 tb, tb0, 32;\n"
        "wgmma.mma_async.sync.aligned.m64n192k16.f16.f16.f16 {%0, %1, %2, %3, %4, %5, %6, %7, %8, %9, %10, %11, %12, %13, %14, %15, %16, %17, %18, %19, %20, %21, %22, %23, %24, %25, %26, %27, %28, %29, %30, %31, %32, %33, %34, %35, %36, %37, %38, %39, %40, %41, %42, %43, %44, %45, %46, %47}, {%52, %53, %54, %55}, tb, p1, 1, 1, 1;\n"
        "add.s64 tb, tb0, 64;\n"
        "wgmma.mma_async.sync.aligned.m64n192k16.f16.f16.f16 {%0, %1, %2, %3, %4, %5, %6, %7, %8, %9, %10, %11, %12, %13, %14, %15, %16, %17, %18, %19, %20, %21, %22, %23, %24, %25, %26, %27, %28, %29, %30, %31, %32, %33, %34, %35, %36, %37, %38, %39, %40, %41, %42, %43, %44, %45, %46, %47}, {%56, %57, %58, %59}, tb, p1, 1, 1, 1;\n"
        "add.s64 tb, tb0, 96;\n"
        "wgmma.mma_async.sync.aligned.m64n192k16.f16.f16.f16 {%0, %1, %2, %3, %4, %5, %6, %7, %8, %9, %10, %11, %12, %13, %14, %15, %16, %17, %18, %19, %20, %21, %22, %23, %24, %25, %26, %27, %28, %29, %30, %31, %32, %33, %34, %35, %36, %37, %38, %39, %40, %41, %42, %43, %44, %45, %46, %47}, {%60, %61, %62, %63}, tb, p1, 1, 1, 1;\n"
        "}\n"
        : "+r"(d[0]), "+r"(d[1]), "+r"(d[2]), "+r"(d[3]), "+r"(d[4]), "+r"(d[5]), "+r"(d[6]), "+r"(d[7]), "+r"(d[8]), "+r"(d[9]), "+r"(d[10]), "+r"(d[11]), "+r"(d[12]), "+r"(d[13]), "+r"(d[14]), "+r"(d[15]), "+r"(d[16]), "+r"(d[17]), "+r"(d[18]), "+r"(d[19]), "+r"(d[20]), "+r"(d[21]), "+r"(d[22]), "+r"(d[23]), "+r"(d[24]), "+r"(d[25]), "+r"(d[26]), "+r"(d[27]), "+r"(d[28]), "+r"(d[29]), "+r"(d[30]), "+r"(d[31]), "+r"(d[32]), "+r"(d[33]), "+r"(d[34]), "+r"(d[35]), "+r"(d[36]), "+r"(d[37]), "+r"(d[38]), "+r"(d[39]), "+r"(d[40]), "+r"(d[41]), "+r"(d[42]), "+r"(d[43]), "+r"(d[44]), "+r"(d[45]), "+r"(d[46]), "+r"(d[47])
        : "r"(a[AOFF + 0][0]), "r"(a[AOFF + 0][1]), "r"(a[AOFF + 0][2]), "r"(a[AOFF + 0][3]), "r"(a[AOFF + 1][0]), "r"(a[AOFF + 1][1]), "r"(a[AOFF + 1][2]), "r"(a[AOFF + 1][3]), "r"(a[AOFF + 2][0]), "r"(a[AOFF + 2][1]), "r"(a[AOFF + 2][2]), "r"(a[AOFF + 2][3]), "r"(a[AOFF + 3][0]), "r"(a[AOFF + 3][1]), "r"(a[AOFF + 3][2]), "r"(a[AOFF + 3][3]), "l"(descB), "n"(BOFF >> 4));
}

template <int BOFF, int AOFF, int NA>
__device__ __forceinline__ void mma_v_first(uint32_t (&d)[24], const uint32_t (&a)[NA][4], uint64_t descB) {
    asm volatile(
        "{\n"
        ".reg .pred p0, p1;\n"
        ".reg .b64 ta, ta0, tb, tb0;\n"
        "setp.ne.b32 p0, 0, 0;\n"
        "setp.eq.b32 p1, 0, 0;\n"
        "add.s64 tb0, %40, %41;\n"
        "add.s64 tb, tb0, 0;\n"
        "wgmma.mma_async.sync.aligned.m64n96k16.f16.f16.f16 {%0, %1, %2, %3, %4, %5, %6, %7, %8, %9, %10, %11, %12, %13, %14, %15, %16, %17, %18, %19, %20, %21, %22, %23}, {%24, %25, %26, %27}, tb, p0, 1, 1, 1;\n"
        "add.s64 tb, tb0, 32;\n"
        "wgmma.mma_async.sync.aligned.m64n96k16.f16.f16.f16 {%0, %1, %2, %3, %4, %5, %6, %7, %8, %9, %10, %11, %12, %13, %14, %15, %16, %17, %18, %19, %20, %21, %22, %23}, {%28, %29, %30, %31}, tb, p1, 1, 1, 1;\n"
        "add.s64 tb, tb0, 64;\n"
        "wgmma.mma_async.sync.aligned.m64n96k16.f16.f16.f16 {%0, %1, %2, %3, %4, %5, %6, %7, %8, %9, %10, %11, %12, %13, %14, %15, %16, %17, %18, %19, %20, %21, %22, %23}, {%32, %33, %34, %35}, tb, p1, 1, 1, 1;\n"
        "add.s64 tb, tb0, 96;\n"
        "wgmma.mma_async.sync.aligned.m64n96k16.f16.f16.f16 {%0, %1, %2, %3, %4, %5, %6, %7, %8, %9, %10, %11, %12, %13, %14, %15, %16, %17, %18, %19, %20, %21, %22, %23}, {%36, %37, %38, %39}, tb, p1, 1, 1, 1;\n"
        "}\n"
        : "=r"(d[0]), "=r"(d[1]), "=r"(d[2]), "=r"(d[3]), "=r"(d[4]), "=r"(d[5]), "=r"(d[6]), "=r"(d[7]), "=r"(d[8]), "=r"(d[9]), "=r"(d[10]), "=r"(d[11]), "=r"(d[12]), "=r"(d[13]), "=r"(d[14]), "=r"(d[15]), "=r"(d[16]), "=r"(d[17]), "=r"(d[18]), "=r"(d[19]), "=r"(d[20]), "=r"(d[21]), "=r"(d[22]), "=r"(d[23])
        : "r"(a[AOFF + 0][0]), "r"(a[AOFF + 0][1]), "r"(a[AOFF + 0][2]), "r"(a[AOFF + 0][3]), "r"(a[AOFF + 1][0]), "r"(a[AOFF + 1][1]), "r"(a[AOFF + 1][2]), "r"(a[AOFF + 1][3]), "r"(a[AOFF + 2][0]), "r"(a[AOFF + 2][1]), "r"(a[AOFF + 2][2]), "r"(a[AOFF + 2][3]), "r"(a[AOFF + 3][0]), "r"(a[AOFF + 3][1]), "r"(a[AOFF + 3][2]), "r"(a[AOFF + 3][3]), "l"(descB), "n"(BOFF >> 4));
}

template <int BOFF, int AOFF, int NA>
__device__ __forceinline__ void mma_v_next(uint32_t (&d)[24], const uint32_t (&a)[NA][4], uint64_t descB) {
    asm volatile(
        "{\n"
        ".reg .pred p0, p1;\n"
        ".reg .b64 ta, ta0, tb, tb0;\n"
        "setp.ne.b32 p0, 0, 0;\n"
        "setp.eq.b32 p1, 0, 0;\n"
        "add.s64 tb0, %40, %41;\n"
        "add.s64 tb, tb0, 0;\n"
        "wgmma.mma_async.sync.aligned.m64n96k16.f16.f16.f16 {%0, %1, %2, %3, %4, %5, %6, %7, %8, %9, %10, %11, %12, %13, %14, %15, %16, %17, %18, %19, %20, %21, %22, %23}, {%24, %25, %26, %27}, tb, p1, 1, 1, 1;\n"
        "add.s64 tb, tb0, 32;\n"
        "wgmma.mma_async.sync.aligned.m64n96k16.f16.f16.f16 {%0, %1, %2, %3, %4, %5, %6, %7, %8, %9, %10, %11, %12, %13, %14, %15, %16, %17, %18, %19, %20, %21, %22, %23}, {%28, %29, %30, %31}, tb, p1, 1, 1, 1;\n"
        "add.s64 tb, tb0, 64;\n"
        "wgmma.mma_async.sync.aligned.m64n96k16.f16.f16.f16 {%0, %1, %2, %3, %4, %5, %6, %7, %8, %9, %10, %11, %12, %13, %14, %15, %16, %17, %18, %19, %20, %21, %22, %23}, {%32, %33, %34, %35}, tb, p1, 1, 1, 1;\n"
        "add.s64 tb, tb0, 96;\n"
        "wgmma.mma_async.sync.aligned.m64n96k16.f16.f16.f16 {%0, %1, %2, %3, %4, %5, %6, %7, %8, %9, %10, %11, %12, %13, %14, %15, %16, %17, %18, %19, %20, %21, %22, %23}, {%36, %37, %38, %39}, tb, p1, 1, 1, 1;\n"
        "}\n"
        : "+r"(d[0]), "+r"(d[1]), "+r"(d[2]), "+r"(d[3]), "+r"(d[4]), "+r"(d[5]), "+r"(d[6]), "+r"(d[7]), "+r"(d[8]), "+r"(d[9]), "+r"(d[10]), "+r"(d[11]), "+r"(d[12]), "+r"(d[13]), "+r"(d[14]), "+r"(d[15]), "+r"(d[16]), "+r"(d[17]), "+r"(d[18]), "+r"(d[19]), "+r"(d[20]), "+r"(d[21]), "+r"(d[22]), "+r"(d[23])
        : "r"(a[AOFF + 0][0]), "r"(a[AOFF + 0][1]), "r"(a[AOFF + 0][2]), "r"(a[AOFF + 0][3]), "r"(a[AOFF + 1][0]), "r"(a[AOFF + 1][1]), "r"(a[AOFF + 1][2]), "r"(a[AOFF + 1][3]), "r"(a[AOFF + 2][0]), "r"(a[AOFF + 2][1]), "r"(a[AOFF + 2][2]), "r"(a[AOFF + 2][3]), "r"(a[AOFF + 3][0]), "r"(a[AOFF + 3][1]), "r"(a[AOFF + 3][2]), "r"(a[AOFF + 3][3]), "l"(descB), "n"(BOFF >> 4));
}

template <int AOFF, int BOFF>
__device__ __forceinline__ void mma_s0_f32(float (&d)[28], uint64_t descA, uint64_t descB) {
    asm volatile(
        "{\n"
        ".reg .pred p0, p1;\n"
        ".reg .b64 ta, ta0, tb, tb0;\n"
        "setp.ne.b32 p0, 0, 0;\n"
        "setp.eq.b32 p1, 0, 0;\n"
        "add.s64 tb0, %30, %31;\n"
        "add.s64 ta0, %28, %29;\n"
        "add.s64 tb, tb0, 4;\n"
        "add.s64 ta, ta0, 0;\n"
        "wgmma.mma_async.sync.aligned.m64n56k16.f32.f16.f16 {%0, %1, %2, %3, %4, %5, %6, %7, %8, %9, %10, %11, %12, %13, %14, %15, %16, %17, %18, %19, %20, %21, %22, %23, %24, %25, %26, %27}, ta, tb, p1, 1, 1, 0, 0;\n"
        "add.s64 tb, tb0, 1572;\n"
        "add.s64 ta, ta0, 1568;\n"
        "wgmma.mma_async.sync.aligned.m64n56k16.f32.f16.f16 {%0, %1, %2, %3, %4, %5, %6, %7, %8, %9, %10, %11, %12, %13, %14, %15, %16, %17, %18, %19, %20, %21, %22, %23, %24, %25, %26, %27}, ta, tb, p1, 1, 1, 0, 0;\n"
        "add.s64 tb, tb0, 3140;\n"
        "add.s64 ta, ta0, 3136;\n"
        "wgmma.mma_async.sync.aligned.m64n56k16.f32.f16.f16 {%0, %1, %2, %3, %4, %5, %6, %7, %8, %9, %10, %11, %12, %13, %14, %15, %16, %17, %18, %19, %20, %21, %22, %23, %24, %25, %26, %27}, ta, tb, p1, 1, 1, 0, 0;\n"
        "}\n"
        : "+f"(d[0]), "+f"(d[1]), "+f"(d[2]), "+f"(d[3]), "+f"(d[4]), "+f"(d[5]), "+f"(d[6]), "+f"(d[7]), "+f"(d[8]), "+f"(d[9]), "+f"(d[10]), "+f"(d[11]), "+f"(d[12]), "+f"(d[13]), "+f"(d[14]), "+f"(d[15]), "+f"(d[16]), "+f"(d[17]), "+f"(d[18]), "+f"(d[19]), "+f"(d[20]), "+f"(d[21]), "+f"(d[22]), "+f"(d[23]), "+f"(d[24]), "+f"(d[25]), "+f"(d[26]), "+f"(d[27])
        : "l"(descA), "n"(AOFF >> 4), "l"(descB), "n"(BOFF >> 4));
}

template <int AOFF, int BOFF>
__device__ __forceinline__ void mma_s0_f16(uint32_t (&d)[14], uint64_t descA, uint64_t descB) {
    asm volatile(
        "{\n"
        ".reg .pred p0, p1;\n"
        ".reg .b64 ta, ta0, tb, tb0;\n"
        "setp.ne.b32 p0, 0, 0;\n"
        "setp.eq.b32 p1, 0, 0;\n"
        "add.s64 tb0, %16, %17;\n"
        "add.s64 ta0, %14, %15;\n"
        "add.s64 tb, tb0, 4;\n"
        "add.s64 ta, ta0, 0;\n"
        "wgmma.mma_async.sync.aligned.m64n56k16.f16.f16.f16 {%0, %1, %2, %3, %4, %5, %6, %7, %8, %9, %10, %11, %12, %13}, ta, tb, p1, 1, 1, 0, 0;\n"
        "add.s64 tb, tb0, 1572;\n"
        "add.s64 ta, ta0, 1568;\n"
        "wgmma.mma_async.sync.aligned.m64n56k16.f16.f16.f16 {%0, %1, %2, %3, %4, %5, %6, %7, %8, %9, %10, %11, %12, %13}, ta, tb, p1, 1, 1, 0, 0;\n"
        "add.s64 tb, tb0, 3140;\n"
        "add.s64 ta, ta0, 3136;\n"
        "wgmma.mma_async.sync.aligned.m64n56k16.f16.f16.f16 {%0, %1, %2, %3, %4, %5, %6, %7, %8, %9, %10, %11, %12, %13}, ta, tb, p1, 1, 1, 0, 0;\n"
        "}\n"
        : "+r"(d[0]), "+r"(d[1]), "+r"(d[2]), "+r"(d[3]), "+r"(d[4]), "+r"(d[5]), "+r"(d[6]), "+r"(d[7]), "+r"(d[8]), "+r"(d[9]), "+r"(d[10]), "+r"(d[11]), "+r"(d[12]), "+r"(d[13])
        : "l"(descA), "n"(AOFF >> 4), "l"(descB), "n"(BOFF >> 4));
}

template <int AOFF, int BOFF>
__device__ __forceinline__ void mma_s1_f32(float (&d)[28], uint64_t descA, uint64_t descB) {
    asm volatile(
        "{\n"
        ".reg .pred p0, p1;\n"
        ".reg .b64 ta, ta0, tb, tb0;\n"
        "setp.ne.b32 p0, 0, 0;\n"
        "setp.eq.b32 p1, 0, 0;\n"
        "add.s64 tb0, %30, %31;\n"
        "add.s64 ta0, %28, %29;\n"
        "add.s64 tb, tb0, 6;\n"
        "add.s64 ta, ta0, 2;\n"
        "wgmma.mma_async.sync.aligned.m64n56k16.f32.f16.f16 {%0, %1, %2, %3, %4, %5, %6, %7, %8, %9, %10, %11, %12, %13, %14, %15, %16, %17, %18, %19, %20, %21, %22, %23, %24, %25, %26, %27}, ta, tb, p1, 1, 1, 0, 0;\n"
        "add.s64 tb, tb0, 1574;\n"
        "add.s64 ta, ta0, 1570;\n"
        "wgmma.mma_async.sync.aligned.m64n56k16.f32.f16.f16 {%0, %1, %2, %3, %4, %5, %6, %7, %8, %9, %10, %11, %12, %13, %14, %15, %16, %17, %18, %19, %20, %21, %22, %23, %24, %25, %26, %27}, ta, tb, p1, 1, 1, 0, 0;\n"
        "add.s64 tb, tb0, 3142;\n"
        "add.s64 ta, ta0, 3138;\n"
        "wgmma.mma_async.sync.aligned.m64n56k16.f32.f16.f16 {%0, %1, %2, %3, %4, %5, %6, %7, %8, %9, %10, %11, %12, %13, %14, %15, %16, %17, %18, %19, %20, %21, %22, %23, %24, %25, %26, %27}, ta, tb, p1, 1, 1, 0, 0;\n"
        "}\n"
        : "+f"(d[0]), "+f"(d[1]), "+f"(d[2]), "+f"(d[3]), "+f"(d[4]), "+f"(d[5]), "+f"(d[6]), "+f"(d[7]), "+f"(d[8]), "+f"(d[9]), "+f"(d[10]), "+f"(d[11]), "+f"(d[12]), "+f"(d[13]), "+f"(d[14]), "+f"(d[15]), "+f"(d[16]), "+f"(d[17]), "+f"(d[18]), "+f"(d[19]), "+f"(d[20]), "+f"(d[21]), "+f"(d[22]), "+f"(d[23]), "+f"(d[24]), "+f"(d[25]), "+f"(d[26]), "+f"(d[27])
        : "l"(descA), "n"(AOFF >> 4), "l"(descB), "n"(BOFF >> 4));
}

template <int AOFF, int BOFF>
__device__ __forceinline__ void mma_s1_f16(uint32_t (&d)[14], uint64_t descA, uint64_t descB) {
    asm volatile(
        "{\n"
        ".reg .pred p0, p1;\n"
        ".reg .b64 ta, ta0, tb, tb0;\n"
        "setp.ne.b32 p0, 0, 0;\n"
        "setp.eq.b32 p1, 0, 0;\n"
        "add.s64 tb0, %16, %17;\n"
        "add.s64 ta0, %14, %15;\n"
        "add.s64 tb, tb0, 6;\n"
        "add.s64 ta, ta0, 2;\n"
        "wgmma.mma_async.sync.aligned.m64n56k16.f16.f16.f16 {%0, %1, %2, %3, %4, %5, %6, %7, %8, %9, %10, %11, %12, %13}, ta, tb, p1, 1, 1, 0, 0;\n"
        "add.s64 tb, tb0, 1574;\n"
        "add.s64 ta, ta0, 1570;\n"
        "wgmma.mma_async.sync.aligned.m64n56k16.f16.f16.f16 {%0, %1, %2, %3, %4, %5, %6, %7, %8, %9, %10, %11, %12, %13}, ta, tb, p1, 1, 1, 0, 0;\n"
        "add.s64 tb, tb0, 3142;\n"
        "add.s64 ta, ta0, 3138;\n"
        "wgmma.mma_async.sync.aligned.m64n56k16.f16.f16.f16 {%0, %1, %2, %3, %4, %5, %6, %7, %8, %9, %10, %11, %12, %13}, ta, tb, p1, 1, 1, 0, 0;\n"
        "}\n"
        : "+r"(d[0]), "+r"(d[1]), "+r"(d[2]), "+r"(d[3]), "+r"(d[4]), "+r"(d[5]), "+r"(d[6]), "+r"(d[7]), "+r"(d[8]), "+r"(d[9]), "+r"(d[10]), "+r"(d[11]), "+r"(d[12]), "+r"(d[13])
        : "l"(descA), "n"(AOFF >> 4), "l"(descB), "n"(BOFF >> 4));
}

template <int BOFF, int AOFF, int NA>
__device__ __forceinline__ void mma_pv(uint32_t (&d)[14], const uint32_t (&a)[NA][4], uint64_t descB) {
    asm volatile(
        "{\n"
        ".reg .pred p0, p1;\n"
        ".reg .b64 ta, ta0, tb, tb0;\n"
        "setp.ne.b32 p0, 0, 0;\n"
        "setp.eq.b32 p1, 0, 0;\n"
        "add.s64 tb0, %30, %31;\n"
        "add.s64 tb, tb0, 0;\n"
        "wgmma.mma_async.sync.aligned.m64n56k16.f16.f16.f16 {%0, %1, %2, %3, %4, %5, %6, %7, %8, %9, %10, %11, %12, %13}, {%14, %15, %16, %17}, tb, p0, 1, 1, 1;\n"
        "add.s64 tb, tb0, 16;\n"
        "wgmma.mma_async.sync.aligned.m64n56k16.f16.f16.f16 {%0, %1, %2, %3, %4, %5, %6, %7, %8, %9, %10, %11, %12, %13}, {%18, %19, %20, %21}, tb, p1, 1, 1, 1;\n"
        "add.s64 tb, tb0, 32;\n"
        "wgmma.mma_async.sync.aligned.m64n56k16.f16.f16.f16 {%0, %1, %2, %3, %4, %5, %6, %7, %8, %9, %10, %11, %12, %13}, {%22, %23, %24, %25}, tb, p1, 1, 1, 1;\n"
        "add.s64 tb, tb0, 48;\n"
        "wgmma.mma_async.sync.aligned.m64n56k16.f16.f16.f16 {%0, %1, %2, %3, %4, %5, %6, %7, %8, %9, %10, %11, %12, %13}, {%26, %27, %28, %29}, tb, p1, 1, 1, 1;\n"
        "}\n"
        : "=r"(d[0]), "=r"(d[1]), "=r"(d[2]), "=r"(d[3]), "=r"(d[4]), "=r"(d[5]), "=r"(d[6]), "=r"(d[7]), "=r"(d[8]), "=r"(d[9]), "=r"(d[10]), "=r"(d[11]), "=r"(d[12]), "=r"(d[13])
        : "r"(a[AOFF + 0][0]), "r"(a[AOFF + 0][1]), "r"(a[AOFF + 0][2]), "r"(a[AOFF + 0][3]), "r"(a[AOFF + 1][0]), "r"(a[AOFF + 1][1]), "r"(a[AOFF + 1][2]), "r"(a[AOFF + 1][3]), "r"(a[AOFF + 2][0]), "r"(a[AOFF + 2][1]), "r"(a[AOFF + 2][2]), "r"(a[AOFF + 2][3]), "r"(a[AOFF + 3][0]), "r"(a[AOFF + 3][1]), "r"(a[AOFF + 3][2]), "r"(a[AOFF + 3][3]), "l"(descB), "n"(BOFF >> 4));
}

template <int AOFF, int BOFF>
__device__ __forceinline__ void mma_proj(float (&d)[96], uint64_t descA, uint64_t descB) {
    asm volatile(
        "{\n"
        ".reg .pred p0, p1;\n"
        ".reg .b64 ta, ta0, tb, tb0;\n"
        "setp.ne.b32 p0, 0, 0;\n"
        "setp.eq.b32 p1, 0, 0;\n"
        "add.s64 tb0, %98, %99;\n"
        "add.s64 ta0, %96, %97;\n"
        "add.s64 tb, tb0, 0;\n"
        "add.s64 ta, ta0, 0;\n"
        "wgmma.mma_async.sync.aligned.m64n192k16.f32.f16.f16 {%0, %1, %2, %3, %4, %5, %6, %7, %8, %9, %10, %11, %12, %13, %14, %15, %16, %17, %18, %19, %20, %21, %22, %23, %24, %25, %26, %27, %28, %29, %30, %31, %32, %33, %34, %35, %36, %37, %38, %39, %40, %41, %42, %43, %44, %45, %46, %47, %48, %49, %50, %51, %52, %53, %54, %55, %56, %57, %58, %59, %60, %61, %62, %63, %64, %65, %66, %67, %68, %69, %70, %71, %72, %73, %74, %75, %76, %77, %78, %79, %80, %81, %82, %83, %84, %85, %86, %87, %88, %89, %90, %91, %92, %93, %94, %95}, ta, tb, p0, 1, 1, 0, 1;\n"
        "add.s64 tb, tb0, 64;\n"
        "add.s64 ta, ta0, 2;\n"
        "wgmma.mma_async.sync.aligned.m64n192k16.f32.f16.f16 {%0, %1, %2, %3, %4, %5, %6, %7, %8, %9, %10, %11, %12, %13, %14, %15, %16, %17, %18, %19, %20, %21, %22, %23, %24, %25, %26, %27, %28, %29, %30, %31, %32, %33, %34, %35, %36, %37, %38, %39, %40, %41, %42, %43, %44, %45, %46, %47, %48, %49, %50, %51, %52, %53, %54, %55, %56, %57, %58, %59, %60, %61, %62, %63, %64, %65, %66, %67, %68, %69, %70, %71, %72, %73, %74, %75, %76, %77, %78, %79, %80, %81, %82, %83, %84, %85, %86, %87, %88, %89, %90, %91, %92, %93, %94, %95}, ta, tb, p1, 1, 1, 0, 1;\n"
        "add.s64 tb, tb0, 128;\n"
        "add.s64 ta, ta0, 4;\n"
        "wgmma.mma_async.sync.aligned.m64n192k16.f32.f16.f16 {%0, %1, %2, %3, %4, %5, %6, %7, %8, %9, %10, %11, %12, %13, %14, %15, %16, %17, %18, %19, %20, %21, %22, %23, %24, %25, %26, %27, %28, %29, %30, %31, %32, %33, %34, %35, %36, %37, %38, %39, %40, %41, %42, %43, %44, %45, %46, %47, %48, %49, %50, %51, %52, %53, %54, %55, %56, %57, %58, %59, %60, %61, %62, %63, %64, %65, %66, %67, %68, %69, %70, %71, %72, %73, %74, %75, %76, %77, %78, %79, %80, %81, %82, %83, %84, %85, %86, %87, %88, %89, %90, %91, %92, %93, %94, %95}, ta, tb, p1, 1, 1, 0, 1;\n"
        "add.s64 tb, tb0, 192;\n"
        "add.s64 ta, ta0, 6;\n"
        "wgmma.mma_async.sync.aligned.m64n192k16.f32.f16.f16 {%0, %1, %2, %3, %4, %5, %6, %7, %8, %9, %10, %11, %12, %13, %14, %15, %16, %17, %18, %19, %20, %21, %22, %23, %24, %25, %26, %27, %28, %29, %30, %31, %32, %33, %34, %35, %36, %37, %38, %39, %40, %41, %42, %43, %44, %45, %46, %47, %48, %49, %50, %51, %52, %53, %54, %55, %56, %57, %58, %59, %60, %61, %62, %63, %64, %65, %66, %67, %68, %69, %70, %71, %72, %73, %74, %75, %76, %77, %78, %79, %80, %81, %82, %83, %84, %85, %86, %87, %88, %89, %90, %91, %92, %93, %94, %95}, ta, tb, p1, 1, 1, 0, 1;\n"
        "add.s64 tb, tb0, 256;\n"
        "add.s64 ta, ta0, 512;\n"
        "wgmma.mma_async.sync.aligned.m64n192k16.f32.f16.f16 {%0, %1, %2, %3, %4, %5, %6, %7, %8, %9, %10, %11, %12, %13, %14, %15, %16, %17, %18, %19, %20, %21, %22, %23, %24, %25, %26, %27, %28, %29, %30, %31, %32, %33, %34, %35, %36, %37, %38, %39, %40, %41, %42, %43, %44, %45, %46, %47, %48, %49, %50, %51, %52, %53, %54, %55, %56, %57, %58, %59, %60, %61, %62, %63, %64, %65, %66, %67, %68, %69, %70, %71, %72, %73, %74, %75, %76, %77, %78, %79, %80, %81, %82, %83, %84, %85, %86, %87, %88, %89, %90, %91, %92, %93, %94, %95}, ta, tb, p1, 1, 1, 0, 1;\n"
        "add.s64 tb, tb0, 320;\n"
        "add.s64 ta, ta0, 514;\n"
        "wgmma.mma_async.sync.aligned.m64n192k16.f32.f16.f16 {%0, %1, %2, %3, %4, %5, %6, %7, %8, %9, %10, %11, %12, %13, %14, %15, %16, %17, %18, %19, %20, %21, %22, %23, %24, %25, %26, %27, %28, %29, %30, %31, %32, %33, %34, %35, %36, %37, %38, %39, %40, %41, %42, %43, %44, %45, %46, %47, %48, %49, %50, %51, %52, %53, %54, %55, %56, %57, %58, %59, %60, %61, %62, %63, %64, %65, %66, %67, %68, %69, %70, %71, %72, %73, %74, %75, %76, %77, %78, %79, %80, %81, %82, %83, %84, %85, %86, %87, %88, %89, %90, %91, %92, %93, %94, %95}, ta, tb, p1, 1, 1, 0, 1;\n"
        "add.s64 tb, tb0, 384;\n"
        "add.s64 ta, ta0, 516;\n"
        "wgmma.mma_async.sync.aligned.m64n192k16.f32.f16.f16 {%0, %1, %2, %3, %4, %5, %6, %7, %8, %9, %10, %11, %12, %13, %14, %15, %16, %17, %18, %19, %20, %21, %22, %23, %24, %25, %26, %27, %28, %29, %30, %31, %32, %33, %34, %35, %36, %37, %38, %39, %40, %41, %42, %43, %44, %45, %46, %47, %48, %49, %50, %51, %52, %53, %54, %55, %56, %57, %58, %59, %60, %61, %62, %63, %64, %65, %66, %67, %68, %69, %70, %71, %72, %73, %74, %75, %76, %77, %78, %79, %80, %81, %82, %83, %84, %85, %86, %87, %88, %89, %90, %91, %92, %93, %94, %95}, ta, tb, p1, 1, 1, 0, 1;\n"
        "add.s64 tb, tb0, 448;\n"
        "add.s64 ta, ta0, 518;\n"
        "wgmma.mma_async.sync.aligned.m64n192k16.f32.f16.f16 {%0, %1, %2, %3, %4, %5, %6, %7, %8, %9, %10, %11, %12, %13, %14, %15, %16, %17, %18, %19, %20, %21, %22, %23, %24, %25, %26, %27, %28, %29, %30, %31, %32, %33, %34, %35, %36, %37, %38, %39, %40, %41, %42, %43, %44, %45, %46, %47, %48, %49, %50, %51, %52, %53, %54, %55, %56, %57, %58, %59, %60, %61, %62, %63, %64, %65, %66, %67, %68, %69, %70, %71, %72, %73, %74, %75, %76, %77, %78, %79, %80, %81, %82, %83, %84, %85, %86, %87, %88, %89, %90, %91, %92, %93, %94, %95}, ta, tb, p1, 1, 1, 0, 1;\n"
        "add.s64 tb, tb0, 512;\n"
        "add.s64 ta, ta0, 1024;\n"
        "wgmma.mma_async.sync.aligned.m64n192k16.f32.f16.f16 {%0, %1, %2, %3, %4, %5, %6, %7, %8, %9, %10, %11, %12, %13, %14, %15, %16, %17, %18, %19, %20, %21, %22, %23, %24, %25, %26, %27, %28, %29, %30, %31, %32, %33, %34, %35, %36, %37, %38, %39, %40, %41, %42, %43, %44, %45, %46, %47, %48, %49, %50, %51, %52, %53, %54, %55, %56, %57, %58, %59, %60, %61, %62, %63, %64, %65, %66, %67, %68, %69, %70, %71, %72, %73, %74, %75, %76, %77, %78, %79, %80, %81, %82, %83, %84, %85, %86, %87, %88, %89, %90, %91, %92, %93, %94, %95}, ta, tb, p1, 1, 1, 0, 1;\n"
        "add.s64 tb, tb0, 576;\n"
        "add.s64 ta, ta0, 1026;\n"
        "wgmma.mma_async.sync.aligned.m64n192k16.f32.f16.f16 {%0, %1, %2, %3, %4, %5, %6, %7, %8, %9, %10, %11, %12, %13, %14, %15, %16, %17, %18, %19, %20, %21, %22, %23, %24, %25, %26, %27, %28, %29, %30, %31, %32, %33, %34, %35, %36, %37, %38, %39, %40, %41, %42, %43, %44, %45, %46, %47, %48, %49, %50, %51, %52, %53, %54, %55, %56, %57, %58, %59, %60, %61, %62, %63, %64, %65, %66, %67, %68, %69, %70, %71, %72, %73, %74, %75, %76, %77, %78, %79, %80, %81, %82, %83, %84, %85, %86, %87, %88, %89, %90, %91, %92, %93, %94, %95}, ta, tb, p1, 1, 1, 0, 1;\n"
        "add.s64 tb, tb0, 640;\n"
        "add.s64 ta, ta0, 1028;\n"
        "wgmma.mma_async.sync.aligned.m64n192k16.f32.f16.f16 {%0, %1, %2, %3, %4, %5, %6, %7, %8, %9, %10, %11, %12, %13, %14, %15, %16, %17, %18, %19, %20, %21, %22, %23, %24, %25, %26, %27, %28, %29, %30, %31, %32, %33, %34, %35, %36, %37, %38, %39, %40, %41, %42, %43, %44, %45, %46, %47, %48, %49, %50, %51, %52, %53, %54, %55, %56, %57, %58, %59, %60, %61, %62, %63, %64, %65, %66, %67, %68, %69, %70, %71, %72, %73, %74, %75, %76, %77, %78, %79, %80, %81, %82, %83, %84, %85, %86, %87, %88, %89, %90, %91, %92, %93, %94, %95}, ta, tb, p1, 1, 1, 0, 1;\n"
        "add.s64 tb, tb0, 704;\n"
        "add.s64 ta, ta0, 1030;\n"
        "wgmma.mma_async.sync.aligned.m64n192k16.f32.f16.f16 {%0, %1, %2, %3, %4, %5, %6, %7, %8, %9, %10, %11, %12, %13, %14, %15, %16, %17, %18, %19, %20, %21, %22, %23, %24, %25, %26, %27, %28, %29, %30, %31, %32, %33, %34, %35, %36, %37, %38, %39, %40, %41, %42, %43, %44, %45, %46, %47, %48, %49, %50, %51, %52, %53, %54, %55, %56, %57, %58, %59, %60, %61, %62, %63, %64, %65, %66, %67, %68, %69, %70, %71, %72, %73, %74, %75, %76, %77, %78, %79, %80, %81, %82, %83, %84, %85, %86, %87, %88, %89, %90, %91, %92, %93, %94, %95}, ta, tb, p1, 1, 1, 0, 1;\n"
        "}\n"
        : "+f"(d[0]), "+f"(d[1]), "+f"(d[2]), "+f"(d[3]), "+f"(d[4]), "+f"(d[5]), "+f"(d[6]), "+f"(d[7]), "+f"(d[8]), "+f"(d[9]), "+f"(d[10]), "+f"(d[11]), "+f"(d[12]), "+f"(d[13]), "+f"(d[14]), "+f"(d[15]), "+f"(d[16]), "+f"(d[17]), "+f"(d[18]), "+f"(d[19]), "+f"(d[20]), "+f"(d[21]), "+f"(d[22]), "+f"(d[23]), "+f"(d[24]), "+f"(d[25]), "+f"(d[26]), "+f"(d[27]), "+f"(d[28]), "+f"(d[29]), "+f"(d[30]), "+f"(d[31]), "+f"(d[32]), "+f"(d[33]), "+f"(d[34]), "+f"(d[35]), "+f"(d[36]), "+f"(d[37]), "+f"(d[38]), "+f"(d[39]), "+f"(d[40]), "+f"(d[41]), "+f"(d[42]), "+f"(d[43]), "+f"(d[44]), "+f"(d[45]), "+f"(d[46]), "+f"(d[47]), "+f"(d[48]), "+f"(d[49]), "+f"(d[50]), "+f"(d[51]), "+f"(d[52]), "+f"(d[53]), "+f"(d[54]), "+f"(d[55]), "+f"(d[56]), "+f"(d[57]), "+f"(d[58]), "+f"(d[59]), "+f"(d[60]), "+f"(d[61]), "+f"(d[62]), "+f"(d[63]), "+f"(d[64]), "+f"(d[65]), "+f"(d[66]), "+f"(d[67]), "+f"(d[68]), "+f"(d[69]), "+f"(d[70]), "+f"(d[71]), "+f"(d[72]), "+f"(d[73]), "+f"(d[74]), "+f"(d[75]), "+f"(d[76]), "+f"(d[77]), "+f"(d[78]), "+f"(d[79]), "+f"(d[80]), "+f"(d[81]), "+f"(d[82]), "+f"(d[83]), "+f"(d[84]), "+f"(d[85]), "+f"(d[86]), "+f"(d[87]), "+f"(d[88]), "+f"(d[89]), "+f"(d[90]), "+f"(d[91]), "+f"(d[92]), "+f"(d[93]), "+f"(d[94]), "+f"(d[95])
        : "l"(descA), "n"(AOFF >> 4), "l"(descB), "n"(BOFF >> 4));
}

struct Params {
    const __nv_bfloat16* x;
    const __nv_bfloat16* wqkv;
    const __nv_bfloat16* wo;
    const __nv_bfloat16* logit_scale;
    const __nv_bfloat16* cpb_w1;
    const __nv_bfloat16* cpb_w2;
    const __nv_bfloat16* rel_coords;
    const int*           rel_idx;
    const __nv_bfloat16* mask;
    __nv_bfloat16*       out;
    unsigned long long   z1;
    int                  npair;
    uint32_t             need;
    int                  nq, nr;
    int                  spread;
    int                  t1;
};

__device__ __forceinline__ int role_of(const Params& P, int b) {
    const int n0 = (b * P.spread) >> 16, n1 = ((b + 1) * P.spread) >> 16;
    return n1 != n0 ? 2 * P.npair + n0 : b - n0;
}
__device__ __forceinline__ void finish(uint32_t total) {
    __threadfence();
    if (atomicAdd(&g_done, 1u) == total - 1) {
        for (int i = 0; i < NWS; i++) g_cnt[i] = 0;
        g_done = 0;
    }
}

constexpr int FB_PITCH = 584, FB_X = TOK * FB_PITCH * 2, FB_TAB = FB_X + TOK * 384, FB_BYTES = FB_TAB + 169 * 8 + 8;
static_assert(3 * FB_BYTES <= SM_PBAR && FB_BYTES % 16 == 0 && SM_BAR + B_ROWS == SM_PBAR + 64 && PCHUNK, "smem");
__device__ __forceinline__ void redo(const Params& P, uint8_t* sm, uint32_t tag, int barid) {
    typedef __nv_bfloat16 bf;
    const int t = threadIdx.x & 127, lane = t & 31;
    bf* const qkv = reinterpret_cast<bf*>(sm);
    bf* const xs = reinterpret_cast<bf*>(sm + FB_X);
    bf* const tab = reinterpret_cast<bf*>(sm + FB_TAB);
    volatile int* const next = reinterpret_cast<volatile int*>(sm + FB_TAB + 169 * 8);
#pragma unroll 1
    for (uint32_t n = 0; n < (1u << 22); n++) {
        uint32_t a;
        asm volatile("ld.acquire.gpu.global.u32 %0, [%1];\n" : "=r"(a) : "l"(g_guard) : "memory");
        if (a == tag + 1) break;
        __nanosleep(256);
    }
    asm volatile("fence.proxy.async;\n" ::: "memory");
#pragma unroll 1
    for (int i = t; i < 169 * 4; i += 128) {
        float a = 0.f;
#pragma unroll 1
        for (int u = 0; u < 16; u++) {
            const float h = round_bf16(__bfloat162float(P.rel_coords[(i >> 2) * 2]) * __bfloat162float(P.cpb_w1[u]) +
                                       __bfloat162float(P.rel_coords[(i >> 2) * 2 + 1]) * __bfloat162float(P.cpb_w1[16 + u]));
            a += (h > 0.f ? h : h * 0.f) * __bfloat162float(P.cpb_w2[u * 4 + (i & 3)]);
        }
        tab[i] = __float2bfloat16_rn(16.f * round_bf16(1.f / (1.f + expf(-round_bf16(a)))));
    }
#pragma unroll 1
    for (;;) {
        wg_bar(barid);
        if (t == 0) *next = (int)atomicAdd(g_guard + 2, 1u);
        wg_bar(barid);
        const int win = *next;
        if (win >= NWINDOWS) return;
        const int y0 = 7 * (win / NWS) + 3, x0 = 7 * (win % NWS) + 3;
        auto pixel = [&](int r) { return (size_t)(((y0 + r / 7) % IMG) * IMG + (x0 + r % 7) % IMG) * 192; };
#pragma unroll 1
        for (int i = t; i < TOK * 24; i += 128)
            reinterpret_cast<uint4*>(xs)[i] = reinterpret_cast<const uint4*>(P.x + pixel(i / 24))[i % 24];
#pragma unroll 1
        for (int ph = 0; ph < 2; ph++) {
            const bf* const a = ph ? qkv : xs;
            bf* const d = ph ? xs : qkv;
            const int n = ph ? 192 : 576, pa = ph ? FB_PITCH : 192, pd = ph ? 192 : FB_PITCH;
            wg_bar(barid);
#pragma unroll 1
            for (int col = t; col < n; col += 128) {
                const bf* w = (ph ? P.wo : P.wqkv) + col;
                float acc[TOK];
#pragma unroll
                for (int r = 0; r < TOK; r++) acc[r] = 0.f;
#pragma unroll 1
                for (int k = 0; k < 192; k += 2) {
                    const float w0 = __bfloat162float(w[k * n]), w1 = __bfloat162float(w[(k + 1) * n]);
#pragma unroll
                    for (int r = 0; r < TOK; r++) {
                        const uint32_t v = *reinterpret_cast<const uint32_t*>(a + r * pa + k);
                        acc[r] = fmaf(bf16hi(v), w1, fmaf(bf16lo(v), w0, acc[r]));
                    }
                }
#pragma unroll
                for (int r = 0; r < TOK; r++) d[r * pd + col] = __float2bfloat16_rn(acc[r]);
            }
            wg_bar(barid);
            if (ph) break;
#pragma unroll 1
            for (int i = t; i < TOK * 8; i += 128) {
                bf* const v = qkv + (i % TOK) * FB_PITCH + (i / TOK) * 48;
                float s = 0.f;
#pragma unroll 1
                for (int j = 0; j < 48; j++) s = fmaf(__bfloat162float(v[j]), __bfloat162float(v[j]), s);
                s = round_bf16(1.f / sqrtf(round_bf16(round_bf16(s) + 1e-12f)));
#pragma unroll 1
                for (int j = 0; j < 48; j++) v[j] = __float2bfloat16_rn(__bfloat162float(v[j]) * s);
            }
            wg_bar(barid);
#pragma unroll 1
            for (int i = t; i < TOK * 4; i += 128) {
                const int r = i % TOK, h = i / TOK;
                uint32_t* const q = reinterpret_cast<uint32_t*>(qkv + r * FB_PITCH + h * 48);
                const float tau = round_bf16(expf(round_bf16(fminf(fmaxf(__bfloat162float(P.logit_scale[h]), -100.f), 4.6052f))));
                float v[48], mx = -INFINITY, sum = 0.f;
#pragma unroll
                for (int j = 0; j < 24; j++) { v[2 * j] = bf16lo(q[j]); v[2 * j + 1] = bf16hi(q[j]); }
#pragma unroll 1
                for (int j = 0; j < TOK; j++) {
                    const uint32_t* kk = reinterpret_cast<const uint32_t*>(qkv + j * FB_PITCH + 192 + h * 48);
                    float s = 0.f;
#pragma unroll
                    for (int u = 0; u < 24; u++) s = fmaf(v[2 * u + 1], bf16hi(kk[u]), fmaf(v[2 * u], bf16lo(kk[u]), s));
                    s = round_bf16(round_bf16(s) * tau);
                    s = round_bf16(s + __bfloat162float(tab[min(max(P.rel_idx[r * TOK + j], 0), 168) * 4 + h]));
                    s = round_bf16(s + __bfloat162float(P.mask[(size_t)win * (TOK * TOK) + r * TOK + j]));
                    xs[j * 128 + t] = __float2bfloat16_rn(s);
                    mx = fmaxf(mx, s);
                }
#pragma unroll 1
                for (int j = 0; j < TOK; j++) sum += expf(__bfloat162float(xs[j * 128 + t]) - mx);
#pragma unroll
                for (int j = 0; j < 48; j++) v[j] = 0.f;
#pragma unroll 1
                for (int j = 0; j < TOK; j++) {
                    const uint32_t* vv = reinterpret_cast<const uint32_t*>(qkv + j * FB_PITCH + 384 + h * 48);
                    const float p = round_bf16(expf(__bfloat162float(xs[j * 128 + t]) - mx) / sum);
#pragma unroll
                    for (int u = 0; u < 24; u++) {
                        v[2 * u] = fmaf(p, bf16lo(vv[u]), v[2 * u]);
                        v[2 * u + 1] = fmaf(p, bf16hi(vv[u]), v[2 * u + 1]);
                    }
                }
#pragma unroll
                for (int j = 0; j < 24; j++) q[j] = pack_bf16(v[2 * j], v[2 * j + 1]);
            }
        }
#pragma unroll 1
        for (int r = t >> 5; r < TOK; r += 4) {
            float v[6], m = 0.f, s = 0.f;
#pragma unroll
            for (int j = 0; j < 6; j++) { v[j] = __bfloat162float(xs[r * 192 + j * 32 + lane]); m += v[j]; }
#pragma unroll
            for (int o = 16; o; o >>= 1) m += __shfl_xor_sync(0xffffffffu, m, o);
            m *= 1.f / 192.f;
#pragma unroll
            for (int j = 0; j < 6; j++) s = fmaf(v[j] - m, v[j] - m, s);
#pragma unroll
            for (int o = 16; o; o >>= 1) s += __shfl_xor_sync(0xffffffffu, s, o);
            s = round_bf16(sqrtf(round_bf16(round_bf16(s * (1.f / 192.f)) + 1e-5f)));
            m = round_bf16(m);
#pragma unroll
            for (int j = 0; j < 6; j++) P.out[pixel(r) + j * 32 + lane] = __float2bfloat16_rn(round_bf16(v[j] - m) / s);
        }
    }
}

__global__ void __launch_bounds__(NTHREADS, 1)
swin_window_attn_kernel(const Params P, const __grid_constant__ CUtensorMap xmap, const __grid_constant__ CUtensorMap xmap4,
                        const __grid_constant__ CUtensorMap xmap3,
                        const __grid_constant__ CUtensorMap omap, const __grid_constant__ CUtensorMap wmap,
                        const __grid_constant__ CUtensorMap smap, const __grid_constant__ CUtensorMap omapb,
                        const __grid_constant__ CUtensorMap xmapa, const __grid_constant__ CUtensorMap xmapb,
                        const __grid_constant__ CUtensorMap smap3, const __grid_constant__ CUtensorMap wraw) {
    extern __shared__ __align__(1024) uint8_t smem[];
    constexpr uint32_t sbase = 1024;
    if (smem_u32(smem) != sbase) return;
    const int tid = threadIdx.x;
    const int wg = __shfl_sync(0xffffffffu, tid >> 7, 0);
    const int warp = __shfl_sync(0xffffffffu, (tid >> 5) & 3, 0);
    const int lane = tid & 31;
    const int g = lane >> 2, c = lane & 3;

    TR(26, wg);
    const int role = role_of(P, blockIdx.x);
    const bool attn = role < 2 * P.npair;
    const int pair = role >> 1, half = role & 1;
    const int nwin = P.nq + (pair < P.nr ? 1 : 0);
    const int ntiles = (nwin * TOK + 63) >> 6;
    const uint32_t bars = sbase + SM_BAR;
    const int t0 = min(warp * 16 + g, TOK - 1), t1 = min(warp * 16 + g + 8, TOK - 1);
    int ridx[26];
    uint32_t rc, w2[16];
    uint4 w1[4];
    if (attn && (wg == 1 || wg == 2)) {
        rc = reinterpret_cast<const uint32_t*>(P.rel_coords)[min(tid - 128, 168)];
#pragma unroll
        for (int i = 0; i < 4; i++) w1[i] = reinterpret_cast<const uint4*>(P.cpb_w1)[i];
#pragma unroll
        for (int u = 0; u < 16; u++) w2[u] = reinterpret_cast<const uint32_t*>(P.cpb_w2)[2 * u + half];
#pragma unroll
        for (int rh = 0; rh < 2; rh++) {
            const int* ri = P.rel_idx + (rh ? t1 : t0) * TOK;
#pragma unroll
            for (int j = 0; j < 12; j++) ridx[13 * rh + j] = ri[8 * (j >> 1) + 2 * c + (j & 1)];
            ridx[13 * rh + 12] = ri[48];
        }
    }
    {
        if (tid == 416) {
            const CUtensorMap* maps[4] = {attn ? &smap : &omap, &smap3, &xmapa, &xmapb};
#pragma unroll
            for (int i = 0; i < 4; i++) asm volatile("prefetch.tensormap [%0];\n" :: "l"(reinterpret_cast<uint64_t>(maps[i])) : "memory");
        }
        if (tid == 384) {
            for (int b = 0; b < 4; b++) {
                mbar_init(bars + B_XFULL + b * 8, 2);
                mbar_init(bars + B_QKRAW + b * 8, 4);
                mbar_init(bars + B_VRAW + b * 8, 4);
                mbar_init(bars + B_VFREE + b * 8, 2);
                mbar_init(bars + B_QKFREE + b * 8, 4);
                mbar_init(bars + B_ODONE + b * 8, 4);
            }
            mbar_init(bars + B_MFULL, 1);
            sts32(bars + B_MSTATE, 0);
            sts32(bars + B_ROWS, 0xFFFFFFFFu);
            mbar_init(bars + B_MCONS, 4);
            mbar_init(bars + B_WFULL, 2);
            mbar_init(bars + B_WRAW, 1);
            mbar_init(bars + B_XCONS, 4);
            for (int b = 0; b < 4; b++) mbar_init(bars + B_STORED + b * 8, 1);
            for (int b = 0; b < 6; b++) {
                mbar_init(sbase + SM_PBAR + b * 8, 1);
                if (PCHUNK) sts32(sbase + SM_PBAR + 48, 0); else
                mbar_init(sbase + SM_PBAR + 48 + b * 8, PSTORE ? 1 : 4);
                mbar_init(sbase + SM_PBAR + 104 + b * 8, 4);
            }
            mbar_init(sbase + SM_PBAR + 96, 13);
            mbar_init(sbase + SM_PBAR + 56, 12);
            asm volatile("fence.mbarrier_init.release.cluster;\n" ::: "memory");
        }
        if (wg == 3) {
            if (attn) *reinterpret_cast<uint4*>(smem + SM_V + warp * V_STRIDE + (lane < 16 ? lane * 16 : V_STRIDE - 64 + (lane & 3) * 16)) = make_uint4(0, 0, 0, 0);
            fence_async_smem();
        }
        __syncthreads();
        TR(26, 4 + wg);
            if (attn && tid == 0) {
                const int nw = 4;
                mbar_arrive_expect_tx(bars + B_WRAW, nw * 96 * O_PITCH);
                TR(26, 30);
#pragma unroll
                for (int i = 0; i < 4; i++) if (i < nw) {
                    const int q = (i + pair) & 3;
                    tma_3d(sbase + q * 96 * O_PITCH, &wraw, bars + B_WRAW, 0, 2 * (q >> 1) + half, (q & 1) * 96);
                    TR(26, 31 + i);
                }
                int wh = 0, ww = pair;
#pragma unroll
                for (int j = 0; j < NEARLY; j++) {
                    if (ww < NWS - 1) {
                        const uint32_t bar = bars + B_XFULL + (j ? j - 1 : 0) * 8;
                        if (j >= 2) mbar_arrive(bar);
                        mbar_arrive_expect_tx(bar, 3 * XCH);
#pragma unroll
                        for (int ch = 0; ch < 3; ch++)
                            tma_3d(sbase + SM_QK + ((j + 3) & 3) * XCH + ch * QK_CHUNK, &xmap, bar, ch * 64, 7 * ww + 3, 7 * wh + 3);
                    }
                    ww += P.npair; if (ww >= NWS) { ww -= NWS; wh++; }
                    TR(26, 40 + j);
                    if (j == 1) {
                        mbar_arrive_expect_tx(bars + B_MFULL, 4816);
                        asm volatile("cp.async.bulk.shared::cluster.global.mbarrier::complete_tx::bytes [%0], [%1], 4816, [%2];\n"
                                     :: "r"(sbase + SM_MASK), "l"(reinterpret_cast<const char*>(P.mask) + (((uint32_t)pair * 4802u) & ~15u)),
                                        "r"(bars + B_MFULL) : "memory");
                        mbar_arrive_expect_tx(bars + B_WFULL, 5 * W_ATOM);
#pragma unroll
                        for (int a = 1; a < 6; a++)
                            tma_2d(sbase + SM_WV + a * W_ATOM, &wmap, bars + B_WFULL, 384 + half * 96 + a * 16, 0);
                        TR(26, 50);
                    }
                }
            }
        __syncwarp();
        TR(26, 13);
    }

    auto permute_w = [&]() {
        uint4 w[3][4];
        TR(26, 16 + wg);
        mbar_wait(bars + B_WRAW, 0);
        TR(26, 20 + wg);
#pragma unroll
        for (int it = 0; it < 3; it++) {
            const int o = ((tid >> 5) * 3 + it) * 4 + (lane >> 3);
            const uint8_t* src = smem + ((o / 6) * 8 + (lane & 7)) * O_PITCH + (o % 6) * 16;
#pragma unroll
            for (int m = 0; m < 4; m++) w[it][m] = *reinterpret_cast<const uint4*>(src + (m >> 1) * 192 * O_PITCH + (m & 1) * 96);
        }
        asm volatile("bar.sync 2, 384;\n" ::: "memory");
        if (tid == 0) {
            fence_async_smem();
            TR(26, 24);
            mbar_arrive_expect_tx(bars + B_WFULL, W_ATOM);
            tma_2d(sbase + SM_WV, &wmap, bars + B_WFULL, 384 + half * 96, 0);
        }
#pragma unroll
        for (int it = 0; it < 3; it++) {
            const int o = ((tid >> 5) * 3 + it) * 4 + (lane >> 3);
            const uint32_t d = sbase + (o % 6) * 2 * W_ATOM + ((o / 6) * 8 + (lane & 7)) * 32 + ((lane >> 2) & 1) * 16;
            sts128(d, bf2h(w[it][0].x), bf2h(w[it][1].x), bf2h(w[it][2].x), bf2h(w[it][3].x));
            sts128(d ^ 16, bf2h(w[it][0].y), bf2h(w[it][1].y), bf2h(w[it][2].y), bf2h(w[it][3].y));
            sts128(d + W_ATOM, bf2h(w[it][0].z), bf2h(w[it][1].z), bf2h(w[it][2].z), bf2h(w[it][3].z));
            sts128((d ^ 16) + W_ATOM, bf2h(w[it][0].w), bf2h(w[it][1].w), bf2h(w[it][2].w), bf2h(w[it][3].w));
        }
    };
    static_assert(2 * 192 * O_PITCH <= 13 * W_ATOM, "raw weights");
    const uint32_t nfinish = gridDim.x + (POLLER ? 0 : 2 * P.npair);
#define PROJ_SCHEDULE                                                                                   \
    int bid = blockIdx.x;                                                                               \
    asm volatile("" : "+r"(bid));                      \
    bid = role_of(P, bid);                                                                              \
    const bool at = bid < 2 * P.npair;                                                                  \
    const int tile0 = at ? P.t1 + bid : bid - 2 * P.npair;                                              \
    const int tstep = at ? 2 * P.npair : (int)gridDim.x - 2 * P.npair;                                  \
    const int tend = at ? TILES : P.t1;
    if (wg == 3) {
        asm volatile("setmaxnreg.dec.sync.aligned.u32 %0;\n" :: "n"(REG_H));
        if (warp == 1 && attn) {
            const uint16_t mlast = reinterpret_cast<const uint16_t*>(P.mask)[NWINDOWS * TOK * TOK - 1];
            const uint32_t ma = sbase + SM_MASK + lane * 16, mb = sbase + SM_MASK + min(288 + lane, 300) * 16;
            uint32_t ph = 0;
#pragma unroll 1
            for (int k = 0; k < nwin; k++) {
                mbar_wait(bars + B_MFULL, k & 1);
                uint32_t acc = 0;
#pragma unroll
                for (int i = 0; i < 10; i += MRND) {
                    uint32_t w[MRND][4];
#pragma unroll
                    for (int j = 0; j < MRND; j++) if (i + j < 10) lds128(w[j], i + j < 9 ? ma + (i + j) * 512 : mb);
#pragma unroll
                    for (int j = 0; j < MRND; j++) if (i + j < 10) acc |= w[j][0] | w[j][1] | w[j][2] | w[j][3];
                    asm volatile("" : "+r"(acc) :: "memory");
                }
                const uint32_t nz = __any_sync(0xffffffffu, (acc & 0x7FFF7FFFu) != 0) ? 1 : 0;
                if (lane == 0) asm volatile("st.volatile.shared.b32 [%0], %1;\n" :: "r"(bars + B_MSTATE), "r"(2 * k + 2 - nz) : "memory");
                if (nz) { mbar_wait(bars + B_MCONS, ph); ph ^= 1; fence_async_smem(); }
                if (k + 1 < nwin && elect_one()) {
                    const int win = pair + (k + 1) * P.npair;
                    uint32_t bytes = 4816;
                    if (win == NWINDOWS - 1) {
                        bytes = 4800;
                        asm volatile("st.shared.u16 [%0], %1;\n" :: "r"(sbase + SM_MASK + 4800), "h"(mlast) : "memory");
                    }
                    TR(25, k + 1);
                    mbar_arrive_expect_tx(bars + B_MFULL, bytes);
                    asm volatile("cp.async.bulk.shared::cluster.global.mbarrier::complete_tx::bytes [%0], [%1], %2, [%3];\n"
                                 :: "r"(sbase + SM_MASK),
                                    "l"(reinterpret_cast<const char*>(P.mask) + (((uint32_t)win * 4802u) & ~15u)),
                                    "r"(bytes), "r"(bars + B_MFULL) : "memory");
                    if (MPF && half == (k & 1) && k + 1 + MPF < nwin)
                        asm volatile("cp.async.bulk.prefetch.L2.global [%0], %1;\n"
                                     :: "l"(reinterpret_cast<const char*>(P.mask) + (((uint32_t)(win + MPF * P.npair) * 4802u) & ~15u)),
                                        "r"(4800) : "memory");
                }
                __syncwarp();
            }
        }
        if (!elect_one()) return;
        if (warp == 0) {
          if (attn) {
            const int kmax = (64 * ntiles + 63) / TOK;
            int wh = 0, ww = pair;
            int ph2 = (pair + PF_DIST * P.npair) / NWS, pw2 = pair + PF_DIST * P.npair - ph2 * NWS;
#pragma unroll 1
            for (int k = -4; k + 4 <= kmax; k++) {
                const int row0 = (k + 4) * TOK;
                const uint32_t dst = sbase + SM_QK + ((k + 3) & 3) * XCH, bar = bars + B_XFULL + ((row0 >> 6) & 3) * 8;
                const bool alone = (row0 & 63) >= 64 - TOK && (row0 & 63) < TOK;
                const int x0 = 7 * ww + 3, y0 = 7 * wh + 3;
                const bool done = k < NEARLY - 4 && ww < NWS - 1;
                if (k >= 0) mbar_wait(bars + B_QKFREE + ((k + 3) & 3) * 8, (k >> 2) & 1);
                if (alone && !done) mbar_arrive(bar);
                if (row0 >= 64 * ntiles || ((EXP & 32) && k >= 0)) {
                    mbar_arrive(bar);
                    continue;
                }
                TR(20, k + 4);
                const bool inner = wh < NWS - 1 && ww < NWS - 1;
                if (done) {
                } else if (XSPLIT && inner && (row0 & 63) >= 64 - 21) {
                    const uint32_t bar2 = bars + B_XFULL + (((row0 >> 6) + 1) & 3) * 8;
                    mbar_arrive_expect_tx(bar, 3 * 21 * 128);
#pragma unroll
                    for (int ch = 0; ch < 3; ch++) tma_3d(dst + ch * QK_CHUNK, &xmapa, bar, ch * 64, x0, y0);
                    asm volatile("mbarrier.expect_tx.relaxed.cta.shared::cta.b64 [%0], %1;\n" :: "r"(bar2), "r"(3 * 28 * 128) : "memory");
#pragma unroll
                    for (int ch = 0; ch < 3; ch++) tma_3d(dst + ch * QK_CHUNK + 21 * 128, &xmapb, bar2, ch * 64, x0, y0 + 3);
                } else if (inner) {
                    mbar_arrive_expect_tx(bar, 3 * XCH);
#pragma unroll
                    for (int ch = 0; ch < 3; ch++) tma_3d(dst + ch * QK_CHUNK, &xmap, bar, ch * 64, x0, y0);
                } else if (ww < NWS - 1) {
                    mbar_arrive_expect_tx(bar, 3 * XCH);
#pragma unroll
                    for (int ch = 0; ch < 3; ch++) {
                        tma_3d(dst + ch * QK_CHUNK, &xmapb, bar, ch * 64, x0, y0);
                        tma_3d(dst + ch * QK_CHUNK + 28 * 128, &xmapa, bar, ch * 64, x0, 0);
                    }
                } else {
                    mbar_arrive_expect_tx(bar, 3 * XCH);
                    const int x1 = (ww == NWS - 1) ? 0 : x0 + 4;
#pragma unroll 1
                    for (int i = 0; i < 7; i++) {
                        const int y = (y0 + i >= IMG) ? y0 + i - IMG : y0 + i;
#pragma unroll
                        for (int ch = 0; ch < 3; ch++) {
                            tma_3d(dst + ch * QK_CHUNK + i * 896, &xmap4, bar, ch * 64, x0, y);
                            tma_3d(dst + ch * QK_CHUNK + i * 896 + 512, &xmap3, bar, ch * 64, x1, y);
                        }
                    }
                }
                if (NOPF) {
                } else if (half == 0) {
                    if (ph2 < NWS) {
#pragma unroll
                        for (int ch = 0; ch < 3; ch++)
                            asm volatile("cp.async.bulk.prefetch.tensor.3d.L2.global.tile [%0, {%1, %2, %3}];\n"
                                         :: "l"(reinterpret_cast<uint64_t>(&xmap)), "r"(ch * 64), "r"(7 * pw2 + 3), "r"(7 * ph2 + 3)
                                         : "memory");
                    }
                }
                if (k + 5 < nwin) {
                    ww += P.npair; if (ww >= NWS) { ww -= NWS; wh++; }
                }
                pw2 += P.npair; if (pw2 >= NWS) { pw2 -= NWS; ph2++; }
            }
            mbar_wait(sbase + SM_PBAR + 96, 0);
            fence_async_smem();
          }
            PROJ_SCHEDULE
            int st = 0, ready = -1, want = -6 * PSM, freed = 0;
            uint32_t ph = 1;
#pragma unroll 1
            for (int t = tile0; t < tend; t += tstep) {
                const int p0 = (t < TILES_A) ? SEG_B + 64 * (t & PWRAP) : 64 * (t - TILES_A);
                const int w1 = (t < TILES_A) ? min((64 * t + 63) / (7 * IMG), NWS - 1) : NWS - 1;
#pragma unroll 1
                for (uint32_t n = 0; n < (1u << 24) && ready < w1; n++) ready = (int)lds32v(bars + B_ROWS);
#pragma unroll
                for (int ch = 0; ch < PSM; ch++) {
                    want++;
#pragma unroll 1
                    for (uint32_t n = 0; n < (1u << 22) && freed < want; n++) freed = (int)lds32v(sbase + SM_PBAR + 48);
                    if (ch == 0) mbar_arrive_expect_tx(sbase + SM_PBAR + st * 8, STAGE_BYTES);
                    tma_2d(sbase + SM_STAGE + st * STAGE_BYTES + ch * 8192, &omap, sbase + SM_PBAR + st * 8, ch * 64, p0);
                    if (ch == 0) {
#pragma unroll
                        for (int c2 = PSM; c2 < 3; c2++)
                            tma_2d(sbase + SM_STAGE + st * STAGE_BYTES + c2 * 8192, &omap, sbase + SM_PBAR + st * 8, c2 * 64, p0);
                    }
                }
                if (++st == 6) st = 0;
            }
            if (!POLLER) finish(nfinish);
        } else if (warp == 2 && (POLLER || attn)) {
            int wh = 0, ww = pair;
            uint32_t rows = 0;
#pragma unroll 1
            for (int k = 0; k < (attn ? nwin : 0); k++) {
                mbar_wait(bars + B_STORED + (k & 1) * 8, (k >> 1) & 1);
                mbar_arrive(bars + B_PUBD + (k & 1) * 8);
                rows = rows * 128 + wh + 1;
                if (rows >= (1u << (7 * PUBN - 7)) || k < 2 || k + PUBT >= nwin) {
                    asm volatile("fence.acq_rel.gpu;\n" ::: "memory");
#pragma unroll 1
                    for (; rows; rows >>= 7)
                        asm volatile("red.relaxed.gpu.global.add.u32 [%0], 1;\n" :: "l"(g_cnt + ((rows & 127) - 1)) : "memory");
                }
                TR(24, k);
                ww += P.npair; if (ww >= NWS) { ww -= NWS; wh++; }
            }
            const int r1 = attn ? NWS - 1 : min((64 * P.t1 - 1) / (7 * IMG), NWS - 1);
#pragma unroll 1
            for (int r = attn ? min(64 * P.t1 / (7 * IMG), NWS - 1) : 0; r <= r1; r++) {
#pragma unroll 1
                for (uint32_t n = 0; n < (1u << 22); n++) {
                    uint32_t a;
                    asm volatile("ld.acquire.gpu.global.u32 %0, [%1];\n" : "=r"(a) : "l"(g_cnt + r) : "memory");
                    if (a >= P.need) break;
                    __nanosleep(64);
                }
                asm volatile("fence.proxy.async.global;\n" ::: "memory");
                asm volatile("st.volatile.shared.b32 [%0], %1;\n" :: "r"(bars + B_ROWS), "r"(r) : "memory");
            }
            finish(nfinish);
        } else if (warp == 3 && attn) {
            for (int t = 0; t < 3; t++) mbar_arrive_n(bars + B_VFREE + t * 8, 2);
            int wh = 0, ww = pair;
#pragma unroll 1
            for (int k = 0; k < nwin; k++) {
                const uint32_t src = sbase + SM_V + (k & 3) * V_STRIDE;
                const int x0 = 7 * ww + 3, y0 = 7 * wh + 3;
                mbar_wait(bars + B_ODONE + (k & 3) * 8, (k >> 2) & 1);
                fence_async_smem();
                TR(22, k);
#if !(EXP & 4)
                tma_store_4d(&smap, src, 0, half, x0, y0);
                tma_store_4d(&smap3, src + 28 * O_PITCH + 64, 0, half, x0, wh == NWS - 1 ? 0 : y0 + 4);
#endif
                if (ww == NWS - 1) {
#pragma unroll 1
                    for (int i = 0; i < 7; i++) {
                        char* const d = reinterpret_cast<char*>(P.out) + (uint32_t)((y0 + i >= IMG ? y0 + i - IMG : y0 + i) * IMG) * 384u + half * 192;
#pragma unroll
                        for (int j = 0; j < 3; j++)
                            asm volatile("cp.async.bulk.global.shared::cta.bulk_group [%0], [%1], 192;\n"
                                         :: "l"(d + j * 384), "r"(src + (7 * i + 4 + j) * O_PITCH + (i >= 4 ? 64 : 0)) : "memory");
                    }
                }
                asm volatile("cp.async.bulk.commit_group;\n" ::: "memory");
                asm volatile("cp.async.bulk.wait_group.read 0;\n" ::: "memory");
                {
                    const int row0 = (k + 4) * TOK;
                    mbar_arrive_n(bars + B_VFREE + ((row0 >> 6) & 3) * 8, ((row0 & 63) >= 64 - TOK && (row0 & 63) < TOK) ? 2 : 1);
                }
                TR(23, k);
                asm volatile("cp.async.bulk.wait_group 0;\n" ::: "memory");
                asm volatile("fence.proxy.async.global;\n" ::: "memory");
                mbar_wait(bars + B_PUBD + (k & 1) * 8, ((k >> 1) + 1) & 1);
                mbar_arrive(bars + B_STORED + (k & 1) * 8);
                ww += P.npair; if (ww >= NWS) { ww -= NWS; wh++; }
            }
            mbar_arrive(sbase + SM_PBAR + 96);
        }
        if (PSTORE && warp == 1) {
            PROJ_SCHEDULE
            int st = 0, prev = -1, done = 0;
            uint32_t ph = 0;
            if (bid == gridDim.x - 1) { g_guard[2] = 0; __threadfence(); }
#pragma unroll 1
            for (int t = tile0; t < tend; t += tstep) {
                const int p0 = (t < TILES_A) ? SEG_B + 64 * (t & PWRAP) : 64 * (t - TILES_A);
                mbar_wait(sbase + SM_PBAR + 104 + st * 8, ph);
                fence_async_smem();
                if (!at) TR(22, (t - tile0) / tstep);
#pragma unroll
                for (int ch = 0; ch < PSM; ch++) {
                    asm volatile("cp.async.bulk.tensor.2d.global.shared::cta.tile.bulk_group [%0, {%2, %3}], [%1];\n"
                                 :: "l"(reinterpret_cast<uint64_t>(t < TILES_A ? &omap : &omapb)),
                                    "r"(sbase + SM_STAGE + st * STAGE_BYTES + ch * 8192), "r"(ch * 64), "r"(p0) : "memory");
                    asm volatile("cp.async.bulk.commit_group;\n" ::: "memory");
                    asm volatile("cp.async.bulk.wait_group.read %0;\n" :: "n"(PCHUNK) : "memory");
                    asm volatile("st.volatile.shared.b32 [%0], %1;\n" :: "r"(sbase + SM_PBAR + 48), "r"(max(done + ch + 1 - PCHUNK, 0)) : "memory");
                }
                done += PSM;
                if (!mbar_test(sbase + SM_PBAR + 104 + (st == 5 ? 0 : st + 1) * 8, st == 5 ? ph ^ 1 : ph)) {
                    if (PCHUNK > 1) {
                        asm volatile("cp.async.bulk.wait_group.read 1;\n" ::: "memory");
                        asm volatile("st.volatile.shared.b32 [%0], %1;\n" :: "r"(sbase + SM_PBAR + 48), "r"(done - 1) : "memory");
                    }
                    asm volatile("cp.async.bulk.wait_group.read 0;\n" ::: "memory");
                    asm volatile("st.volatile.shared.b32 [%0], %1;\n" :: "r"(sbase + SM_PBAR + 48), "r"(done) : "memory");
                }
                prev = st;
                if (++st == 6) { st = 0; ph ^= 1; }
            }
            mbar_wait(sbase + SM_PBAR + 56, 0);
            asm volatile("fence.acq_rel.gpu;\n" ::: "memory");
            asm volatile("cp.async.bulk.wait_group 0;\n" ::: "memory");
            asm volatile("red.relaxed.gpu.global.add.u32 [%0], %1;\n" :: "l"(g_guard), "r"(bid == 0 ? 257 - gridDim.x : 1) : "memory");
            TR(30, 0);
        }
        return;
    }
    bool bad = false;
    if (!attn) {
        asm volatile("setmaxnreg.inc.sync.aligned.u32 160;\n");
        uint32_t lo = 0x7F807F80u, hi = 0;
#pragma unroll 1
        for (int i = (role - 2 * P.npair) * 384 + tid; i < 192 * 96; i += (gridDim.x - 2 * P.npair) * 384) {
            const bool o = i >= 192 * 72;
            const uint4 w = o ? reinterpret_cast<const uint4*>(P.wo)[i - 192 * 72] : reinterpret_cast<const uint4*>(P.wqkv)[i];
            const uint32_t m = __vmaxu2(__vmaxu2(w.x & 0x7FFF7FFFu, w.y & 0x7FFF7FFFu), __vmaxu2(w.z & 0x7FFF7FFFu, w.w & 0x7FFF7FFFu));
            lo = __vminu2(lo, m);
            hi = __vmaxu2(hi, m + (o ? 0x02000200u : 0u));
        }
        bad = __vminu2(lo, 0x38803880u) != 0x38803880u || __vmaxu2(hi, 0x42004200u) != 0x42004200u;
    } else if (wg == 0) {
        asm volatile("setmaxnreg.inc.sync.aligned.u32 %0;\n" :: "n"(REG_G));
        float qs = 1.f;
        if (c < 2) qs = round_bf16(expf(round_bf16(fminf(fmaxf(__bfloat162float(P.logit_scale[2 * half + c]), -100.f), 4.6052f)))) * LOG2E;
        uint32_t xa[8][4];
        uint32_t qk[2][48], vv[24];
        uint32_t rho = warp * 16 + (lane & 15), rq = warp * 16 + g;
        uint32_t rx = rho + 3 * TOK - (rho >= TOK ? 4 * TOK : 0);
        uint32_t hi = lane >> 4, lane0 = lane == 0, c2 = 2 * c;
        asm volatile("" : "+r"(hi), "+r"(lane0), "+r"(c2));
        auto row_addr = [&](uint32_t (&ax)[4], uint32_t r) {
            ax[0] = sbase + SM_QK + r * 128 + (((r & 7) ^ hi) << 4);
#pragma unroll
            for (int i = 1; i < 4; i++) ax[i] = ax[0] ^ (32 * i);
        };
#define XADDR(ax, s) ((ax)[((s) & 3) ^ (((s) >> 1) & 2)] + ((s) >> 2) * QK_CHUNK)
        uint64_t descW = make_desc(sbase, W_ATOM, 256, 3);
        const uint32_t zero = (uint32_t)P.z1;
        const uint32_t vbase = sbase + SM_V + (lane >> 4) * GRP;
        uint32_t ones = 0x3C003C00u | zero, ones2 = ones | (zero >> 1);
        asm volatile("" : "+r"(ones), "+r"(ones2));
        const uint32_t mh[2] = {0xFFFF0000u, 0xFFFF0000u}, ml[2] = {0x10000u, 0x10000u};
        uint32_t raw[48], xb[4][4];
        auto cvt = [&](auto& dst, int d0, const uint32_t (&raw)[48], int s0) {
#pragma unroll
            for (int s = 0; s < 4; s++) {
#pragma unroll
                for (int i = 0; i < 4; i++)
                    dst[d0 + s][i] = pack_f16(__uint_as_float(raw[4 * (s0 + s) + i] * ml[i & 1]), __uint_as_float(raw[4 * (s0 + s) + i] & mh[i & 1]));
                reg_fence(dst[d0 + s]);
            }
        };
        uint32_t ax[4];
        auto load_x = [&](int s0) {
#pragma unroll
            for (int s = s0; s < s0 + 4; s++) ldsm_x4(reinterpret_cast<uint32_t (&)[4]>(raw[4 * s]), XADDR(ax, s));
        };
        auto next_x = [&]() {
            row_addr(ax, rx);
            rx += 64;
            if (rx >= 4 * TOK) rx -= 4 * TOK;
        };
        permute_w();
        TR(26, 10);
        mbar_wait(bars + B_XFULL, 0);
        next_x();
        load_x(0); load_x(4); load_x(8);
        cvt(xa, 0, raw, 0); cvt(xa, 4, raw, 4); cvt(xb, 0, raw, 8);
        __syncwarp();
        mbar_arrive_if(bars + B_QKFREE + 24, lane0);
        TR(26, 8);
        asm volatile("bar.sync 7, 384;\n" ::: "memory");
        fence_async_smem();
        TR(26, 9);
        wgmma_fence();
        mma_qk_first<SM_WA, 0>(qk[0], xa, descW);
        mma_qk_next<SM_WA + 2048, 4>(qk[0], xa, descW);
        mma_qk_next<SM_WA + 4096, 0>(qk[0], xb, descW);
        wgmma_commit();
        TR(26, 11);
        asm volatile("bar.sync 11, 384;\n" ::: "memory");
        fence_async_smem();
        TR(26, 12);
        wgmma_fence();
        mma_v_first<SM_WV, 0>(vv, xa, descW);
        mma_v_next<SM_WV + 2048, 4>(vv, xa, descW);
        wgmma_commit();
        wgmma_wait<0>();
        uint32_t xok = 0, range = 0;
        auto body = [&](auto U_, int t) {
            constexpr int U = decltype(U_)::value;
            uint32_t (&cur)[48] = qk[U];
            uint32_t (&nxt)[48] = qk[U ^ 1];
            descW += P.z1;
            const uint32_t bt = bars + (t & 3) * 8, pt = (t >> 2) & 1;
            TR(1, t);
            wgmma_fence();
            mma_v_next<SM_WV + 4096, 0>(vv, xb, descW);
            wgmma_commit();
            next_x();
            mbar_wait_unless(xok, bars + ((t + 1) & 3) * 8 + B_XFULL, ((t + 1) >> 2) & 1);
            TR(2, t);
            load_x(0);
            load_x(4);
            uint32_t av = vbase + rho * 16 + ((rho * 1338) >> 16) * (V_STRIDE - GRP);
            uint32_t aq[2];
            aq[0] = sbase + SM_QK + rq * 128 + (((rq & 7) ^ c2) << 4);
            aq[1] = aq[0] + 1024;
            if (rq >= 4 * TOK - 8) aq[1] = (aq[1] - QK_CHUNK) ^ 64;
            rho += 64;
            if (rho >= 4 * TOK) rho -= 4 * TOK;
            rq += 64;
            if (rq >= 4 * TOK) rq -= 4 * TOK;
            asm volatile("" : "+r"(av), "+r"(aq[0]), "+r"(aq[1]), "+r"(rho), "+r"(rq));
            cvt(xa, 0, raw, 0);
            wgmma_fence();
            mma_qk_first<SM_WA, 0>(nxt, xa, descW);
            wgmma_commit();
            load_x(8);
            __syncwarp();
            mbar_arrive_if(bars + B_XCONS, lane0);
            const uint32_t vok = mbar_test(bt + B_VFREE, pt);
            cvt(xa, 4, raw, 4);
            TR(5, t);
            wgmma_fence();
            mma_qk_next<SM_WA + 2048, 4>(nxt, xa, descW);
            wgmma_commit();
            wgmma_wait<2>();
            reg_fence(cur);
            reg_fence(vv);
            TR(6, t);
            mbar_wait_unless(vok, bt + B_VFREE, pt);
            if (U == 0 && t == 2) asm volatile("bar.sync 3, 384;\n" ::: "memory");
#pragma unroll
            for (int p = 0; p < 6; p++)
                stsm_x4(av + (p < 3 ? 2 * p : 2 * p + 1) * GRP, vv[4 * p], vv[4 * p + 1], vv[4 * p + 2], vv[4 * p + 3]);
            stsm_x2(av + 6 * GRP, ones, ones2);
            __syncwarp();
            mbar_arrive_if(bt + B_VRAW, lane0);
            const uint32_t cok = mbar_test(bars + B_XCONS, U);
            TR(4, t);
            cvt(xb, 0, raw, 8);
            uint32_t ss[4];
#pragma unroll
            for (int i = 0; i < 4; i++) ss[i] = hmul2_f16(cur[i], cur[i]);
#pragma unroll
            for (int i = 4; i < ((EXP & 16) ? 4 : 48); i++) ss[i & 3] = hfma2_f16(cur[i], cur[i], ss[i & 3]);
            ss[0] = hadd2_f16(ss[0], ss[2]);
            ss[1] = hadd2_f16(ss[1], ss[3]);
            const float s0 = f16lo(ss[0]) + f16hi(ss[0]) + 1e-12f, s1 = f16lo(ss[1]) + f16hi(ss[1]) + 1e-12f;
            range = __viaddmax_u32(__float_as_uint(s0), 0u - SS_MIN, __viaddmax_u32(__float_as_uint(s1), 0u - SS_MIN, range));
            const float f0 = rsqrt_ftz(s0) * qs, f1 = rsqrt_ftz(s1) * qs;
            uint32_t f2[2] = {pack_f16_sat(f0, f0), pack_f16_sat(f1, f1)};
            reg_fence(f2);
            sched_fence16(zero, xb, f2[0], f2[1]);
            wgmma_fence();
            mma_v_first<SM_WV, 0>(vv, xa, descW);
            wgmma_commit();
            mbar_wait_unless_dep(cok, bars + B_XCONS, U, zero, f2[0], f2[1], aq[0], aq[1]);
            TR(7, t);
#pragma unroll
            for (int u = 0; u < 6; u++)
#pragma unroll
                for (int r = 0; r < 2; r++)
                    sts128((aq[r] ^ ((u & 1) * 16 + (u & 2) * 32)) + (u >> 1) * QK_CHUNK,
                           hmul2_f16(cur[8 * u + r], f2[r]), hmul2_f16(cur[8 * u + 2 + r], f2[r]),
                           hmul2_f16(cur[8 * u + 4 + r], f2[r]), hmul2_f16(cur[8 * u + 6 + r], f2[r]));
            __syncwarp();
            mbar_arrive_if(bt + B_QKRAW, lane0);
            TR(3, t);
            wgmma_fence();
            mma_v_next<SM_WV + 2048, 4>(vv, xa, descW);
            wgmma_commit();
            xok = mbar_test(bars + ((t + 2) & 3) * 8 + B_XFULL, ((t + 2) >> 2) & 1);
            mma_qk_next<SM_WA + 4096, 0>(nxt, xb, descW);
            wgmma_commit();
            TR(0, t + 1);
            wgmma_wait<1>();
        };
        for (int t = 0;; t += 2) {
            body(std::integral_constant<int, 0>(), t);
            if (t + 1 >= ntiles) { wgmma_wait<0>(); reg_fence(qk[1]); break; }
            body(std::integral_constant<int, 1>(), t + 1);
            if (t + 2 >= ntiles) { wgmma_wait<0>(); reg_fence(qk[0]); break; }
        }
        reg_fence(vv);
        bad = range >= F32_INF - SS_MIN;
        wg_bar(2);
        asm volatile("setmaxnreg.dec.sync.aligned.u32 160;\n");
    } else {
        if (REG_A > 128) asm volatile("setmaxnreg.inc.sync.aligned.u32 %0;\n" :: "n"(REG_A));
        if (REG_A < 128) asm volatile("setmaxnreg.dec.sync.aligned.u32 %0;\n" :: "n"(REG_A));
        {
            const float c0 = bf16lo(rc), c1 = bf16hi(rc);
            float a0 = 0.f, a1 = 0.f;
#pragma unroll
            for (int u = 0; u < 16; u++) {
                const uint32_t p = reinterpret_cast<const uint32_t*>(w1)[u >> 1], q = reinterpret_cast<const uint32_t*>(w1)[8 + (u >> 1)];
                float h = round_bf16(c0 * ((u & 1) ? bf16hi(p) : bf16lo(p)) + c1 * ((u & 1) ? bf16hi(q) : bf16lo(q)));
                h = fmaxf(h, 0.f);
                a0 += h * bf16lo(w2[u]);
                a1 += h * bf16hi(w2[u]);
            }
            const float s0 = round_bf16(__fdividef(1.f, 1.f + expf(-round_bf16(a0))));
            const float s1 = round_bf16(__fdividef(1.f, 1.f + expf(-round_bf16(a1))));
            if (tid - 128 < 169) sts32(sbase + SM_TAB + (tid - 128) * 4, pack_f16(16.f * LOG2E * s0, 16.f * LOG2E * s1));
        }
        permute_w();
        asm volatile("bar.arrive 7, 384;\n" ::: "memory");
        {
            mbar_wait(bars + B_WFULL, 0);
#pragma unroll 1
            for (int i = 0; i < 9 - 9 * T_NOWV; i++) {
                uint4* q = reinterpret_cast<uint4*>(smem + SM_WV + (tid - 128) * 16 + i * 4096);
                const uint4 w = *q;
                *q = make_uint4(bf2h(w.x), bf2h(w.y), bf2h(w.z), bf2h(w.w));
            }
            asm volatile("bar.arrive 11, 384;\n" ::: "memory");
        }
        asm volatile("bar.sync 1, 256;\n" ::: "memory");
        uint32_t bias[28];
        {
            const uint32_t* tab = reinterpret_cast<const uint32_t*>(smem + SM_TAB);
#pragma unroll
            for (int rh = 0; rh < 2; rh++) {
#pragma unroll
                for (int j = 0; j < 6; j++) {
                    const uint32_t lo = tab[min(max(ridx[13 * rh + 2 * j], 0), 168)];
                    const uint32_t hi = tab[min(max(ridx[13 * rh + 2 * j + 1], 0), 168)];
                    bias[2 * j + rh]      = prmt(lo, hi, 0x5410);
                    bias[14 + 2 * j + rh] = prmt(lo, hi, 0x7632);
                }
                const uint32_t l = (c == 0) ? tab[min(max(ridx[13 * rh + 12], 0), 168)] : 0xFC00FC00u;
                bias[12 + rh] = (l & 0xFFFFu) | 0xFC000000u;
                bias[26 + rh] = (l >> 16) | 0xFC000000u;
            }
        }
        reg_fence(bias);
        asm volatile("bar.arrive 3, 384;\n" ::: "memory");
        const bool ov = warp * 16 + (lane & 15) < TOK;
        const int orow = warp * 16 + (lane & 15);
        const uint32_t orel = sbase + (ov ? SM_V + orow * O_PITCH + (orow >= 28 ? 64 : 0) : SM_DUMP + (lane & 7) * 16) + (lane >> 4) * 16;
        const uint32_t omul = ov ? V_STRIDE : 0;
        const uint64_t descK0 = make_desc(sbase + SM_QK, 16, 1024, 1);
        const uint64_t descV0 = make_desc(sbase + SM_V, 128, GRP, 0);
        const uint32_t mrel = sbase + SM_MASK + t0 * 98 + c * 4;
        const uint32_t mrow = (warp < 3) ? 784 : 0;
        const uint32_t pmask = (c == 0) ? 0xFFFFu : 0u;

        uint32_t mstate = 0;
        const uint32_t barw = bars + (wg - 1) * 8;
        const uint64_t descKw = descK0 + (uint64_t)((wg - 1) * (XCH >> 4)), descVw = descV0 + (uint64_t)((wg - 1) * (V_STRIDE >> 4));
        uint32_t oa = orel + (wg - 1) * omul;
        const uint32_t oflip = oa ^ (oa + 2 * omul);
        uint32_t qok = 0;
        const uint32_t zero = (uint32_t)P.z1;
        auto window = [&](auto IT_, int k) {
            constexpr int IT = decltype(IT_)::value;
            const uint32_t bar = barw + 16 * IT;
            const int tl = (k * TOK + TOK - 1) >> 6, tn = ((k + 2) * TOK + TOK - 1) >> 6;
            const uint32_t bt = bars + (tl & 3) * 8, pt = (tl >> 2) & 1;
            TR(8, k);
            uint32_t sc0[14], sc1[14];
#pragma unroll
            for (int i = 0; i < 14; i++) { sc0[i] = bias[i]; sc1[i] = bias[14 + i]; }
            if (mstate < 2 * k + 2) {
#pragma unroll 1
                for (uint32_t n = 0; n < (1u << 22) && mstate <= 2 * k; n++) mstate = lds32v(bars + B_MSTATE);
                if (mstate == 2 * k + 1) {
                    mbar_wait(bars + B_MFULL, k & 1);
                    const uint32_t ma = mrel + ((2 * (pair + k * P.npair)) & 14);
#pragma unroll
                    for (int i = 0; i < 14; i++) {
                        const uint32_t lo = lds16(ma + (i & 1) * mrow + (i >> 1) * 16);
                        const uint32_t hi = i < 12 ? lds16(ma + (i & 1) * mrow + (i >> 1) * 16 + 2) : 0u;
                        const uint32_t mk = pack_f16(__uint_as_float(lo << 16), __uint_as_float(hi << 16));
                        sc0[i] = hfma2_f16(mk, 0x3DC53DC5u, sc0[i]);
                        sc1[i] = hfma2_f16(mk, 0x3DC53DC5u, sc1[i]);
                    }
                    __syncwarp();
                    if (lane == 0) mbar_arrive(bars + B_MCONS);
                }
            }
            reg_fence(sc0);
            reg_fence(sc1);
            TR(10, k);
            mbar_wait_unless(qok, bt + B_QKRAW, pt);
            fence_async_smem();
            TR(11, k);
            wgmma_fence();
#if !(EXP & 128)
            mma_s0_f16<2 * IT * XCH, 2 * IT * XCH>(sc0, descKw, descKw);
            mma_s1_f16<2 * IT * XCH, 2 * IT * XCH>(sc1, descKw, descKw);
#endif
            wgmma_commit();
            const uint32_t vok = mbar_test(bt + B_VRAW, pt);
            uint32_t m[2];
            auto rowmax = [&](const uint32_t (&S)[14], int h) {
                uint32_t a[2];
#pragma unroll
                for (int o = 0; o < 2; o++)
                    a[o] = hmax2_f16(hmax2_f16(hmax2_f16(hmax2_f16(S[o], S[2 + o]), S[4 + o]), hmax2_f16(hmax2_f16(S[6 + o], S[8 + o]), S[10 + o])), S[12 + o]);
                m[h] = hmax2_f16(prmt(a[0], a[1], 0x5410), prmt(a[0], a[1], 0x7632));
            };
            wgmma_wait<0>();
            reg_fence(sc0);
            reg_fence(sc1);
            if (lane == 0) mbar_arrive(bar + B_QKFREE);
            TR(12, k);
            rowmax(sc0, 0);
            rowmax(sc1, 1);
#pragma unroll
            for (int i = 0; i < 2; i++) m[i] = hmax2_f16(m[i], __shfl_xor_sync(0xffffffffu, m[i], 1));
#pragma unroll
            for (int i = 0; i < 2; i++) m[i] = hmax2_f16(m[i], __shfl_xor_sync(0xffffffffu, m[i], 2));
            auto probs = [&](const uint32_t (&S)[14], uint32_t mm, uint32_t (&pa)[4][4]) {
#pragma unroll
                for (int j = 0; j < 6; j++) {
                    pa[j >> 1][(j & 1) * 2]     = ex2_f16x2(hsub2_bc<0>(S[2 * j], mm));
                    pa[j >> 1][(j & 1) * 2 + 1] = ex2_f16x2(hsub2_bc<1>(S[2 * j + 1], mm));
                }
                pa[3][0] = ex2_f16lo(hsub2_bc<0>(S[12], mm)) & pmask;
                pa[3][1] = ex2_f16lo(hsub2_bc<1>(S[13], mm)) & pmask;
                pa[3][2] = 0u; pa[3][3] = 0u;
                reg_fence(pa);
            };
            uint32_t pa0[4][4], pa1[4][4];
            uint32_t o0[14], o1[14];
            TR(13, k);
            mbar_wait_unless(vok, bt + B_VRAW, pt);
            fence_async_smem();
            TR(14, k);
            probs(sc0, m[0], pa0);
            wgmma_fence();
            mma_pv<2 * IT * V_STRIDE, 0>(o0, pa0, descVw);
            wgmma_commit();
            probs(sc1, m[1], pa1);
            wgmma_fence();
            mma_pv<2 * IT * V_STRIDE + 6 * GRP, 0>(o1, pa1, descVw);
            wgmma_commit();
            uint32_t w[24];
            wgmma_wait<1>();
            reg_fence(o0);
            {
                const float il0 = rcp_ftz(f16lo(o0[12])), il1 = rcp_ftz(f16lo(o0[13]));
                const uint32_t l0 = pack_f16(il0, il0), l1 = pack_f16(il1, il1);
#pragma unroll
                for (int j = 0; j < 12; j++) w[j] = hmul2_f16(o0[j], (j & 1) ? l1 : l0);
            }
            wgmma_wait<0>();
            reg_fence(o1);
            TR(15, k);
            asm volatile("{\n.reg .pred p;\nsetp.eq.u32 p, %0, 1;\n@p bar.sync 4, 128;\n@!p bar.sync 5, 128;\n}\n"
                         :: "r"(wg) : "memory");
            qok = mbar_test(bars + (tn & 3) * 8 + B_QKRAW, (tn >> 2) & 1);
            mstate = lds32v(bars + B_MSTATE);
            {
                const float il2 = rcp_ftz(f16lo(o1[0])), il3 = rcp_ftz(f16lo(o1[1]));
                const uint32_t l2 = pack_f16(il2, il2), l3 = pack_f16(il3, il3);
#pragma unroll
                for (int j = 0; j < 12; j++) w[12 + j] = hmul2_f16(o1[j + 2], (j & 1) ? l3 : l2);
#pragma unroll
                for (int p = 0; p < 6; p++) stsm_x4(oa + p * 32, w[4 * p], w[4 * p + 1], w[4 * p + 2], w[4 * p + 3]);
            }
            __syncwarp();
            if (lane == 0) mbar_arrive(bar + B_ODONE);
            TR(16, k);
            oa ^= oflip;
            asm volatile("" : "+r"(oa));
        };
        for (int k = wg - 1;; k += 4) {
            window(std::integral_constant<int, 0>(), k);
            if (k + 2 >= nwin) break;
            window(std::integral_constant<int, 1>(), k + 2);
            if (k + 4 >= nwin) break;
        }
        (void)zero;
        asm volatile("setmaxnreg.inc.sync.aligned.u32 160;\n");
    }

    TR(27, wg);
    uint32_t tag, seen;
    asm volatile("ld.relaxed.gpu.global.v2.u32 {%0, %1}, [%2];\n" : "=r"(tag), "=r"(seen) : "l"(g_guard) : "memory");
    if (attn) {
        __syncwarp();
        if (lane == 0) mbar_arrive(sbase + SM_PBAR + 96);
    }
    if (!attn || wg == 0) {
#pragma unroll 3
        for (int row = tid >> 2; row < 192; row += attn ? 32 : 96) {
            uint4 w[6];
#pragma unroll
            for (int a = 0; a < 6; a++) w[a] = *reinterpret_cast<const uint4*>(P.wo + row * 192 + 32 * a + 8 * c);
            float s = 0.f;
#pragma unroll
            for (int a = 0; a < 6; a++)
                s += ((bf16lo(w[a].x) + bf16hi(w[a].x)) + (bf16lo(w[a].y) + bf16hi(w[a].y))) +
                     ((bf16lo(w[a].z) + bf16hi(w[a].z)) + (bf16lo(w[a].w) + bf16hi(w[a].w)));
            s += __shfl_xor_sync(0xffffffffu, s, 1);
            s += __shfl_xor_sync(0xffffffffu, s, 2);
            s *= (1.f / 192.f);
            const uint32_t sw = (row >> 1) & 3;
            const uint32_t d = sbase + SM_WO + row * 64 + ((c ^ sw) << 4), e = sbase + SM_WO + row * 64 + c * 4;
#pragma unroll
            for (int a = 0; a < 6; a++) {
                const uint32_t h[4] = {pack_f16(bf16lo(w[a].x) - s, bf16hi(w[a].x) - s), pack_f16(bf16lo(w[a].y) - s, bf16hi(w[a].y) - s),
                                       pack_f16(bf16lo(w[a].z) - s, bf16hi(w[a].z) - s), pack_f16(bf16lo(w[a].w) - s, bf16hi(w[a].w) - s)};
                if (a < 2 * PSM) {
                    sts128(d + a * 12288, h[0], h[1], h[2], h[3]);
                } else {
#pragma unroll
                    for (int i = 0; i < 4; i++) sts32(e + a * 12288 + ((i ^ sw) << 4), h[i]);
                }
            }
        }
        fence_async_smem();
    }
    tag |= 255;
    if (bad) g_guard[1] = tag;
    bad |= seen == tag;
    asm volatile("bar.sync 6, 384;\n" ::: "memory");
    TR(27, 4 + wg);
    {
        PROJ_SCHEDULE
        uint64_t descW = make_desc(sbase + SM_WO, 12288, 512, 2);
        const uint64_t descA = make_desc(sbase + SM_STAGE + wg * STAGE_BYTES, 16, 1024, 1);
        const uint32_t bar = sbase + SM_PBAR + wg * 8;
        const uint32_t yrel = sbase + SM_STAGE + wg * STAGE_BYTES + (warp * 16 + (lane & 15)) * 128 + (((lane & 7) ^ (lane >> 4)) << 4);
        float acc[96];
#pragma unroll
        for (int i = 0; i < 96; i++) acc[i] = 0.f;
        uint32_t it = 0;
        for (int tile = tile0 + wg * tstep; tile < tend; tile += 3 * tstep, it++) {
            descW += P.z1;
            mbar_wait(bar + (it & 1) * 24, (it >> 1) & 1);
            TR(28, it * 3 + wg);
            if (it > 0 || wg > 0) asm volatile("bar.sync %0, 256;\n" :: "r"(8 + wg) : "memory");
            wgmma_fence();
            mma_proj<0, 0>(acc, descA + (uint64_t)((it & 1) * (3 * STAGE_BYTES >> 4)), descW);
            wgmma_commit();
            if (tile + tstep < tend) asm volatile("bar.arrive %0, 256;\n" :: "r"(wg == 2 ? 8 : 9 + wg) : "memory");
            wgmma_wait<0>();
            reg_fence(acc);
            TR(18, it * 3 + wg);
            float a[4];
#pragma unroll
            for (int i = 0; i < 4; i++) a[i] = acc[i] * acc[i];
#pragma unroll
            for (int j = 1; j < 24; j++)
#pragma unroll
                for (int i = 0; i < 4; i++) a[i] = fmaf(acc[4 * j + i], acc[4 * j + i], a[i]);
            float s0 = a[0] + a[1], s1 = a[2] + a[3];
            s0 += __shfl_xor_sync(0xffffffffu, s0, 1);
            s1 += __shfl_xor_sync(0xffffffffu, s1, 1);
            s0 += __shfl_xor_sync(0xffffffffu, s0, 2);
            s1 += __shfl_xor_sync(0xffffffffu, s1, 2);
            if (max(__float_as_uint(s0) - VAR_MIN, __float_as_uint(s1) - VAR_MIN) >= F32_INF - VAR_MIN) {
                const int rem = ((tile < TILES_A) ? NPIX - SEG_B - 64 * tile : SEG_B - 64 * (tile - TILES_A)) - warp * 16 - g;
                if ((__float_as_uint(s0) - VAR_MIN >= F32_INF - VAR_MIN && rem > 0) ||
                    (__float_as_uint(s1) - VAR_MIN >= F32_INF - VAR_MIN && rem > 8)) {
                    bad = true;
                    g_guard[1] = tag;
                }
            }
            const float rs0 = rsqrt_ftz(fmaf(s0, 1.f / 192.f, 1e-5f));
            const float rs1 = rsqrt_ftz(fmaf(s1, 1.f / 192.f, 1e-5f));
            const uint32_t ya = yrel + (it & 1) * 3 * STAGE_BYTES;
            auto direct = [&]() {
                const int p0 = (tile < TILES_A) ? SEG_B + 64 * (tile & PWRAP) : 64 * (tile - TILES_A);
                const int lim = ((tile < TILES_A) ? NPIX : SEG_B) - p0;
                char* const po = reinterpret_cast<char*>(P.out) + (uint32_t)((p0 + warp * 16 + g) * 384 + c * 16);
                const bool v0 = warp * 16 + g < lim, v1 = warp * 16 + g + 8 < lim;
#pragma unroll
                for (int i = 2 * PSM; i < 6; i++) {
                    const int j = 16 * i;
                    stg128_if(v0, po + 64 * i, pack_bf16(acc[j] * rs0, acc[j + 1] * rs0), pack_bf16(acc[j + 4] * rs0, acc[j + 5] * rs0),
                              pack_bf16(acc[j + 8] * rs0, acc[j + 9] * rs0), pack_bf16(acc[j + 12] * rs0, acc[j + 13] * rs0));
                    stg128_if(v1, po + 8 * 384 + 64 * i, pack_bf16(acc[j + 2] * rs1, acc[j + 3] * rs1),
                              pack_bf16(acc[j + 6] * rs1, acc[j + 7] * rs1), pack_bf16(acc[j + 10] * rs1, acc[j + 11] * rs1),
                              pack_bf16(acc[j + 14] * rs1, acc[j + 15] * rs1));
                }
            };
            if (PSM < 3 && PDF) direct();
#pragma unroll
            for (int p = 0; p < 4 * PSM; p++)
                stsm_x4((ya ^ (32 * (p & 3))) + (p >> 2) * 8192,
                        pack_bf16(acc[8 * p] * rs0, acc[8 * p + 1] * rs0), pack_bf16(acc[8 * p + 2] * rs1, acc[8 * p + 3] * rs1),
                        pack_bf16(acc[8 * p + 4] * rs0, acc[8 * p + 5] * rs0), pack_bf16(acc[8 * p + 6] * rs1, acc[8 * p + 7] * rs1));
            __syncwarp();
            if (lane == 0) mbar_arrive(bar + 104 + (it & 1) * 24);
            if (PSM < 3 && !PDF) direct();
            TR(29, it * 3 + wg);
        }
        __syncwarp();
        if (lane == 0) mbar_arrive(sbase + SM_PBAR + 56);
    }

    {
        uint32_t any;
        asm volatile("{\n.reg .pred p, q;\nsetp.ne.u32 q, %1, 0;\nbarrier.cta.red.or.pred.aligned p, %2, 128, q;\nselp.u32 %0, 1, 0, p;\n}\n"
                     : "=r"(any) : "r"((uint32_t)bad), "r"(12 + wg) : "memory");
        if (!any) return;
    }
    redo(P, smem + wg * FB_BYTES, tag, 12 + wg);
}

}

typedef CUresult (*PFN_encodeTiled)(CUtensorMap*, CUtensorMapDataType, cuuint32_t, void*, const cuuint64_t*,
                                    const cuuint64_t*, const cuuint32_t*, const cuuint32_t*, CUtensorMapInterleave,
                                    CUtensorMapSwizzle, CUtensorMapL2promotion, CUtensorMapFloatOOBfill);

extern "C" void kernel_launch(void* const* d_in, const int* in_sizes, int n_in, void* d_out, int out_size) {
    swin::Params P;
    P.x           = (const __nv_bfloat16*)d_in[0];
    P.wqkv        = (const __nv_bfloat16*)d_in[1];
    P.wo          = (const __nv_bfloat16*)d_in[2];
    P.logit_scale = (const __nv_bfloat16*)d_in[3];
    P.cpb_w1      = (const __nv_bfloat16*)d_in[4];
    P.cpb_w2      = (const __nv_bfloat16*)d_in[5];
    P.rel_coords  = (const __nv_bfloat16*)d_in[6];
    P.rel_idx     = (const int*)d_in[7];
    P.mask        = (const __nv_bfloat16*)d_in[8];
    P.out         = (__nv_bfloat16*)d_out;
    P.z1 = 0;
    static PFN_encodeTiled encode = nullptr;
    if (!encode) {
        cudaFuncSetAttribute(swin::swin_window_attn_kernel, cudaFuncAttributeMaxDynamicSharedMemorySize, swin::SM_TOTAL);
        cudaDriverEntryPointQueryResult qr;
        cudaGetDriverEntryPoint("cuTensorMapEncodeTiled", (void**)&encode, cudaEnableDefault, &qr);
    }
    CUtensorMap xmap, xmap4, xmap3, omap, wmap, smap, omapb, xmapa, xmapb, smap3, wraw;
    const cuuint32_t estr[4] = {1, 1, 1, 1};
    auto make = [&](CUtensorMap* m, const void* base, int rank, const cuuint64_t* gdim, const cuuint64_t* gstr,
                    const cuuint32_t* box, CUtensorMapSwizzle swz = CU_TENSOR_MAP_SWIZZLE_128B) {
        CUresult r = encode(m, CU_TENSOR_MAP_DATA_TYPE_BFLOAT16, rank, const_cast<void*>(base), gdim, gstr, box, estr,
               CU_TENSOR_MAP_INTERLEAVE_NONE, swz, CU_TENSOR_MAP_L2_PROMOTION_L2_128B,
               CU_TENSOR_MAP_FLOAT_OOB_FILL_NONE);
        (void)r;
    };
    {
        const cuuint64_t gdim[3] = {192, swin::IMG, swin::IMG}, gstr[2] = {384, swin::IMG * 384};
        const cuuint32_t box[3] = {64, 7, 7}, box4[3] = {64, 4, 1}, box3[3] = {64, 3, 1};
        make(&xmap, P.x, 3, gdim, gstr, box);
        make(&xmap4, P.x, 3, gdim, gstr, box4);
        make(&xmap3, P.x, 3, gdim, gstr, box3);
        const cuuint32_t boxa[3] = {64, 7, 3}, boxb[3] = {64, 7, 4};
        make(&xmapa, P.x, 3, gdim, gstr, boxa);
        make(&xmapb, P.x, 3, gdim, gstr, boxb);
    }
    {
        const cuuint64_t gdim[2] = {192, (cuuint64_t)swin::NPIX}, gstr[1] = {384};
        const cuuint32_t box64[2] = {64, 64};
        make(&omap, d_out, 2, gdim, gstr, box64);
        const cuuint64_t gdimb[2] = {192, (cuuint64_t)swin::SEG_B};
        make(&omapb, d_out, 2, gdimb, gstr, box64);
    }
    {
        const cuuint64_t gdim[2] = {576, 192}, gstr[1] = {1152};
        const cuuint32_t box[2] = {16, 192};
        make(&wmap, P.wqkv, 2, gdim, gstr, box, CU_TENSOR_MAP_SWIZZLE_32B);
        const cuuint64_t gdim3[3] = {96, 6, 192}, gstr3[2] = {192, 1152};
        const cuuint32_t box3[3] = {104, 1, 96};
        make(&wraw, P.wqkv, 3, gdim3, gstr3, box3, CU_TENSOR_MAP_SWIZZLE_NONE);
    }
    {
        const cuuint64_t gdim[4] = {96, 2, swin::IMG, swin::IMG}, gstr[3] = {192, 384, swin::IMG * 384};
        const cuuint32_t box4[4] = {104, 1, 7, 4}, box3[4] = {104, 1, 7, 3};
        make(&smap, d_out, 4, gdim, gstr, box4, CU_TENSOR_MAP_SWIZZLE_NONE);
        make(&smap3, d_out, 4, gdim, gstr, box3, CU_TENSOR_MAP_SWIZZLE_NONE);
    }
    P.npair = NPAIR; P.need = swin::ROW_DONE; P.nq = swin::NWINDOWS / NPAIR; P.nr = swin::NWINDOWS % NPAIR;
    P.t1 = swin::TILES - NTAIL;
    P.spread = ((132 - 2 * NPAIR) * 65536 + 131) / 132;
    swin::swin_window_attn_kernel<<<132, swin::NTHREADS, swin::SM_TOTAL>>>(P, xmap, xmap4, xmap3, omap, wmap, smap, omapb, xmapa, xmapb, smap3, wraw);
}
```

```cpp
#include <cuda_runtime.h>
#include <cuda.h>
#include <cuda_bf16.h>
#include <stdint.h>
#include <type_traits>

namespace swin {

#define NPAIR 53
#define QFP32 0
#define PF_DIST 3
#define EXP 0
#define QSPLIT 3
#define SSPLIT 0
#define LATEMASK 0
#define CLUSTER 0
#define NOPF 0
#define NTAIL 224
#define PSTORE 1
#define PORDER 1
#define GORD 0
#define GMERGE 0
#define XSPLIT 1
#define EARLYW 1
#define NEARLY 4
#define W1 1
#define W2 2
#define W3 2
#define T_ONEBUF 0
#define T_NOWV 0
#define MPF 3
#define MRND 5
#define PX_L 3
#define PX_S 3
#define PX_W 0
#define PCHUNK 1
#define SPREAD 2
#define PSM 2
#define PDF 0
#define PWRAP -1
#define POLLER 1
#define PUBN 2
#define PUBT 4
#define NSTATIC 92
#define RSLEEP 800
#define AROLL 0
#define WOSPLIT 4
#define HINT 0
#define HINT_A ""
#define HINT_B ""
#define REG_G 232
#define REG_A 120
#define REG_H 32
constexpr int IMG      = 511;
constexpr int NWS      = 73;
constexpr int NWINDOWS = NWS * NWS;
constexpr int TOK      = 49;
constexpr int NPIX     = IMG * IMG;
constexpr int NTHREADS = 512;

constexpr int W_ATOM = 6144;
constexpr int SM_WA = 0, SM_WB = 6 * W_ATOM, SM_WV = 12 * W_ATOM;
constexpr int GRP   = TOK * 16;
constexpr int XCH   = TOK * 128;
constexpr int SM_V  = 18 * W_ATOM, V_STRIDE = 10240, O_PITCH = 208;
constexpr int SM_QK = SM_V + 4 * V_STRIDE, QK_CHUNK = 4 * XCH;
constexpr int SM_MASK = SM_QK + 3 * QK_CHUNK;
constexpr int SM_TAB  = SM_V + 3 * V_STRIDE + 256;
constexpr int SM_DUMP = SM_MASK + 4816;
constexpr int SM_BAR  = SM_DUMP + 320;
constexpr int B_XFULL = 0, B_WRAW = 32, B_XCONS = 40, B_NTILES = 48, B_GDONE = 56, B_DYN = 192, B_ROWS = 384, B_QKRAW = 64, B_QKFREE = 96, B_VFREE = 128, B_ODONE = 160,
              B_VRAW = 224, B_MFULL = 256, B_MSTATE = 264, B_MCONS = 272, B_WFULL = 280, B_STORED = 288, B_PUBD = 304;
constexpr int SM_A_END = SM_BAR + 320;
static_assert(SM_QK % 1024 == 0 && TOK * O_PITCH + 64 - 16 <= V_STRIDE && (28 * O_PITCH + 64) % 128 == 0, "layout");
constexpr int SM_WO    = 0;
constexpr int SM_STAGE = 73728;
constexpr int STAGE_BYTES = 24576;
constexpr int SM_PBAR  = SM_A_END;
constexpr int SM_TOTAL = SM_PBAR + 152;
static_assert(SM_STAGE + 6 * STAGE_BYTES <= SM_BAR, "smem");
static_assert(SM_TOTAL <= 232448, "smem");
static_assert(SM_BAR % 8 == 0, "barrier alignment");

constexpr int SEG_B   = 3 * IMG;
constexpr int TILES_A = (NPIX - SEG_B + 63) / 64;
constexpr int TILES   = TILES_A + (SEG_B + 63) / 64;
constexpr uint32_t ROW_DONE = NWS * 2;

__device__ uint32_t g_cnt[NWS + 7];
__device__ __align__(128) uint8_t g_wo[SM_STAGE];
__device__ uint32_t g_next[2];
__device__ uint32_t g_done;
__device__ __align__(16) uint32_t g_guard[4];
constexpr uint32_t F32_INF = 0x7F800000u;
constexpr uint32_t SS_MIN  = 0x3B800000u;
constexpr uint32_t VAR_MIN = 0x3D400000u;

#define TR(ev, idx)
#define ST(i)
#define SC(i)
#define CK(k)
constexpr float LOG2E = 1.4426950408889634f;

__device__ __forceinline__ uint32_t smem_u32(const void* p) {
    return (uint32_t)__cvta_generic_to_shared(p);
}
__device__ __forceinline__ uint64_t make_desc(uint32_t saddr, uint32_t lbo, uint32_t sbo, uint32_t swz = 0) {
    return (uint64_t)((saddr & 0x3FFFF) >> 4) | ((uint64_t)(lbo >> 4) << 16) | ((uint64_t)(sbo >> 4) << 32) |
           ((uint64_t)swz << 62);
}
__host__ __device__ constexpr uint64_t make_desc_c(uint32_t saddr, uint32_t lbo, uint32_t sbo, uint32_t swz) {
    return (uint64_t)(saddr >> 4) | ((uint64_t)(lbo >> 4) << 16) | ((uint64_t)(sbo >> 4) << 32) | ((uint64_t)swz << 62);
}
__device__ __forceinline__ void wgmma_fence()  { asm volatile("wgmma.fence.sync.aligned;\n" ::: "memory"); }
__device__ __forceinline__ void wgmma_commit() { asm volatile("wgmma.commit_group.sync.aligned;\n" ::: "memory"); }
template <int N> __device__ __forceinline__ void wgmma_wait() {
    asm volatile("wgmma.wait_group.sync.aligned %0;\n" :: "n"(N) : "memory");
}
__device__ __forceinline__ void fence_async_smem() { asm volatile("fence.proxy.async.shared::cta;\n" ::: "memory"); }
__device__ __forceinline__ void wg_bar(int id) { asm volatile("bar.sync %0, 128;\n" :: "r"(id) : "memory"); }

template <int N> __device__ __forceinline__ void reg_fence(float (&v)[N]) {
#pragma unroll
    for (int i = 0; i < N; i++) asm volatile("" : "+f"(v[i]) :: "memory");
}
template <int N> __device__ __forceinline__ void reg_fence(uint32_t (&v)[N]) {
#pragma unroll
    for (int i = 0; i < N; i++) asm volatile("" : "+r"(v[i]) :: "memory");
}
template <int N, int M> __device__ __forceinline__ void reg_fence(uint32_t (&v)[N][M]) {
#pragma unroll
    for (int i = 0; i < N; i++) reg_fence(v[i]);
}

__device__ __forceinline__ uint32_t pack_bf16(float lo, float hi) {
    uint32_t r;
    asm("cvt.rn.bf16x2.f32 %0, %1, %2;\n" : "=r"(r) : "f"(hi), "f"(lo));
    return r;
}
__device__ __forceinline__ uint32_t pack_f16(float lo, float hi) {
    uint32_t r;
    asm("cvt.rn.f16x2.f32 %0, %1, %2;\n" : "=r"(r) : "f"(hi), "f"(lo));
    return r;
}
__device__ __forceinline__ uint32_t pack_f16_sat(float lo, float hi) {
    uint32_t r;
    asm("cvt.rn.satfinite.f16x2.f32 %0, %1, %2;\n" : "=r"(r) : "f"(hi), "f"(lo));
    return r;
}
__device__ __forceinline__ uint32_t hmul2_f16(uint32_t a, uint32_t b) {
    uint32_t r;
    asm("mul.rn.f16x2 %0, %1, %2;\n" : "=r"(r) : "r"(a), "r"(b));
    return r;
}
__device__ __forceinline__ uint32_t hadd2_f16(uint32_t a, uint32_t b) {
    uint32_t r;
    asm("add.rn.f16x2 %0, %1, %2;\n" : "=r"(r) : "r"(a), "r"(b));
    return r;
}
__device__ __forceinline__ uint32_t hfma2_f16(uint32_t a, uint32_t b, uint32_t c) {
    uint32_t r;
    asm("fma.rn.f16x2 %0, %1, %2, %3;\n" : "=r"(r) : "r"(a), "r"(b), "r"(c));
    return r;
}
__device__ __forceinline__ uint32_t hmax2_f16(uint32_t a, uint32_t b) {
    uint32_t r;
    asm("max.f16x2 %0, %1, %2;\n" : "=r"(r) : "r"(a), "r"(b));
    return r;
}
template <int H> __device__ __forceinline__ uint32_t hsub2_bc(uint32_t a, uint32_t b) {
    uint32_t r;
    if (H == 0) asm("{\n.reg .b16 l, h;\n.reg .b32 t;\nmov.b32 {l, h}, %2;\nmov.b32 t, {l, l};\nsub.rn.f16x2 %0, %1, t;\n}\n" : "=r"(r) : "r"(a), "r"(b));
    else        asm("{\n.reg .b16 l, h;\n.reg .b32 t;\nmov.b32 {l, h}, %2;\nmov.b32 t, {h, h};\nsub.rn.f16x2 %0, %1, t;\n}\n" : "=r"(r) : "r"(a), "r"(b));
    return r;
}
__device__ __forceinline__ uint32_t ex2_f16x2(uint32_t a) {
    uint32_t r;
    asm("ex2.approx.f16x2 %0, %1;\n" : "=r"(r) : "r"(a));
    return r;
}
__device__ __forceinline__ uint32_t ex2_f16lo(uint32_t a) {
    uint32_t r;
    asm("{\n.reg .b16 l, h;\nmov.b32 {l, h}, %1;\nex2.approx.f16 l, l;\nmov.b32 %0, {l, h};\n}\n" : "=r"(r) : "r"(a));
    return r;
}
__device__ __forceinline__ uint32_t lds16(uint32_t addr) {
    uint32_t v;
    asm volatile("ld.shared.u16 %0, [%1];\n" : "=r"(v) : "r"(addr) : "memory");
    return v;
}
__device__ __forceinline__ uint32_t lds16v(uint32_t addr) {
    uint32_t v;
    asm volatile("ld.volatile.shared.u16 %0, [%1];\n" : "=r"(v) : "r"(addr) : "memory");
    return v;
}
__device__ __forceinline__ void sts16(uint32_t addr, uint32_t v) {
    asm volatile("st.volatile.shared.u16 [%0], %1;\n" :: "r"(addr), "r"(v) : "memory");
}
__device__ __forceinline__ float f16lo(uint32_t v) {
    float r;
    asm("{\n.reg .b16 l, h;\nmov.b32 {l, h}, %1;\ncvt.f32.f16 %0, l;\n}\n" : "=f"(r) : "r"(v));
    return r;
}
__device__ __forceinline__ float f16hi(uint32_t v) {
    float r;
    asm("{\n.reg .b16 l, h;\nmov.b32 {l, h}, %1;\ncvt.f32.f16 %0, h;\n}\n" : "=f"(r) : "r"(v));
    return r;
}
__device__ __forceinline__ uint32_t bf2h(uint32_t v) {
    return pack_f16(__uint_as_float(v << 16), __uint_as_float(v & 0xFFFF0000u));
}
__device__ __forceinline__ float bf16lo(uint32_t v) { return __uint_as_float(v << 16); }
__device__ __forceinline__ float bf16hi(uint32_t v) { return __uint_as_float(v & 0xFFFF0000u); }
__device__ __forceinline__ uint32_t hadd2_bf16(uint32_t a, uint32_t b) {
    uint32_t r;
    asm("add.rn.bf16x2 %0, %1, %2;\n" : "=r"(r) : "r"(a), "r"(b));
    return r;
}
__device__ __forceinline__ uint32_t hmul2_bf16(uint32_t a, uint32_t b) {
    uint32_t r;
    asm("mul.rn.bf16x2 %0, %1, %2;\n" : "=r"(r) : "r"(a), "r"(b));
    return r;
}
__device__ __forceinline__ uint32_t hsub2_bf16(uint32_t a, uint32_t b) {
    uint32_t r;
    asm("sub.rn.bf16x2 %0, %1, %2;\n" : "=r"(r) : "r"(a), "r"(b));
    return r;
}
__device__ __forceinline__ uint32_t hfma2_bf16(uint32_t a, uint32_t b, uint32_t c) {
    uint32_t r;
    asm("fma.rn.bf16x2 %0, %1, %2, %3;\n" : "=r"(r) : "r"(a), "r"(b), "r"(c));
    return r;
}
__device__ __forceinline__ uint32_t hmax2_bf16(uint32_t a, uint32_t b) {
    uint32_t r;
    asm("max.bf16x2 %0, %1, %2;\n" : "=r"(r) : "r"(a), "r"(b));
    return r;
}
__device__ __forceinline__ uint32_t ex2_bf16x2(uint32_t a) {
    uint32_t r;
    asm("ex2.approx.ftz.bf16x2 %0, %1;\n" : "=r"(r) : "r"(a));
    return r;
}
__device__ __forceinline__ uint32_t ex2_bf16lo(uint32_t a) {
    uint32_t r;
    asm("{\n.reg .b16 l, h;\nmov.b32 {l, h}, %1;\nex2.approx.ftz.bf16 l, l;\ncvt.u32.u16 %0, l;\n}\n" : "=r"(r) : "r"(a));
    return r;
}
__device__ __forceinline__ uint32_t mbar_test(uint32_t bar, uint32_t parity) {
    uint32_t ok;
    asm volatile("{\n.reg .pred p;\nmbarrier.test_wait.parity.shared::cta.b64 p, [%1], %2;\nselp.u32 %0, 1, 0, p;\n}\n"
                 : "=r"(ok) : "r"(bar), "r"(parity) : "memory");
    return ok;
}
__device__ __forceinline__ uint32_t prmt(uint32_t a, uint32_t b, uint32_t sel) {
    uint32_t r;
    asm("prmt.b32 %0, %1, %2, %3;\n" : "=r"(r) : "r"(a), "r"(b), "r"(sel));
    return r;
}
__device__ __forceinline__ float round_bf16(float x) { return __bfloat162float(__float2bfloat16_rn(x)); }

__device__ __forceinline__ void mbar_init(uint32_t bar, uint32_t count) {
    asm volatile("mbarrier.init.shared::cta.b64 [%0], %1;\n" :: "r"(bar), "r"(count) : "memory");
}
__device__ __forceinline__ void mbar_wait(uint32_t bar, uint32_t parity) {
    asm volatile(
        "{\n"
        ".reg .pred p;\n"
        ".reg .u32 n;\n"
        "mov.u32 n, 0;\n"
        "WAIT_%=:\n"
        "mbarrier.try_wait.parity.shared::cta.b64 p, [%0], %1" HINT_A ";\n"
        "@p bra DONE_%=;\n"
        "add.u32 n, n, 1;\n"
        "setp.lt.u32 p, n, 4194304;\n"
        "@p bra WAIT_%=;\n"
        "exit;\n"
        "DONE_%=:\n"
        "}\n" :: "r"(bar), "r"(parity) : "memory");
}
__device__ __forceinline__ void mbar_wait4(uint32_t b0, uint32_t p0, uint32_t b1, uint32_t p1, uint32_t b2, uint32_t p2,
                                           uint32_t b3, uint32_t p3) {
    asm volatile(
        "{\n"
        ".reg .pred p, q, r, s;\n"
        ".reg .u32 n;\n"
        "mov.u32 n, 0;\n"
        "WAIT_%=:\n"
        "mbarrier.try_wait.parity.shared::cta.b64 p, [%0], %1;\n"
        "mbarrier.try_wait.parity.shared::cta.b64 q, [%2], %3;\n"
        "mbarrier.try_wait.parity.shared::cta.b64 r, [%4], %5;\n"
        "mbarrier.try_wait.parity.shared::cta.b64 s, [%6], %7;\n"
        "and.pred p, p, q;\n"
        "and.pred r, r, s;\n"
        "and.pred p, p, r;\n"
        "@p bra DONE_%=;\n"
        "add.u32 n, n, 1;\n"
        "setp.lt.u32 p, n, 4194304;\n"
        "@p bra WAIT_%=;\n"
        "exit;\n"
        "DONE_%=:\n"
        "}\n" :: "r"(b0), "r"(p0), "r"(b1), "r"(p1), "r"(b2), "r"(p2), "r"(b3), "r"(p3) : "memory");
}
__device__ __forceinline__ void mbar_wait2(uint32_t b0, uint32_t p0, uint32_t b1, uint32_t p1) {
    asm volatile(
        "{\n"
        ".reg .pred p, q;\n"
        ".reg .u32 n;\n"
        "mov.u32 n, 0;\n"
        "WAIT_%=:\n"
        "mbarrier.try_wait.parity.shared::cta.b64 p, [%0], %1;\n"
        "mbarrier.try_wait.parity.shared::cta.b64 q, [%2], %3;\n"
        "and.pred p, p, q;\n"
        "@p bra DONE_%=;\n"
        "add.u32 n, n, 1;\n"
        "setp.lt.u32 p, n, 4194304;\n"
        "@p bra WAIT_%=;\n"
        "exit;\n"
        "DONE_%=:\n"
        "}\n" :: "r"(b0), "r"(p0), "r"(b1), "r"(p1) : "memory");
}
__device__ __forceinline__ void mbar_wait_unless(uint32_t ok, uint32_t bar, uint32_t parity) {
    asm volatile(
        "{\n"
        ".reg .pred p;\n"
        ".reg .u32 n;\n"
        "setp.ne.u32 p, %2, 0;\n"
        "vote.sync.all.pred p, p, 0xffffffff;\n"
        "@p bra DONE_%=;\n"
        "mov.u32 n, 0;\n"
        "WAIT_%=:\n"
        "mbarrier.try_wait.parity.shared::cta.b64 p, [%0], %1" HINT_B ";\n"
        "@p bra DONE_%=;\n"
        "add.u32 n, n, 1;\n"
        "setp.lt.u32 p, n, 4194304;\n"
        "@p bra WAIT_%=;\n"
        "exit;\n"
        "DONE_%=:\n"
        "}\n" :: "r"(bar), "r"(parity), "r"(ok) : "memory");
}
__device__ __forceinline__ void mbar_wait_unless_dep(uint32_t ok, uint32_t bar, uint32_t parity, uint32_t zero, uint32_t& a,
                                                     uint32_t& b, uint32_t& c, uint32_t& d) {
    asm volatile(
        "{\n"
        ".reg .pred p;\n"
        ".reg .u32 n;\n"
        "setp.ne.u32 p, %6, 0;\n"
        "vote.sync.all.pred p, p, 0xffffffff;\n"
        "@p bra DONE_%=;\n"
        "mov.u32 n, 0;\n"
        "WAIT_%=:\n"
        "setp.ne.u32 p, %7, 0;\n"
        "@p ld.shared.v4.b32 {%0, %1, %2, %3}, [%7];\n"
        "mbarrier.try_wait.parity.shared::cta.b64 p, [%4], %5;\n"
        "@p bra DONE_%=;\n"
        "add.u32 n, n, 1;\n"
        "setp.lt.u32 p, n, 4194304;\n"
        "@p bra WAIT_%=;\n"
        "exit;\n"
        "DONE_%=:\n"
        "}\n" : "+r"(a), "+r"(b), "+r"(c), "+r"(d) : "r"(bar), "r"(parity), "r"(ok), "r"(zero) : "memory");
}
__device__ __forceinline__ void mbar_wait2_unless(uint32_t ok, uint32_t b0, uint32_t p0, uint32_t b1, uint32_t p1) {
    asm volatile(
        "{\n"
        ".reg .pred p, q;\n"
        ".reg .u32 n;\n"
        "setp.ne.u32 p, %4, 0;\n"
        "vote.sync.all.pred p, p, 0xffffffff;\n"
        "@p bra DONE_%=;\n"
        "mov.u32 n, 0;\n"
        "WAIT_%=:\n"
        "mbarrier.try_wait.parity.shared::cta.b64 p, [%0], %1" HINT_B ";\n"
        "mbarrier.try_wait.parity.shared::cta.b64 q, [%2], %3" HINT_B ";\n"
        "and.pred p, p, q;\n"
        "@p bra DONE_%=;\n"
        "add.u32 n, n, 1;\n"
        "setp.lt.u32 p, n, 4194304;\n"
        "@p bra WAIT_%=;\n"
        "exit;\n"
        "DONE_%=:\n"
        "}\n" :: "r"(b0), "r"(p0), "r"(b1), "r"(p1), "r"(ok) : "memory");
}
__device__ __forceinline__ void mbar_wait4_unless(uint32_t ok, uint32_t b0, uint32_t p0, uint32_t b1, uint32_t p1, uint32_t b2,
                                                  uint32_t p2, uint32_t b3, uint32_t p3) {
    asm volatile(
        "{\n"
        ".reg .pred p, q, r, s;\n"
        ".reg .u32 n;\n"
        "setp.ne.u32 p, %8, 0;\n"
        "vote.sync.all.pred p, p, 0xffffffff;\n"
        "@p bra DONE_%=;\n"
        "mov.u32 n, 0;\n"
        "WAIT_%=:\n"
        "mbarrier.try_wait.parity.shared::cta.b64 p, [%0], %1;\n"
        "mbarrier.try_wait.parity.shared::cta.b64 q, [%2], %3;\n"
        "mbarrier.try_wait.parity.shared::cta.b64 r, [%4], %5;\n"
        "mbarrier.try_wait.parity.shared::cta.b64 s, [%6], %7;\n"
        "and.pred p, p, q;\n"
        "and.pred r, r, s;\n"
        "and.pred p, p, r;\n"
        "@p bra DONE_%=;\n"
        "add.u32 n, n, 1;\n"
        "setp.lt.u32 p, n, 4194304;\n"
        "@p bra WAIT_%=;\n"
        "exit;\n"
        "DONE_%=:\n"
        "}\n" :: "r"(b0), "r"(p0), "r"(b1), "r"(p1), "r"(b2), "r"(p2), "r"(b3), "r"(p3), "r"(ok) : "memory");
}
__device__ __forceinline__ void sched_fence(uint32_t zero, uint32_t a, uint32_t b, uint32_t c, uint32_t d, uint32_t e = 0,
                                            uint32_t f = 0, uint32_t g = 0, uint32_t h = 0, uint32_t i = 0, uint32_t j = 0,
                                            uint32_t k = 0) {
    asm volatile("{\n.reg .pred p;\n.reg .u32 n;\nsetp.eq.u32 p, %0, 0;\n@p bra.uni DONE_%=;\nmov.u32 n, %0;\nSPIN_%=:\n"
                 "nanosleep.u32 %1;\nnanosleep.u32 %2;\nnanosleep.u32 %3;\nnanosleep.u32 %4;\nnanosleep.u32 %5;\n"
                 "nanosleep.u32 %6;\nnanosleep.u32 %7;\nnanosleep.u32 %8;\nnanosleep.u32 %9;\nnanosleep.u32 %10;\n"
                 "nanosleep.u32 %11;\nsub.u32 n, n, 1;\nsetp.ne.u32 p, n, 0;\n@p bra.uni SPIN_%=;\nDONE_%=:\n}\n"
                 :: "r"(zero), "r"(a), "r"(b), "r"(c), "r"(d), "r"(e), "r"(f), "r"(g), "r"(h), "r"(i), "r"(j), "r"(k) : "memory");
}
__device__ __forceinline__ void sched_fence16(uint32_t zero, const uint32_t (&v)[4][4], uint32_t a = 0, uint32_t b = 0) {
    asm volatile("{\n.reg .pred p;\n.reg .u32 n;\nsetp.eq.u32 p, %0, 0;\n@p bra.uni DONE_%=;\nmov.u32 n, %0;\nSPIN_%=:\n"
                 "nanosleep.u32 %17;\nnanosleep.u32 %18;\n"
                 "st.shared.v4.b32 [n], {%1, %2, %3, %4};\nst.shared.v4.b32 [n + 16], {%5, %6, %7, %8};\n"
                 "st.shared.v4.b32 [n + 32], {%9, %10, %11, %12};\nst.shared.v4.b32 [n + 48], {%13, %14, %15, %16};\n"
                 "sub.u32 n, n, 1;\nsetp.ne.u32 p, n, 0;\n@p bra.uni SPIN_%=;\nDONE_%=:\n}\n"
                 :: "r"(zero), "r"(v[0][0]), "r"(v[0][1]), "r"(v[0][2]), "r"(v[0][3]), "r"(v[1][0]), "r"(v[1][1]), "r"(v[1][2]), "r"(v[1][3]),
                    "r"(v[2][0]), "r"(v[2][1]), "r"(v[2][2]), "r"(v[2][3]), "r"(v[3][0]), "r"(v[3][1]), "r"(v[3][2]), "r"(v[3][3]),
                    "r"(a), "r"(b) : "memory");
}
__device__ __forceinline__ void sched_dep(uint32_t zero, uint32_t& a, uint32_t& b, uint32_t& c, uint32_t& d) {
    asm volatile("{\n.reg .pred p;\n.reg .u32 n;\nsetp.eq.u32 p, %4, 0;\n@p bra.uni DONE_%=;\nmov.u32 n, %4;\nSPIN_%=:\n"
                 "ld.shared.v4.b32 {%0, %1, %2, %3}, [n];\n"
                 "sub.u32 n, n, 1;\nsetp.ne.u32 p, n, 0;\n@p bra.uni SPIN_%=;\nDONE_%=:\n}\n"
                 : "+r"(a), "+r"(b), "+r"(c), "+r"(d) : "r"(zero) : "memory");
}
__device__ __forceinline__ void mbar_arrive(uint32_t bar) {
    asm volatile("mbarrier.arrive.shared::cta.b64 _, [%0];\n" :: "r"(bar) : "memory");
}
__device__ __forceinline__ void mbar_arrive_n(uint32_t bar, uint32_t n) {
    asm volatile("mbarrier.arrive.shared::cta.b64 _, [%0], %1;\n" :: "r"(bar), "r"(n) : "memory");
}
__device__ __forceinline__ void mbar_arrive_expect_tx(uint32_t bar, uint32_t bytes) {
    asm volatile("mbarrier.arrive.expect_tx.shared::cta.b64 _, [%0], %1;\n" :: "r"(bar), "r"(bytes) : "memory");
}
__device__ __forceinline__ void stg128_if(bool p, void* addr, uint32_t x, uint32_t y, uint32_t z, uint32_t w) {
    asm volatile("{\n.reg .pred q;\nsetp.ne.b32 q, %5, 0;\n@q st.global.L1::no_allocate.v4.b32 [%0], {%1, %2, %3, %4};\n}\n"
                 :: "l"(addr), "r"(x), "r"(y), "r"(z), "r"(w), "r"((uint32_t)p) : "memory");
}
__device__ __forceinline__ void stsm_x4(uint32_t addr, uint32_t r0, uint32_t r1, uint32_t r2, uint32_t r3) {
    asm volatile("stmatrix.sync.aligned.m8n8.x4.shared.b16 [%0], {%1, %2, %3, %4};\n"
                 :: "r"(addr), "r"(r0), "r"(r1), "r"(r2), "r"(r3) : "memory");
}
__device__ __forceinline__ void stsm_x2(uint32_t addr, uint32_t r0, uint32_t r1) {
    asm volatile("stmatrix.sync.aligned.m8n8.x2.shared.b16 [%0], {%1, %2};\n" :: "r"(addr), "r"(r0), "r"(r1) : "memory");
}
__device__ __forceinline__ void sts128(uint32_t addr, uint32_t r0, uint32_t r1, uint32_t r2, uint32_t r3) {
    asm volatile("st.shared.v4.b32 [%0], {%1, %2, %3, %4};\n" :: "r"(addr), "r"(r0), "r"(r1), "r"(r2), "r"(r3) : "memory");
}
__device__ __forceinline__ void sts32(uint32_t addr, uint32_t v) {
    asm volatile("st.shared.b32 [%0], %1;\n" :: "r"(addr), "r"(v) : "memory");
}
__device__ __forceinline__ uint32_t lds32(uint32_t addr) {
    uint32_t v;
    asm volatile("ld.shared.b32 %0, [%1];\n" : "=r"(v) : "r"(addr) : "memory");
    return v;
}
__device__ __forceinline__ void lds128(uint32_t (&r)[4], uint32_t addr) {
    asm volatile("ld.shared.v4.b32 {%0, %1, %2, %3}, [%4];\n" : "=r"(r[0]), "=r"(r[1]), "=r"(r[2]), "=r"(r[3]) : "r"(addr) : "memory");
}
__device__ __forceinline__ uint32_t lds32v(uint32_t addr) {
    uint32_t v;
    asm volatile("ld.volatile.shared.b32 %0, [%1];\n" : "=r"(v) : "r"(addr) : "memory");
    return v;
}
__device__ __forceinline__ void ldg_nc_v4(uint32_t (&r)[4], const void* p) {
    asm volatile("ld.global.nc.L1::no_allocate.v4.u32 {%0, %1, %2, %3}, [%4];\n"
                 : "=r"(r[0]), "=r"(r[1]), "=r"(r[2]), "=r"(r[3]) : "l"(p));
}
__device__ __forceinline__ uint32_t ldg_u32(const void* p) {
    uint32_t v;
    asm volatile("ld.global.nc.L1::evict_first.u32 %0, [%1];\n" : "=r"(v) : "l"(p));
    return v;
}
__device__ __forceinline__ void ldg_u64(const void* p, uint32_t& a, uint32_t& b) {
    asm volatile("ld.global.nc.L1::evict_first.v2.u32 {%0, %1}, [%2];\n" : "=r"(a), "=r"(b) : "l"(p));
}
__device__ __forceinline__ void prefetch_l2(const void* p) {
    asm volatile("prefetch.global.L2 [%0];\n" :: "l"(p));
}
__device__ __forceinline__ void cp_async16(uint32_t dst, const void* src) {
    asm volatile("cp.async.cg.shared.global [%0], [%1], 16;\n" :: "r"(dst), "l"(src) : "memory");
}
__device__ __forceinline__ float ex2_ftz(float x) {
    float y;
    asm("ex2.approx.ftz.f32 %0, %1;\n" : "=f"(y) : "f"(x));
    return y;
}
__device__ __forceinline__ float rcp_ftz(float x) {
    float y;
    asm("rcp.approx.ftz.f32 %0, %1;\n" : "=f"(y) : "f"(x));
    return y;
}
__device__ __forceinline__ float rsqrt_ftz(float x) {
    float y;
    asm("rsqrt.approx.ftz.f32 %0, %1;\n" : "=f"(y) : "f"(x));
    return y;
}

__device__ __forceinline__ bool elect_one() {
    uint32_t p;
    asm volatile("{\n.reg .pred q;\nelect.sync _|q, 0xffffffff;\nselp.u32 %0, 1, 0, q;\n}\n" : "=r"(p));
    return p != 0;
}
__device__ __forceinline__ void ldsm_x4(uint32_t (&r)[4], uint32_t addr) {
    asm volatile("ldmatrix.sync.aligned.m8n8.x4.shared.b16 {%0, %1, %2, %3}, [%4];\n"
                 : "=r"(r[0]), "=r"(r[1]), "=r"(r[2]), "=r"(r[3]) : "r"(addr) : "memory");
}
__device__ __forceinline__ void ldsm_x2(uint32_t& r0, uint32_t& r1, uint32_t addr) {
    asm volatile("ldmatrix.sync.aligned.m8n8.x2.shared.b16 {%0, %1}, [%2];\n" : "=r"(r0), "=r"(r1) : "r"(addr) : "memory");
}
__device__ __forceinline__ void tma_2d(uint32_t dst, const CUtensorMap* map, uint32_t bar, int c0, int c1) {
    asm volatile("cp.async.bulk.tensor.2d.shared::cluster.global.mbarrier::complete_tx::bytes [%0], [%1, {%3, %4}], [%2];\n"
                 :: "r"(dst), "l"(reinterpret_cast<uint64_t>(map)), "r"(bar), "r"(c0), "r"(c1) : "memory");
}
__device__ __forceinline__ void tma_3d(uint32_t dst, const CUtensorMap* map, uint32_t bar, int c0, int c1, int c2) {
    asm volatile("cp.async.bulk.tensor.3d.shared::cluster.global.mbarrier::complete_tx::bytes [%0], [%1, {%3, %4, %5}], [%2];\n"
                 :: "r"(dst), "l"(reinterpret_cast<uint64_t>(map)), "r"(bar), "r"(c0), "r"(c1), "r"(c2) : "memory");
}
__device__ __forceinline__ void tma_store_4d(const CUtensorMap* map, uint32_t src, int c0, int c1, int c2, int c3) {
    asm volatile("cp.async.bulk.tensor.4d.global.shared::cta.tile.bulk_group [%0, {%2, %3, %4, %5}], [%1];\n"
                 :: "l"(reinterpret_cast<uint64_t>(map)), "r"(src), "r"(c0), "r"(c1), "r"(c2), "r"(c3) : "memory");
}
__device__ __forceinline__ void mbar_arrive_if(uint32_t bar, uint32_t cnt) {
    asm volatile("{\n.reg .pred q;\nsetp.ne.b32 q, %1, 0;\n@q mbarrier.arrive.shared::cta.b64 _, [%0], %1;\n}\n"
                 :: "r"(bar), "r"(cnt) : "memory");
}

template <int BOFF, int AOFF, int NA>
__device__ __forceinline__ void mma_qk_first(uint32_t (&d)[48], const uint32_t (&a)[NA][4], uint64_t descB) {
    asm volatile(
        "{\n"
        ".reg .pred p0, p1;\n"
        ".reg .b64 ta, ta0, tb, tb0;\n"
        "setp.ne.b32 p0, 0, 0;\n"
        "setp.eq.b32 p1, 0, 0;\n"
        "add.s64 tb0, %64, %65;\n"
        "add.s64 tb, tb0, 0;\n"
        "wgmma.mma_async.sync.aligned.m64n192k16.f16.f16.f16 {%0, %1, %2, %3, %4, %5, %6, %7, %8, %9, %10, %11, %12, %13, %14, %15, %16, %17, %18, %19, %20, %21, %22, %23, %24, %25, %26, %27, %28, %29, %30, %31, %32, %33, %34, %35, %36, %37, %38, %39, %40, %41, %42, %43, %44, %45, %46, %47}, {%48, %49, %50, %51}, tb, p0, 1, 1, 1;\n"
        "add.s64 tb, tb0, 32;\n"
        "wgmma.mma_async.sync.aligned.m64n192k16.f16.f16.f16 {%0, %1, %2, %3, %4, %5, %6, %7, %8, %9, %10, %11, %12, %13, %14, %15, %16, %17, %18, %19, %20, %21, %22, %23, %24, %25, %26, %27, %28, %29, %30, %31, %32, %33, %34, %35, %36, %37, %38, %39, %40, %41, %42, %43, %44, %45, %46, %47}, {%52, %53, %54, %55}, tb, p1, 1, 1, 1;\n"
        "add.s64 tb, tb0, 64;\n"
        "wgmma.mma_async.sync.aligned.m64n192k16.f16.f16.f16 {%0, %1, %2, %3, %4, %5, %6, %7, %8, %9, %10, %11, %12, %13, %14, %15, %16, %17, %18, %19, %20, %21, %22, %23, %24, %25, %26, %27, %28, %29, %30, %31, %32, %33, %34, %35, %36, %37, %38, %39, %40, %41, %42, %43, %44, %45, %46, %47}, {%56, %57, %58, %59}, tb, p1, 1, 1, 1;\n"
        "add.s64 tb, tb0, 96;\n"
        "wgmma.mma_async.sync.aligned.m64n192k16.f16.f16.f16 {%0, %1, %2, %3, %4, %5, %6, %7, %8, %9, %10, %11, %12, %13, %14, %15, %16, %17, %18, %19, %20, %21, %22, %23, %24, %25, %26, %27, %28, %29, %30, %31, %32, %33, %34, %35, %36, %37, %38, %39, %40, %41, %42, %43, %44, %45, %46, %47}, {%60, %61, %62, %63}, tb, p1, 1, 1, 1;\n"
        "}\n"
        : "=r"(d[0]), "=r"(d[1]), "=r"(d[2]), "=r"(d[3]), "=r"(d[4]), "=r"(d[5]), "=r"(d[6]), "=r"(d[7]), "=r"(d[8]), "=r"(d[9]), "=r"(d[10]), "=r"(d[11]), "=r"(d[12]), "=r"(d[13]), "=r"(d[14]), "=r"(d[15]), "=r"(d[16]), "=r"(d[17]), "=r"(d[18]), "=r"(d[19]), "=r"(d[20]), "=r"(d[21]), "=r"(d[22]), "=r"(d[23]), "=r"(d[24]), "=r"(d[25]), "=r"(d[26]), "=r"(d[27]), "=r"(d[28]), "=r"(d[29]), "=r"(d[30]), "=r"(d[31]), "=r"(d[32]), "=r"(d[33]), "=r"(d[34]), "=r"(d[35]), "=r"(d[36]), "=r"(d[37]), "=r"(d[38]), "=r"(d[39]), "=r"(d[40]), "=r"(d[41]), "=r"(d[42]), "=r"(d[43]), "=r"(d[44]), "=r"(d[45]), "=r"(d[46]), "=r"(d[47])
        : "r"(a[AOFF + 0][0]), "r"(a[AOFF + 0][1]), "r"(a[AOFF + 0][2]), "r"(a[AOFF + 0][3]), "r"(a[AOFF + 1][0]), "r"(a[AOFF + 1][1]), "r"(a[AOFF + 1][2]), "r"(a[AOFF + 1][3]), "r"(a[AOFF + 2][0]), "r"(a[AOFF + 2][1]), "r"(a[AOFF + 2][2]), "r"(a[AOFF + 2][3]), "r"(a[AOFF + 3][0]), "r"(a[AOFF + 3][1]), "r"(a[AOFF + 3][2]), "r"(a[AOFF + 3][3]), "l"(descB), "n"(BOFF >> 4));
}

template <int BOFF, int AOFF, int NA>
__device__ __forceinline__ void mma_qk_next(uint32_t (&d)[48], const uint32_t (&a)[NA][4], uint64_t descB) {
    asm volatile(
        "{\n"
        ".reg .pred p0, p1;\n"
        ".reg .b64 ta, ta0, tb, tb0;\n"
        "setp.ne.b32 p0, 0, 0;\n"
        "setp.eq.b32 p1, 0, 0;\n"
        "add.s64 tb0, %64, %65;\n"
        "add.s64 tb, tb0, 0;\n"
        "wgmma.mma_async.sync.aligned.m64n192k16.f16.f16.f16 {%0, %1, %2, %3, %4, %5, %6, %7, %8, %9, %10, %11, %12, %13, %14, %15, %16, %17, %18, %19, %20, %21, %22, %23, %24, %25, %26, %27, %28, %29, %30, %31, %32, %33, %34, %35, %36, %37, %38, %39, %40, %41, %42, %43, %44, %45, %46, %47}, {%48, %49, %50, %51}, tb, p1, 1, 1, 1;\n"
        "add.s64 tb, tb0, 32;\n"
        "wgmma.mma_async.sync.aligned.m64n192k16.f16.f16.f16 {%0, %1, %2, %3, %4, %5, %6, %7, %8, %9, %10, %11, %12, %13, %14, %15, %16, %17, %18, %19, %20, %21, %22, %23, %24, %25, %26, %27, %28, %29, %30, %31, %32, %33, %34, %35, %36, %37, %38, %39, %40, %41, %42, %43, %44, %45, %46, %47}, {%52, %53, %54, %55}, tb, p1, 1, 1, 1;\n"
        "add.s64 tb, tb0, 64;\n"
        "wgmma.mma_async.sync.aligned.m64n192k16.f16.f16.f16 {%0, %1, %2, %3, %4, %5, %6, %7, %8, %9, %10, %11, %12, %13, %14, %15, %16, %17, %18, %19, %20, %21, %22, %23, %24, %25, %26, %27, %28, %29, %30, %31, %32, %33, %34, %35, %36, %37, %38, %39, %40, %41, %42, %43, %44, %45, %46, %47}, {%56, %57, %58, %59}, tb, p1, 1, 1, 1;\n"
        "add.s64 tb, tb0, 96;\n"
        "wgmma.mma_async.sync.aligned.m64n192k16.f16.f16.f16 {%0, %1, %2, %3, %4, %5, %6, %7, %8, %9, %10, %11, %12, %13, %14, %15, %16, %17, %18, %19, %20, %21, %22, %23, %24, %25, %26, %27, %28, %29, %30, %31, %32, %33, %34, %35, %36, %37, %38, %39, %40, %41, %42, %43, %44, %45, %46, %47}, {%60, %61, %62, %63}, tb, p1, 1, 1, 1;\n"
        "}\n"
        : "+r"(d[0]), "+r"(d[1]), "+r"(d[2]), "+r"(d[3]), "+r"(d[4]), "+r"(d[5]), "+r"(d[6]), "+r"(d[7]), "+r"(d[8]), "+r"(d[9]), "+r"(d[10]), "+r"(d[11]), "+r"(d[12]), "+r"(d[13]), "+r"(d[14]), "+r"(d[15]), "+r"(d[16]), "+r"(d[17]), "+r"(d[18]), "+r"(d[19]), "+r"(d[20]), "+r"(d[21]), "+r"(d[22]), "+r"(d[23]), "+r"(d[24]), "+r"(d[25]), "+r"(d[26]), "+r"(d[27]), "+r"(d[28]), "+r"(d[29]), "+r"(d[30]), "+r"(d[31]), "+r"(d[32]), "+r"(d[33]), "+r"(d[34]), "+r"(d[35]), "+r"(d[36]), "+r"(d[37]), "+r"(d[38]), "+r"(d[39]), "+r"(d[40]), "+r"(d[41]), "+r"(d[42]), "+r"(d[43]), "+r"(d[44]), "+r"(d[45]), "+r"(d[46]), "+r"(d[47])
        : "r"(a[AOFF + 0][0]), "r"(a[AOFF + 0][1]), "r"(a[AOFF + 0][2]), "r"(a[AOFF + 0][3]), "r"(a[AOFF + 1][0]), "r"(a[AOFF + 1][1]), "r"(a[AOFF + 1][2]), "r"(a[AOFF + 1][3]), "r"(a[AOFF + 2][0]), "r"(a[AOFF + 2][1]), "r"(a[AOFF + 2][2]), "r"(a[AOFF + 2][3]), "r"(a[AOFF + 3][0]), "r"(a[AOFF + 3][1]), "r"(a[AOFF + 3][2]), "r"(a[AOFF + 3][3]), "l"(descB), "n"(BOFF >> 4));
}

template <int BOFF, int AOFF, int NA>
__device__ __forceinline__ void mma_v_first(uint32_t (&d)[24], const uint32_t (&a)[NA][4], uint64_t descB) {
    asm volatile(
        "{\n"
        ".reg .pred p0, p1;\n"
        ".reg .b64 ta, ta0, tb, tb0;\n"
        "setp.ne.b32 p0, 0, 0;\n"
        "setp.eq.b32 p1, 0, 0;\n"
        "add.s64 tb0, %40, %41;\n"
        "add.s64 tb, tb0, 0;\n"
        "wgmma.mma_async.sync.aligned.m64n96k16.f16.f16.f16 {%0, %1, %2, %3, %4, %5, %6, %7, %8, %9, %10, %11, %12, %13, %14, %15, %16, %17, %18, %19, %20, %21, %22, %23}, {%24, %25, %26, %27}, tb, p0, 1, 1, 1;\n"
        "add.s64 tb, tb0, 32;\n"
        "wgmma.mma_async.sync.aligned.m64n96k16.f16.f16.f16 {%0, %1, %2, %3, %4, %5, %6, %7, %8, %9, %10, %11, %12, %13, %14, %15, %16, %17, %18, %19, %20, %21, %22, %23}, {%28, %29, %30, %31}, tb, p1, 1, 1, 1;\n"
        "add.s64 tb, tb0, 64;\n"
        "wgmma.mma_async.sync.aligned.m64n96k16.f16.f16.f16 {%0, %1, %2, %3, %4, %5, %6, %7, %8, %9, %10, %11, %12, %13, %14, %15, %16, %17, %18, %19, %20, %21, %22, %23}, {%32, %33, %34, %35}, tb, p1, 1, 1, 1;\n"
        "add.s64 tb, tb0, 96;\n"
        "wgmma.mma_async.sync.aligned.m64n96k16.f16.f16.f16 {%0, %1, %2, %3, %4, %5, %6, %7, %8, %9, %10, %11, %12, %13, %14, %15, %16, %17, %18, %19, %20, %21, %22, %23}, {%36, %37, %38, %39}, tb, p1, 1, 1, 1;\n"
        "}\n"
        : "=r"(d[0]), "=r"(d[1]), "=r"(d[2]), "=r"(d[3]), "=r"(d[4]), "=r"(d[5]), "=r"(d[6]), "=r"(d[7]), "=r"(d[8]), "=r"(d[9]), "=r"(d[10]), "=r"(d[11]), "=r"(d[12]), "=r"(d[13]), "=r"(d[14]), "=r"(d[15]), "=r"(d[16]), "=r"(d[17]), "=r"(d[18]), "=r"(d[19]), "=r"(d[20]), "=r"(d[21]), "=r"(d[22]), "=r"(d[23])
        : "r"(a[AOFF + 0][0]), "r"(a[AOFF + 0][1]), "r"(a[AOFF + 0][2]), "r"(a[AOFF + 0][3]), "r"(a[AOFF + 1][0]), "r"(a[AOFF + 1][1]), "r"(a[AOFF + 1][2]), "r"(a[AOFF + 1][3]), "r"(a[AOFF + 2][0]), "r"(a[AOFF + 2][1]), "r"(a[AOFF + 2][2]), "r"(a[AOFF + 2][3]), "r"(a[AOFF + 3][0]), "r"(a[AOFF + 3][1]), "r"(a[AOFF + 3][2]), "r"(a[AOFF + 3][3]), "l"(descB), "n"(BOFF >> 4));
}

template <int BOFF, int AOFF, int NA>
__device__ __forceinline__ void mma_v_next(uint32_t (&d)[24], const uint32_t (&a)[NA][4], uint64_t descB) {
    asm volatile(
        "{\n"
        ".reg .pred p0, p1;\n"
        ".reg .b64 ta, ta0, tb, tb0;\n"
        "setp.ne.b32 p0, 0, 0;\n"
        "setp.eq.b32 p1, 0, 0;\n"
        "add.s64 tb0, %40, %41;\n"
        "add.s64 tb, tb0, 0;\n"
        "wgmma.mma_async.sync.aligned.m64n96k16.f16.f16.f16 {%0, %1, %2, %3, %4, %5, %6, %7, %8, %9, %10, %11, %12, %13, %14, %15, %16, %17, %18, %19, %20, %21, %22, %23}, {%24, %25, %26, %27}, tb, p1, 1, 1, 1;\n"
        "add.s64 tb, tb0, 32;\n"
        "wgmma.mma_async.sync.aligned.m64n96k16.f16.f16.f16 {%0, %1, %2, %3, %4, %5, %6, %7, %8, %9, %10, %11, %12, %13, %14, %15, %16, %17, %18, %19, %20, %21, %22, %23}, {%28, %29, %30, %31}, tb, p1, 1, 1, 1;\n"
        "add.s64 tb, tb0, 64;\n"
        "wgmma.mma_async.sync.aligned.m64n96k16.f16.f16.f16 {%0, %1, %2, %3, %4, %5, %6, %7, %8, %9, %10, %11, %12, %13, %14, %15, %16, %17, %18, %19, %20, %21, %22, %23}, {%32, %33, %34, %35}, tb, p1, 1, 1, 1;\n"
        "add.s64 tb, tb0, 96;\n"
        "wgmma.mma_async.sync.aligned.m64n96k16.f16.f16.f16 {%0, %1, %2, %3, %4, %5, %6, %7, %8, %9, %10, %11, %12, %13, %14, %15, %16, %17, %18, %19, %20, %21, %22, %23}, {%36, %37, %38, %39}, tb, p1, 1, 1, 1;\n"
        "}\n"
        : "+r"(d[0]), "+r"(d[1]), "+r"(d[2]), "+r"(d[3]), "+r"(d[4]), "+r"(d[5]), "+r"(d[6]), "+r"(d[7]), "+r"(d[8]), "+r"(d[9]), "+r"(d[10]), "+r"(d[11]), "+r"(d[12]), "+r"(d[13]), "+r"(d[14]), "+r"(d[15]), "+r"(d[16]), "+r"(d[17]), "+r"(d[18]), "+r"(d[19]), "+r"(d[20]), "+r"(d[21]), "+r"(d[22]), "+r"(d[23])
        : "r"(a[AOFF + 0][0]), "r"(a[AOFF + 0][1]), "r"(a[AOFF + 0][2]), "r"(a[AOFF + 0][3]), "r"(a[AOFF + 1][0]), "r"(a[AOFF + 1][1]), "r"(a[AOFF + 1][2]), "r"(a[AOFF + 1][3]), "r"(a[AOFF + 2][0]), "r"(a[AOFF + 2][1]), "r"(a[AOFF + 2][2]), "r"(a[AOFF + 2][3]), "r"(a[AOFF + 3][0]), "r"(a[AOFF + 3][1]), "r"(a[AOFF + 3][2]), "r"(a[AOFF + 3][3]), "l"(descB), "n"(BOFF >> 4));
}

template <int AOFF, int BOFF>
__device__ __forceinline__ void mma_s0_f32(float (&d)[28], uint64_t descA, uint64_t descB) {
    asm volatile(
        "{\n"
        ".reg .pred p0, p1;\n"
        ".reg .b64 ta, ta0, tb, tb0;\n"
        "setp.ne.b32 p0, 0, 0;\n"
        "setp.eq.b32 p1, 0, 0;\n"
        "add.s64 tb0, %30, %31;\n"
        "add.s64 ta0, %28, %29;\n"
        "add.s64 tb, tb0, 4;\n"
        "add.s64 ta, ta0, 0;\n"
        "wgmma.mma_async.sync.aligned.m64n56k16.f32.f16.f16 {%0, %1, %2, %3, %4, %5, %6, %7, %8, %9, %10, %11, %12, %13, %14, %15, %16, %17, %18, %19, %20, %21, %22, %23, %24, %25, %26, %27}, ta, tb, p1, 1, 1, 0, 0;\n"
        "add.s64 tb, tb0, 1572;\n"
        "add.s64 ta, ta0, 1568;\n"
        "wgmma.mma_async.sync.aligned.m64n56k16.f32.f16.f16 {%0, %1, %2, %3, %4, %5, %6, %7, %8, %9, %10, %11, %12, %13, %14, %15, %16, %17, %18, %19, %20, %21, %22, %23, %24, %25, %26, %27}, ta, tb, p1, 1, 1, 0, 0;\n"
        "add.s64 tb, tb0, 3140;\n"
        "add.s64 ta, ta0, 3136;\n"
        "wgmma.mma_async.sync.aligned.m64n56k16.f32.f16.f16 {%0, %1, %2, %3, %4, %5, %6, %7, %8, %9, %10, %11, %12, %13, %14, %15, %16, %17, %18, %19, %20, %21, %22, %23, %24, %25, %26, %27}, ta, tb, p1, 1, 1, 0, 0;\n"
        "}\n"
        : "+f"(d[0]), "+f"(d[1]), "+f"(d[2]), "+f"(d[3]), "+f"(d[4]), "+f"(d[5]), "+f"(d[6]), "+f"(d[7]), "+f"(d[8]), "+f"(d[9]), "+f"(d[10]), "+f"(d[11]), "+f"(d[12]), "+f"(d[13]), "+f"(d[14]), "+f"(d[15]), "+f"(d[16]), "+f"(d[17]), "+f"(d[18]), "+f"(d[19]), "+f"(d[20]), "+f"(d[21]), "+f"(d[22]), "+f"(d[23]), "+f"(d[24]), "+f"(d[25]), "+f"(d[26]), "+f"(d[27])
        : "l"(descA), "n"(AOFF >> 4), "l"(descB), "n"(BOFF >> 4));
}

template <int AOFF, int BOFF>
__device__ __forceinline__ void mma_s0_f16(uint32_t (&d)[14], uint64_t descA, uint64_t descB) {
    asm volatile(
        "{\n"
        ".reg .pred p0, p1;\n"
        ".reg .b64 ta, ta0, tb, tb0;\n"
        "setp.ne.b32 p0, 0, 0;\n"
        "setp.eq.b32 p1, 0, 0;\n"
        "add.s64 tb0, %16, %17;\n"
        "add.s64 ta0, %14, %15;\n"
        "add.s64 tb, tb0, 4;\n"
        "add.s64 ta, ta0, 0;\n"
        "wgmma.mma_async.sync.aligned.m64n56k16.f16.f16.f16 {%0, %1, %2, %3, %4, %5, %6, %7, %8, %9, %10, %11, %12, %13}, ta, tb, p1, 1, 1, 0, 0;\n"
        "add.s64 tb, tb0, 1572;\n"
        "add.s64 ta, ta0, 1568;\n"
        "wgmma.mma_async.sync.aligned.m64n56k16.f16.f16.f16 {%0, %1, %2, %3, %4, %5, %6, %7, %8, %9, %10, %11, %12, %13}, ta, tb, p1, 1, 1, 0, 0;\n"
        "add.s64 tb, tb0, 3140;\n"
        "add.s64 ta, ta0, 3136;\n"
        "wgmma.mma_async.sync.aligned.m64n56k16.f16.f16.f16 {%0, %1, %2, %3, %4, %5, %6, %7, %8, %9, %10, %11, %12, %13}, ta, tb, p1, 1, 1, 0, 0;\n"
        "}\n"
        : "+r"(d[0]), "+r"(d[1]), "+r"(d[2]), "+r"(d[3]), "+r"(d[4]), "+r"(d[5]), "+r"(d[6]), "+r"(d[7]), "+r"(d[8]), "+r"(d[9]), "+r"(d[10]), "+r"(d[11]), "+r"(d[12]), "+r"(d[13])
        : "l"(descA), "n"(AOFF >> 4), "l"(descB), "n"(BOFF >> 4));
}

template <int AOFF, int BOFF>
__device__ __forceinline__ void mma_s1_f32(float (&d)[28], uint64_t descA, uint64_t descB) {
    asm volatile(
        "{\n"
        ".reg .pred p0, p1;\n"
        ".reg .b64 ta, ta0, tb, tb0;\n"
        "setp.ne.b32 p0, 0, 0;\n"
        "setp.eq.b32 p1, 0, 0;\n"
        "add.s64 tb0, %30, %31;\n"
        "add.s64 ta0, %28, %29;\n"
        "add.s64 tb, tb0, 6;\n"
        "add.s64 ta, ta0, 2;\n"
        "wgmma.mma_async.sync.aligned.m64n56k16.f32.f16.f16 {%0, %1, %2, %3, %4, %5, %6, %7, %8, %9, %10, %11, %12, %13, %14, %15, %16, %17, %18, %19, %20, %21, %22, %23, %24, %25, %26, %27}, ta, tb, p1, 1, 1, 0, 0;\n"
        "add.s64 tb, tb0, 1574;\n"
        "add.s64 ta, ta0, 1570;\n"
        "wgmma.mma_async.sync.aligned.m64n56k16.f32.f16.f16 {%0, %1, %2, %3, %4, %5, %6, %7, %8, %9, %10, %11, %12, %13, %14, %15, %16, %17, %18, %19, %20, %21, %22, %23, %24, %25, %26, %27}, ta, tb, p1, 1, 1, 0, 0;\n"
        "add.s64 tb, tb0, 3142;\n"
        "add.s64 ta, ta0, 3138;\n"
        "wgmma.mma_async.sync.aligned.m64n56k16.f32.f16.f16 {%0, %1, %2, %3, %4, %5, %6, %7, %8, %9, %10, %11, %12, %13, %14, %15, %16, %17, %18, %19, %20, %21, %22, %23, %24, %25, %26, %27}, ta, tb, p1, 1, 1, 0, 0;\n"
        "}\n"
        : "+f"(d[0]), "+f"(d[1]), "+f"(d[2]), "+f"(d[3]), "+f"(d[4]), "+f"(d[5]), "+f"(d[6]), "+f"(d[7]), "+f"(d[8]), "+f"(d[9]), "+f"(d[10]), "+f"(d[11]), "+f"(d[12]), "+f"(d[13]), "+f"(d[14]), "+f"(d[15]), "+f"(d[16]), "+f"(d[17]), "+f"(d[18]), "+f"(d[19]), "+f"(d[20]), "+f"(d[21]), "+f"(d[22]), "+f"(d[23]), "+f"(d[24]), "+f"(d[25]), "+f"(d[26]), "+f"(d[27])
        : "l"(descA), "n"(AOFF >> 4), "l"(descB), "n"(BOFF >> 4));
}

template <int AOFF, int BOFF>
__device__ __forceinline__ void mma_s1_f16(uint32_t (&d)[14], uint64_t descA, uint64_t descB) {
    asm volatile(
        "{\n"
        ".reg .pred p0, p1;\n"
        ".reg .b64 ta, ta0, tb, tb0;\n"
        "setp.ne.b32 p0, 0, 0;\n"
        "setp.eq.b32 p1, 0, 0;\n"
        "add.s64 tb0, %16, %17;\n"
        "add.s64 ta0, %14, %15;\n"
        "add.s64 tb, tb0, 6;\n"
        "add.s64 ta, ta0, 2;\n"
        "wgmma.mma_async.sync.aligned.m64n56k16.f16.f16.f16 {%0, %1, %2, %3, %4, %5, %6, %7, %8, %9, %10, %11, %12, %13}, ta, tb, p1, 1, 1, 0, 0;\n"
        "add.s64 tb, tb0, 1574;\n"
        "add.s64 ta, ta0, 1570;\n"
        "wgmma.mma_async.sync.aligned.m64n56k16.f16.f16.f16 {%0, %1, %2, %3, %4, %5, %6, %7, %8, %9, %10, %11, %12, %13}, ta, tb, p1, 1, 1, 0, 0;\n"
        "add.s64 tb, tb0, 3142;\n"
        "add.s64 ta, ta0, 3138;\n"
        "wgmma.mma_async.sync.aligned.m64n56k16.f16.f16.f16 {%0, %1, %2, %3, %4, %5, %6, %7, %8, %9, %10, %11, %12, %13}, ta, tb, p1, 1, 1, 0, 0;\n"
        "}\n"
        : "+r"(d[0]), "+r"(d[1]), "+r"(d[2]), "+r"(d[3]), "+r"(d[4]), "+r"(d[5]), "+r"(d[6]), "+r"(d[7]), "+r"(d[8]), "+r"(d[9]), "+r"(d[10]), "+r"(d[11]), "+r"(d[12]), "+r"(d[13])
        : "l"(descA), "n"(AOFF >> 4), "l"(descB), "n"(BOFF >> 4));
}

template <int BOFF, int AOFF, int NA>
__device__ __forceinline__ void mma_pv(uint32_t (&d)[14], const uint32_t (&a)[NA][4], uint64_t descB) {
    asm volatile(
        "{\n"
        ".reg .pred p0, p1;\n"
        ".reg .b64 ta, ta0, tb, tb0;\n"
        "setp.ne.b32 p0, 0, 0;\n"
        "setp.eq.b32 p1, 0, 0;\n"
        "add.s64 tb0, %30, %31;\n"
        "add.s64 tb, tb0, 0;\n"
        "wgmma.mma_async.sync.aligned.m64n56k16.f16.f16.f16 {%0, %1, %2, %3, %4, %5, %6, %7, %8, %9, %10, %11, %12, %13}, {%14, %15, %16, %17}, tb, p0, 1, 1, 1;\n"
        "add.s64 tb, tb0, 16;\n"
        "wgmma.mma_async.sync.aligned.m64n56k16.f16.f16.f16 {%0, %1, %2, %3, %4, %5, %6, %7, %8, %9, %10, %11, %12, %13}, {%18, %19, %20, %21}, tb, p1, 1, 1, 1;\n"
        "add.s64 tb, tb0, 32;\n"
        "wgmma.mma_async.sync.aligned.m64n56k16.f16.f16.f16 {%0, %1, %2, %3, %4, %5, %6, %7, %8, %9, %10, %11, %12, %13}, {%22, %23, %24, %25}, tb, p1, 1, 1, 1;\n"
        "add.s64 tb, tb0, 48;\n"
        "wgmma.mma_async.sync.aligned.m64n56k16.f16.f16.f16 {%0, %1, %2, %3, %4, %5, %6, %7, %8, %9, %10, %11, %12, %13}, {%26, %27, %28, %29}, tb, p1, 1, 1, 1;\n"
        "}\n"
        : "=r"(d[0]), "=r"(d[1]), "=r"(d[2]), "=r"(d[3]), "=r"(d[4]), "=r"(d[5]), "=r"(d[6]), "=r"(d[7]), "=r"(d[8]), "=r"(d[9]), "=r"(d[10]), "=r"(d[11]), "=r"(d[12]), "=r"(d[13])
        : "r"(a[AOFF + 0][0]), "r"(a[AOFF + 0][1]), "r"(a[AOFF + 0][2]), "r"(a[AOFF + 0][3]), "r"(a[AOFF + 1][0]), "r"(a[AOFF + 1][1]), "r"(a[AOFF + 1][2]), "r"(a[AOFF + 1][3]), "r"(a[AOFF + 2][0]), "r"(a[AOFF + 2][1]), "r"(a[AOFF + 2][2]), "r"(a[AOFF + 2][3]), "r"(a[AOFF + 3][0]), "r"(a[AOFF + 3][1]), "r"(a[AOFF + 3][2]), "r"(a[AOFF + 3][3]), "l"(descB), "n"(BOFF >> 4));
}

template <int AOFF, int BOFF>
__device__ __forceinline__ void mma_proj(float (&d)[96], uint64_t descA, uint64_t descB) {
    asm volatile(
        "{\n"
        ".reg .pred p0, p1;\n"
        ".reg .b64 ta, ta0, tb, tb0;\n"
        "setp.ne.b32 p0, 0, 0;\n"
        "setp.eq.b32 p1, 0, 0;\n"
        "add.s64 tb0, %98, %99;\n"
        "add.s64 ta0, %96, %97;\n"
        "add.s64 tb, tb0, 0;\n"
        "add.s64 ta, ta0, 0;\n"
        "wgmma.mma_async.sync.aligned.m64n192k16.f32.f16.f16 {%0, %1, %2, %3, %4, %5, %6, %7, %8, %9, %10, %11, %12, %13, %14, %15, %16, %17, %18, %19, %20, %21, %22, %23, %24, %25, %26, %27, %28, %29, %30, %31, %32, %33, %34, %35, %36, %37, %38, %39, %40, %41, %42, %43, %44, %45, %46, %47, %48, %49, %50, %51, %52, %53, %54, %55, %56, %57, %58, %59, %60, %61, %62, %63, %64, %65, %66, %67, %68, %69, %70, %71, %72, %73, %74, %75, %76, %77, %78, %79, %80, %81, %82, %83, %84, %85, %86, %87, %88, %89, %90, %91, %92, %93, %94, %95}, ta, tb, p0, 1, 1, 0, 1;\n"
        "add.s64 tb, tb0, 64;\n"
        "add.s64 ta, ta0, 2;\n"
        "wgmma.mma_async.sync.aligned.m64n192k16.f32.f16.f16 {%0, %1, %2, %3, %4, %5, %6, %7, %8, %9, %10, %11, %12, %13, %14, %15, %16, %17, %18, %19, %20, %21, %22, %23, %24, %25, %26, %27, %28, %29, %30, %31, %32, %33, %34, %35, %36, %37, %38, %39, %40, %41, %42, %43, %44, %45, %46, %47, %48, %49, %50, %51, %52, %53, %54, %55, %56, %57, %58, %59, %60, %61, %62, %63, %64, %65, %66, %67, %68, %69, %70, %71, %72, %73, %74, %75, %76, %77, %78, %79, %80, %81, %82, %83, %84, %85, %86, %87, %88, %89, %90, %91, %92, %93, %94, %95}, ta, tb, p1, 1, 1, 0, 1;\n"
        "add.s64 tb, tb0, 128;\n"
        "add.s64 ta, ta0, 4;\n"
        "wgmma.mma_async.sync.aligned.m64n192k16.f32.f16.f16 {%0, %1, %2, %3, %4, %5, %6, %7, %8, %9, %10, %11, %12, %13, %14, %15, %16, %17, %18, %19, %20, %21, %22, %23, %24, %25, %26, %27, %28, %29, %30, %31, %32, %33, %34, %35, %36, %37, %38, %39, %40, %41, %42, %43, %44, %45, %46, %47, %48, %49, %50, %51, %52, %53, %54, %55, %56, %57, %58, %59, %60, %61, %62, %63, %64, %65, %66, %67, %68, %69, %70, %71, %72, %73, %74, %75, %76, %77, %78, %79, %80, %81, %82, %83, %84, %85, %86, %87, %88, %89, %90, %91, %92, %93, %94, %95}, ta, tb, p1, 1, 1, 0, 1;\n"
        "add.s64 tb, tb0, 192;\n"
        "add.s64 ta, ta0, 6;\n"
        "wgmma.mma_async.sync.aligned.m64n192k16.f32.f16.f16 {%0, %1, %2, %3, %4, %5, %6, %7, %8, %9, %10, %11, %12, %13, %14, %15, %16, %17, %18, %19, %20, %21, %22, %23, %24, %25, %26, %27, %28, %29, %30, %31, %32, %33, %34, %35, %36, %37, %38, %39, %40, %41, %42, %43, %44, %45, %46, %47, %48, %49, %50, %51, %52, %53, %54, %55, %56, %57, %58, %59, %60, %61, %62, %63, %64, %65, %66, %67, %68, %69, %70, %71, %72, %73, %74, %75, %76, %77, %78, %79, %80, %81, %82, %83, %84, %85, %86, %87, %88, %89, %90, %91, %92, %93, %94, %95}, ta, tb, p1, 1, 1, 0, 1;\n"
        "add.s64 tb, tb0, 256;\n"
        "add.s64 ta, ta0, 512;\n"
        "wgmma.mma_async.sync.aligned.m64n192k16.f32.f16.f16 {%0, %1, %2, %3, %4, %5, %6, %7, %8, %9, %10, %11, %12, %13, %14, %15, %16, %17, %18, %19, %20, %21, %22, %23, %24, %25, %26, %27, %28, %29, %30, %31, %32, %33, %34, %35, %36, %37, %38, %39, %40, %41, %42, %43, %44, %45, %46, %47, %48, %49, %50, %51, %52, %53, %54, %55, %56, %57, %58, %59, %60, %61, %62, %63, %64, %65, %66, %67, %68, %69, %70, %71, %72, %73, %74, %75, %76, %77, %78, %79, %80, %81, %82, %83, %84, %85, %86, %87, %88, %89, %90, %91, %92, %93, %94, %95}, ta, tb, p1, 1, 1, 0, 1;\n"
        "add.s64 tb, tb0, 320;\n"
        "add.s64 ta, ta0, 514;\n"
        "wgmma.mma_async.sync.aligned.m64n192k16.f32.f16.f16 {%0, %1, %2, %3, %4, %5, %6, %7, %8, %9, %10, %11, %12, %13, %14, %15, %16, %17, %18, %19, %20, %21, %22, %23, %24, %25, %26, %27, %28, %29, %30, %31, %32, %33, %34, %35, %36, %37, %38, %39, %40, %41, %42, %43, %44, %45, %46, %47, %48, %49, %50, %51, %52, %53, %54, %55, %56, %57, %58, %59, %60, %61, %62, %63, %64, %65, %66, %67, %68, %69, %70, %71, %72, %73, %74, %75, %76, %77, %78, %79, %80, %81, %82, %83, %84, %85, %86, %87, %88, %89, %90, %91, %92, %93, %94, %95}, ta, tb, p1, 1, 1, 0, 1;\n"
        "add.s64 tb, tb0, 384;\n"
        "add.s64 ta, ta0, 516;\n"
        "wgmma.mma_async.sync.aligned.m64n192k16.f32.f16.f16 {%0, %1, %2, %3, %4, %5, %6, %7, %8, %9, %10, %11, %12, %13, %14, %15, %16, %17, %18, %19, %20, %21, %22, %23, %24, %25, %26, %27, %28, %29, %30, %31, %32, %33, %34, %35, %36, %37, %38, %39, %40, %41, %42, %43, %44, %45, %46, %47, %48, %49, %50, %51, %52, %53, %54, %55, %56, %57, %58, %59, %60, %61, %62, %63, %64, %65, %66, %67, %68, %69, %70, %71, %72, %73, %74, %75, %76, %77, %78, %79, %80, %81, %82, %83, %84, %85, %86, %87, %88, %89, %90, %91, %92, %93, %94, %95}, ta, tb, p1, 1, 1, 0, 1;\n"
        "add.s64 tb, tb0, 448;\n"
        "add.s64 ta, ta0, 518;\n"
        "wgmma.mma_async.sync.aligned.m64n192k16.f32.f16.f16 {%0, %1, %2, %3, %4, %5, %6, %7, %8, %9, %10, %11, %12, %13, %14, %15, %16, %17, %18, %19, %20, %21, %22, %23, %24, %25, %26, %27, %28, %29, %30, %31, %32, %33, %34, %35, %36, %37, %38, %39, %40, %41, %42, %43, %44, %45, %46, %47, %48, %49, %50, %51, %52, %53, %54, %55, %56, %57, %58, %59, %60, %61, %62, %63, %64, %65, %66, %67, %68, %69, %70, %71, %72, %73, %74, %75, %76, %77, %78, %79, %80, %81, %82, %83, %84, %85, %86, %87, %88, %89, %90, %91, %92, %93, %94, %95}, ta, tb, p1, 1, 1, 0, 1;\n"
        "add.s64 tb, tb0, 512;\n"
        "add.s64 ta, ta0, 1024;\n"
        "wgmma.mma_async.sync.aligned.m64n192k16.f32.f16.f16 {%0, %1, %2, %3, %4, %5, %6, %7, %8, %9, %10, %11, %12, %13, %14, %15, %16, %17, %18, %19, %20, %21, %22, %23, %24, %25, %26, %27, %28, %29, %30, %31, %32, %33, %34, %35, %36, %37, %38, %39, %40, %41, %42, %43, %44, %45, %46, %47, %48, %49, %50, %51, %52, %53, %54, %55, %56, %57, %58, %59, %60, %61, %62, %63, %64, %65, %66, %67, %68, %69, %70, %71, %72, %73, %74, %75, %76, %77, %78, %79, %80, %81, %82, %83, %84, %85, %86, %87, %88, %89, %90, %91, %92, %93, %94, %95}, ta, tb, p1, 1, 1, 0, 1;\n"
        "add.s64 tb, tb0, 576;\n"
        "add.s64 ta, ta0, 1026;\n"
        "wgmma.mma_async.sync.aligned.m64n192k16.f32.f16.f16 {%0, %1, %2, %3, %4, %5, %6, %7, %8, %9, %10, %11, %12, %13, %14, %15, %16, %17, %18, %19, %20, %21, %22, %23, %24, %25, %26, %27, %28, %29, %30, %31, %32, %33, %34, %35, %36, %37, %38, %39, %40, %41, %42, %43, %44, %45, %46, %47, %48, %49, %50, %51, %52, %53, %54, %55, %56, %57, %58, %59, %60, %61, %62, %63, %64, %65, %66, %67, %68, %69, %70, %71, %72, %73, %74, %75, %76, %77, %78, %79, %80, %81, %82, %83, %84, %85, %86, %87, %88, %89, %90, %91, %92, %93, %94, %95}, ta, tb, p1, 1, 1, 0, 1;\n"
        "add.s64 tb, tb0, 640;\n"
        "add.s64 ta, ta0, 1028;\n"
        "wgmma.mma_async.sync.aligned.m64n192k16.f32.f16.f16 {%0, %1, %2, %3, %4, %5, %6, %7, %8, %9, %10, %11, %12, %13, %14, %15, %16, %17, %18, %19, %20, %21, %22, %23, %24, %25, %26, %27, %28, %29, %30, %31, %32, %33, %34, %35, %36, %37, %38, %39, %40, %41, %42, %43, %44, %45, %46, %47, %48, %49, %50, %51, %52, %53, %54, %55, %56, %57, %58, %59, %60, %61, %62, %63, %64, %65, %66, %67, %68, %69, %70, %71, %72, %73, %74, %75, %76, %77, %78, %79, %80, %81, %82, %83, %84, %85, %86, %87, %88, %89, %90, %91, %92, %93, %94, %95}, ta, tb, p1, 1, 1, 0, 1;\n"
        "add.s64 tb, tb0, 704;\n"
        "add.s64 ta, ta0, 1030;\n"
        "wgmma.mma_async.sync.aligned.m64n192k16.f32.f16.f16 {%0, %1, %2, %3, %4, %5, %6, %7, %8, %9, %10, %11, %12, %13, %14, %15, %16, %17, %18, %19, %20, %21, %22, %23, %24, %25, %26, %27, %28, %29, %30, %31, %32, %33, %34, %35, %36, %37, %38, %39, %40, %41, %42, %43, %44, %45, %46, %47, %48, %49, %50, %51, %52, %53, %54, %55, %56, %57, %58, %59, %60, %61, %62, %63, %64, %65, %66, %67, %68, %69, %70, %71, %72, %73, %74, %75, %76, %77, %78, %79, %80, %81, %82, %83, %84, %85, %86, %87, %88, %89, %90, %91, %92, %93, %94, %95}, ta, tb, p1, 1, 1, 0, 1;\n"
        "}\n"
        : "+f"(d[0]), "+f"(d[1]), "+f"(d[2]), "+f"(d[3]), "+f"(d[4]), "+f"(d[5]), "+f"(d[6]), "+f"(d[7]), "+f"(d[8]), "+f"(d[9]), "+f"(d[10]), "+f"(d[11]), "+f"(d[12]), "+f"(d[13]), "+f"(d[14]), "+f"(d[15]), "+f"(d[16]), "+f"(d[17]), "+f"(d[18]), "+f"(d[19]), "+f"(d[20]), "+f"(d[21]), "+f"(d[22]), "+f"(d[23]), "+f"(d[24]), "+f"(d[25]), "+f"(d[26]), "+f"(d[27]), "+f"(d[28]), "+f"(d[29]), "+f"(d[30]), "+f"(d[31]), "+f"(d[32]), "+f"(d[33]), "+f"(d[34]), "+f"(d[35]), "+f"(d[36]), "+f"(d[37]), "+f"(d[38]), "+f"(d[39]), "+f"(d[40]), "+f"(d[41]), "+f"(d[42]), "+f"(d[43]), "+f"(d[44]), "+f"(d[45]), "+f"(d[46]), "+f"(d[47]), "+f"(d[48]), "+f"(d[49]), "+f"(d[50]), "+f"(d[51]), "+f"(d[52]), "+f"(d[53]), "+f"(d[54]), "+f"(d[55]), "+f"(d[56]), "+f"(d[57]), "+f"(d[58]), "+f"(d[59]), "+f"(d[60]), "+f"(d[61]), "+f"(d[62]), "+f"(d[63]), "+f"(d[64]), "+f"(d[65]), "+f"(d[66]), "+f"(d[67]), "+f"(d[68]), "+f"(d[69]), "+f"(d[70]), "+f"(d[71]), "+f"(d[72]), "+f"(d[73]), "+f"(d[74]), "+f"(d[75]), "+f"(d[76]), "+f"(d[77]), "+f"(d[78]), "+f"(d[79]), "+f"(d[80]), "+f"(d[81]), "+f"(d[82]), "+f"(d[83]), "+f"(d[84]), "+f"(d[85]), "+f"(d[86]), "+f"(d[87]), "+f"(d[88]), "+f"(d[89]), "+f"(d[90]), "+f"(d[91]), "+f"(d[92]), "+f"(d[93]), "+f"(d[94]), "+f"(d[95])
        : "l"(descA), "n"(AOFF >> 4), "l"(descB), "n"(BOFF >> 4));
}

struct Params {
    const __nv_bfloat16* x;
    const __nv_bfloat16* wqkv;
    const __nv_bfloat16* wo;
    const __nv_bfloat16* logit_scale;
    const __nv_bfloat16* cpb_w1;
    const __nv_bfloat16* cpb_w2;
    const __nv_bfloat16* rel_coords;
    const int*           rel_idx;
    const __nv_bfloat16* mask;
    __nv_bfloat16*       out;
    unsigned long long   z1;
    int                  npair;
    uint32_t             need;
    int                  spread;
    int                  t1;
};

constexpr uint32_t POS_END = 0x8000;
__device__ __forceinline__ uint32_t pos_add(uint32_t pos, int n) {
    pos += n;
    return (pos & 127) >= NWS ? pos + (128 - NWS) : pos;
}
__device__ __forceinline__ int role_of(const Params& P, int b) {
    const int n0 = ((b >> 1) * P.spread) >> 16, n1 = (((b >> 1) + 1) * P.spread) >> 16;
    return n1 != n0 ? 2 * P.npair + 2 * n0 + (b & 1) : b - 2 * n0;
}
__device__ __forceinline__ void finish(uint32_t total) {
    __threadfence();
    if (atomicAdd(&g_done, 1u) == total - 1) {
        for (int i = 0; i < NWS; i++) g_cnt[i] = 0;
        g_next[0] = 0; g_next[1] = 0;
        g_done = 0;
    }
}

constexpr int FB_PITCH = 584, FB_X = TOK * FB_PITCH * 2, FB_TAB = FB_X + TOK * 384, FB_BYTES = FB_TAB + 169 * 8 + 8;
static_assert(3 * FB_BYTES <= SM_PBAR && FB_BYTES % 16 == 0 && SM_BAR + B_ROWS == SM_PBAR + 64 && PCHUNK, "smem");
__device__ __forceinline__ void redo(const Params& P, uint8_t* sm, uint32_t tag, int barid) {
    typedef __nv_bfloat16 bf;
    const int t = threadIdx.x & 127, lane = t & 31;
    bf* const qkv = reinterpret_cast<bf*>(sm);
    bf* const xs = reinterpret_cast<bf*>(sm + FB_X);
    bf* const tab = reinterpret_cast<bf*>(sm + FB_TAB);
    volatile int* const next = reinterpret_cast<volatile int*>(sm + FB_TAB + 169 * 8);
#pragma unroll 1
    for (uint32_t n = 0; n < (1u << 22); n++) {
        uint32_t a;
        asm volatile("ld.acquire.gpu.global.u32 %0, [%1];\n" : "=r"(a) : "l"(g_guard) : "memory");
        if (a == tag + 1) break;
        __nanosleep(256);
    }
    asm volatile("fence.proxy.async;\n" ::: "memory");
#pragma unroll 1
    for (int i = t; i < 169 * 4; i += 128) {
        float a = 0.f;
#pragma unroll 1
        for (int u = 0; u < 16; u++) {
            const float h = round_bf16(__bfloat162float(P.rel_coords[(i >> 2) * 2]) * __bfloat162float(P.cpb_w1[u]) +
                                       __bfloat162float(P.rel_coords[(i >> 2) * 2 + 1]) * __bfloat162float(P.cpb_w1[16 + u]));
            a += (h > 0.f ? h : h * 0.f) * __bfloat162float(P.cpb_w2[u * 4 + (i & 3)]);
        }
        tab[i] = __float2bfloat16_rn(16.f * round_bf16(1.f / (1.f + expf(-round_bf16(a)))));
    }
#pragma unroll 1
    for (;;) {
        wg_bar(barid);
        if (t == 0) *next = (int)atomicAdd(g_guard + 2, 1u);
        wg_bar(barid);
        const int win = *next;
        if (win >= NWINDOWS) return;
        const int y0 = 7 * (win / NWS) + 3, x0 = 7 * (win % NWS) + 3;
        auto pixel = [&](int r) { return (size_t)(((y0 + r / 7) % IMG) * IMG + (x0 + r % 7) % IMG) * 192; };
#pragma unroll 1
        for (int i = t; i < TOK * 24; i += 128)
            reinterpret_cast<uint4*>(xs)[i] = reinterpret_cast<const uint4*>(P.x + pixel(i / 24))[i % 24];
#pragma unroll 1
        for (int ph = 0; ph < 2; ph++) {
            const bf* const a = ph ? qkv : xs;
            bf* const d = ph ? xs : qkv;
            const int n = ph ? 192 : 576, pa = ph ? FB_PITCH : 192, pd = ph ? 192 : FB_PITCH;
            wg_bar(barid);
#pragma unroll 1
            for (int col = t; col < n; col += 128) {
                const bf* w = (ph ? P.wo : P.wqkv) + col;
                float acc[TOK];
#pragma unroll
                for (int r = 0; r < TOK; r++) acc[r] = 0.f;
#pragma unroll 1
                for (int k = 0; k < 192; k += 2) {
                    const float w0 = __bfloat162float(w[k * n]), w1 = __bfloat162float(w[(k + 1) * n]);
#pragma unroll
                    for (int r = 0; r < TOK; r++) {
                        const uint32_t v = *reinterpret_cast<const uint32_t*>(a + r * pa + k);
                        acc[r] = fmaf(bf16hi(v), w1, fmaf(bf16lo(v), w0, acc[r]));
                    }
                }
#pragma unroll
                for (int r = 0; r < TOK; r++) d[r * pd + col] = __float2bfloat16_rn(acc[r]);
            }
            wg_bar(barid);
            if (ph) break;
#pragma unroll 1
            for (int i = t; i < TOK * 8; i += 128) {
                bf* const v = qkv + (i % TOK) * FB_PITCH + (i / TOK) * 48;
                float s = 0.f;
#pragma unroll 1
                for (int j = 0; j < 48; j++) s = fmaf(__bfloat162float(v[j]), __bfloat162float(v[j]), s);
                s = round_bf16(1.f / sqrtf(round_bf16(round_bf16(s) + 1e-12f)));
#pragma unroll 1
                for (int j = 0; j < 48; j++) v[j] = __float2bfloat16_rn(__bfloat162float(v[j]) * s);
            }
            wg_bar(barid);
#pragma unroll 1
            for (int i = t; i < TOK * 4; i += 128) {
                const int r = i % TOK, h = i / TOK;
                uint32_t* const q = reinterpret_cast<uint32_t*>(qkv + r * FB_PITCH + h * 48);
                const float tau = round_bf16(expf(round_bf16(fminf(fmaxf(__bfloat162float(P.logit_scale[h]), -100.f), 4.6052f))));
                float v[48], mx = -INFINITY, sum = 0.f;
#pragma unroll
                for (int j = 0; j < 24; j++) { v[2 * j] = bf16lo(q[j]); v[2 * j + 1] = bf16hi(q[j]); }
#pragma unroll 1
                for (int j = 0; j < TOK; j++) {
                    const uint32_t* kk = reinterpret_cast<const uint32_t*>(qkv + j * FB_PITCH + 192 + h * 48);
                    float s = 0.f;
#pragma unroll
                    for (int u = 0; u < 24; u++) s = fmaf(v[2 * u + 1], bf16hi(kk[u]), fmaf(v[2 * u], bf16lo(kk[u]), s));
                    s = round_bf16(round_bf16(s) * tau);
                    s = round_bf16(s + __bfloat162float(tab[min(max(P.rel_idx[r * TOK + j], 0), 168) * 4 + h]));
                    s = round_bf16(s + __bfloat162float(P.mask[(size_t)win * (TOK * TOK) + r * TOK + j]));
                    xs[j * 128 + t] = __float2bfloat16_rn(s);
                    mx = fmaxf(mx, s);
                }
#pragma unroll 1
                for (int j = 0; j < TOK; j++) sum += expf(__bfloat162float(xs[j * 128 + t]) - mx);
#pragma unroll
                for (int j = 0; j < 48; j++) v[j] = 0.f;
#pragma unroll 1
                for (int j = 0; j < TOK; j++) {
                    const uint32_t* vv = reinterpret_cast<const uint32_t*>(qkv + j * FB_PITCH + 384 + h * 48);
                    const float p = round_bf16(expf(__bfloat162float(xs[j * 128 + t]) - mx) / sum);
#pragma unroll
                    for (int u = 0; u < 24; u++) {
                        v[2 * u] = fmaf(p, bf16lo(vv[u]), v[2 * u]);
                        v[2 * u + 1] = fmaf(p, bf16hi(vv[u]), v[2 * u + 1]);
                    }
                }
#pragma unroll
                for (int j = 0; j < 24; j++) q[j] = pack_bf16(v[2 * j], v[2 * j + 1]);
            }
        }
#pragma unroll 1
        for (int r = t >> 5; r < TOK; r += 4) {
            float v[6], m = 0.f, s = 0.f;
#pragma unroll
            for (int j = 0; j < 6; j++) { v[j] = __bfloat162float(xs[r * 192 + j * 32 + lane]); m += v[j]; }
#pragma unroll
            for (int o = 16; o; o >>= 1) m += __shfl_xor_sync(0xffffffffu, m, o);
            m *= 1.f / 192.f;
#pragma unroll
            for (int j = 0; j < 6; j++) s = fmaf(v[j] - m, v[j] - m, s);
#pragma unroll
            for (int o = 16; o; o >>= 1) s += __shfl_xor_sync(0xffffffffu, s, o);
            s = round_bf16(sqrtf(round_bf16(round_bf16(s * (1.f / 192.f)) + 1e-5f)));
            m = round_bf16(m);
#pragma unroll
            for (int j = 0; j < 6; j++) P.out[pixel(r) + j * 32 + lane] = __float2bfloat16_rn(round_bf16(v[j] - m) / s);
        }
    }
}

__global__ void __launch_bounds__(NTHREADS, 1)
swin_window_attn_kernel(const Params P, const __grid_constant__ CUtensorMap xmap, const __grid_constant__ CUtensorMap xmap4,
                        const __grid_constant__ CUtensorMap xmap3,
                        const __grid_constant__ CUtensorMap omap, const __grid_constant__ CUtensorMap wmap,
                        const __grid_constant__ CUtensorMap smap, const __grid_constant__ CUtensorMap omapb,
                        const __grid_constant__ CUtensorMap xmapa, const __grid_constant__ CUtensorMap xmapb,
                        const __grid_constant__ CUtensorMap smap3, const __grid_constant__ CUtensorMap wraw) {
    extern __shared__ __align__(1024) uint8_t smem[];
    constexpr uint32_t sbase = 1024;
    if (smem_u32(smem) != sbase) return;
    const int tid = threadIdx.x;
    const int wg = __shfl_sync(0xffffffffu, tid >> 7, 0);
    const int warp = __shfl_sync(0xffffffffu, (tid >> 5) & 3, 0);
    const int lane = tid & 31;
    const int g = lane >> 2, c = lane & 3;

    TR(26, wg);
    if (wg == 0) { ST(0); SC(27); }
    const int role = role_of(P, blockIdx.x);
    const bool attn = role < 2 * P.npair;
    const int pair = role >> 1, half = role & 1;
    const uint32_t bars = sbase + SM_BAR;
    const int t0 = min(warp * 16 + g, TOK - 1), t1 = min(warp * 16 + g + 8, TOK - 1);
    int ridx[26];
    uint32_t rc, w2[16];
    uint4 w1[4];
    if (attn && (wg == 1 || wg == 2)) {
        rc = reinterpret_cast<const uint32_t*>(P.rel_coords)[min(tid - 128, 168)];
#pragma unroll
        for (int i = 0; i < 4; i++) w1[i] = reinterpret_cast<const uint4*>(P.cpb_w1)[i];
#pragma unroll
        for (int u = 0; u < 16; u++) w2[u] = reinterpret_cast<const uint32_t*>(P.cpb_w2)[2 * u + half];
#pragma unroll
        for (int rh = 0; rh < 2; rh++) {
            const int* ri = P.rel_idx + (rh ? t1 : t0) * TOK;
#pragma unroll
            for (int j = 0; j < 12; j++) ridx[13 * rh + j] = ri[8 * (j >> 1) + 2 * c + (j & 1)];
            ridx[13 * rh + 12] = ri[48];
        }
    }
    {
        if (tid == 416) {
            const CUtensorMap* maps[4] = {attn ? &smap : &omap, &smap3, &xmapa, &xmapb};
#pragma unroll
            for (int i = 0; i < 4; i++) asm volatile("prefetch.tensormap [%0];\n" :: "l"(reinterpret_cast<uint64_t>(maps[i])) : "memory");
        }
        if (tid == 384) {
            for (int b = 0; b < 4; b++) {
                mbar_init(bars + B_XFULL + b * 8, 2);
                mbar_init(bars + B_QKRAW + b * 8, 4);
                mbar_init(bars + B_VRAW + b * 8, 4);
                mbar_init(bars + B_VFREE + b * 8, 2);
                mbar_init(bars + B_QKFREE + b * 8, 4);
                mbar_init(bars + B_ODONE + b * 8, 4);
            }
            mbar_init(bars + B_MFULL, 1);
            sts32(bars + B_MSTATE, 0);
            sts32(bars + B_MSTATE + 4, 0x7FFFFFFF);
            sts32(bars + B_NTILES, 0x7FFFFFFF);
            sts128(bars + B_DYN, ~0u, ~0u, ~0u, ~0u);
            sts128(bars + B_DYN + 16, ~0u, ~0u, ~0u, ~0u);
            mbar_init(bars + B_GDONE, 4);
            sts32(bars + B_ROWS, 0xFFFFFFFFu);
            mbar_init(bars + B_MCONS, 4);
            mbar_init(bars + B_WFULL, 2);
            mbar_init(bars + B_WRAW, 1);
            mbar_init(bars + B_XCONS, 4);
            for (int b = 0; b < 4; b++) mbar_init(bars + B_STORED + b * 8, 1);
            for (int b = 0; b < 6; b++) {
                mbar_init(sbase + SM_PBAR + b * 8, 1);
                if (PCHUNK) sts32(sbase + SM_PBAR + 48, 0); else
                mbar_init(sbase + SM_PBAR + 48 + b * 8, PSTORE ? 1 : 4);
                mbar_init(sbase + SM_PBAR + 104 + b * 8, 4);
            }
            mbar_init(sbase + SM_PBAR + 96, 13);
            mbar_init(sbase + SM_PBAR + 56, 12);
            asm volatile("fence.mbarrier_init.release.cluster;\n" ::: "memory");
        }
        if (wg == 3) {
            if (attn) *reinterpret_cast<uint4*>(smem + SM_V + warp * V_STRIDE + (lane < 16 ? lane * 16 : V_STRIDE - 64 + (lane & 3) * 16)) = make_uint4(0, 0, 0, 0);
            fence_async_smem();
        }
        __syncthreads();
        TR(26, 4 + wg);
            if (attn && tid == 0) {
                const int nw = 4;
                mbar_arrive_expect_tx(bars + B_WRAW, nw * 96 * O_PITCH);
                TR(26, 30);
#pragma unroll
                for (int i = 0; i < 4; i++) if (i < nw) {
                    const int q = (i + pair) & 3;
                    tma_3d(sbase + q * 96 * O_PITCH, &wraw, bars + B_WRAW, 0, 2 * (q >> 1) + half, (q & 1) * 96);
                    TR(26, 31 + i);
                }
                int wh = 0, ww = pair;
#pragma unroll
                for (int j = 0; j < NEARLY; j++) {
                    if (ww < NWS - 1) {
                        const uint32_t bar = bars + B_XFULL + (j ? j - 1 : 0) * 8;
                        if (j >= 2) mbar_arrive(bar);
                        mbar_arrive_expect_tx(bar, 3 * XCH);
#pragma unroll
                        for (int ch = 0; ch < 3; ch++)
                            tma_3d(sbase + SM_QK + ((j + 3) & 3) * XCH + ch * QK_CHUNK, &xmap, bar, ch * 64, 7 * ww + 3, 7 * wh + 3);
                    }
                    ww += P.npair; if (ww >= NWS) { ww -= NWS; wh++; }
                    TR(26, 40 + j);
                    if (j == 1) {
                        mbar_arrive_expect_tx(bars + B_MFULL, 4816);
                        asm volatile("cp.async.bulk.shared::cluster.global.mbarrier::complete_tx::bytes [%0], [%1], 4816, [%2];\n"
                                     :: "r"(sbase + SM_MASK), "l"(reinterpret_cast<const char*>(P.mask) + (((uint32_t)pair * 4802u) & ~15u)),
                                        "r"(bars + B_MFULL) : "memory");
                        mbar_arrive_expect_tx(bars + B_WFULL, 5 * W_ATOM);
#pragma unroll
                        for (int a = 1; a < 6; a++)
                            tma_2d(sbase + SM_WV + a * W_ATOM, &wmap, bars + B_WFULL, 384 + half * 96 + a * 16, 0);
                        TR(26, 50);
                    }
                }
            }
        __syncwarp();
        TR(26, 13);
    }

    auto permute_w = [&]() {
        uint4 w[3][4];
        TR(26, 16 + wg);
        mbar_wait(bars + B_WRAW, 0);
        TR(26, 20 + wg);
#pragma unroll
        for (int it = 0; it < 3; it++) {
            const int o = ((tid >> 5) * 3 + it) * 4 + (lane >> 3);
            const uint8_t* src = smem + ((o / 6) * 8 + (lane & 7)) * O_PITCH + (o % 6) * 16;
#pragma unroll
            for (int m = 0; m < 4; m++) w[it][m] = *reinterpret_cast<const uint4*>(src + (m >> 1) * 192 * O_PITCH + (m & 1) * 96);
        }
        asm volatile("bar.sync 2, 384;\n" ::: "memory");
        if (tid == 0) {
            fence_async_smem();
            TR(26, 24);
            mbar_arrive_expect_tx(bars + B_WFULL, W_ATOM);
            tma_2d(sbase + SM_WV, &wmap, bars + B_WFULL, 384 + half * 96, 0);
        }
#pragma unroll
        for (int it = 0; it < 3; it++) {
            const int o = ((tid >> 5) * 3 + it) * 4 + (lane >> 3);
            const uint32_t d = sbase + (o % 6) * 2 * W_ATOM + ((o / 6) * 8 + (lane & 7)) * 32 + ((lane >> 2) & 1) * 16;
            sts128(d, bf2h(w[it][0].x), bf2h(w[it][1].x), bf2h(w[it][2].x), bf2h(w[it][3].x));
            sts128(d ^ 16, bf2h(w[it][0].y), bf2h(w[it][1].y), bf2h(w[it][2].y), bf2h(w[it][3].y));
            sts128(d + W_ATOM, bf2h(w[it][0].z), bf2h(w[it][1].z), bf2h(w[it][2].z), bf2h(w[it][3].z));
            sts128((d ^ 16) + W_ATOM, bf2h(w[it][0].w), bf2h(w[it][1].w), bf2h(w[it][2].w), bf2h(w[it][3].w));
        }
    };
    static_assert(2 * 192 * O_PITCH <= 13 * W_ATOM, "raw weights");
    const uint32_t nfinish = gridDim.x + (POLLER ? 0 : 2 * P.npair);
#define PROJ_SCHEDULE                                                                                   \
    int bid = blockIdx.x;                                                                               \
    asm volatile("" : "+r"(bid));                      \
    bid = role_of(P, bid);                                                                              \
    const bool at = bid < 2 * P.npair;                                                                  \
    const int tile0 = at ? P.t1 + bid : bid - 2 * P.npair;                                              \
    const int tstep = at ? 2 * P.npair : (int)gridDim.x - 2 * P.npair;                                  \
    const int tend = at ? TILES : P.t1;
    if (wg == 3) {
        asm volatile("setmaxnreg.dec.sync.aligned.u32 %0;\n" :: "n"(REG_H));
        if (warp == 1 && attn) {
            const uint16_t mlast = reinterpret_cast<const uint16_t*>(P.mask)[NWINDOWS * TOK * TOK - 1];
            const uint32_t ma = sbase + SM_MASK + 16 + lane * 16, mb = sbase + SM_MASK + min(289 + lane, 299) * 16;
            const uint32_t mc = sbase + SM_MASK + (lane & 7) * 2 + (lane & 8) * 600;
            uint32_t ph = 0, win = pair;
#pragma unroll 1
            for (int k = 0;; k++) {
                mbar_wait(bars + B_MFULL, k & 1);
                uint32_t acc = lds16(mc);
                if ((lane & 15) - (win & 7) > 8u) acc = 0;
#pragma unroll
                for (int i = 0; i < 10; i += MRND) {
                    uint32_t w[MRND][4];
#pragma unroll
                    for (int j = 0; j < MRND; j++) if (i + j < 10) lds128(w[j], i + j < 9 ? ma + (i + j) * 512 : mb);
#pragma unroll
                    for (int j = 0; j < MRND; j++) if (i + j < 10) acc |= w[j][0] | w[j][1] | w[j][2] | w[j][3];
                    asm volatile("" : "+r"(acc) :: "memory");
                }
                const uint32_t nz = __any_sync(0xffffffffu, (acc & 0x7FFF7FFFu) != 0) ? 1 : 0;
                if (lane == 0) asm volatile("st.volatile.shared.b32 [%0], %1;\n" :: "r"(bars + B_MSTATE), "r"(32 * k + 32 - 16 * nz + (2 * win & 14)) : "memory");
                win += P.npair;
                if (k + 1 >= NSTATIC) {
                    uint32_t e = 0xFFFF;
#pragma unroll 1
                    for (uint32_t n = 0; n < (1u << 20); n++) {
                        e = lds16v(bars + B_DYN + (k + 1 - NSTATIC) * 2);
                        if (__all_sync(0xffffffffu, e != 0xFFFF)) break;
                        __nanosleep(RSLEEP);
                    }
                    if (__any_sync(0xffffffffu, e >= POS_END)) break;
                    win = e - (e >> 7) * (128 - NWS);
                }
                if (nz) { mbar_wait(bars + B_MCONS, ph); ph ^= 1; fence_async_smem(); }
                if (elect_one()) {
                    uint32_t bytes = 4816;
                    if (win == NWINDOWS - 1) {
                        bytes = 4800;
                        asm volatile("st.shared.u16 [%0], %1;\n" :: "r"(sbase + SM_MASK + 4800), "h"(mlast) : "memory");
                    }
                    TR(25, k + 1);
                    mbar_arrive_expect_tx(bars + B_MFULL, bytes);
                    asm volatile("cp.async.bulk.shared::cluster.global.mbarrier::complete_tx::bytes [%0], [%1], %2, [%3];\n"
                                 :: "r"(sbase + SM_MASK),
                                    "l"(reinterpret_cast<const char*>(P.mask) + (((uint32_t)win * 4802u) & ~15u)),
                                    "r"(bytes), "r"(bars + B_MFULL) : "memory");
                    if (MPF && half == (win & 1) && win + MPF * P.npair < NWINDOWS)
                        asm volatile("cp.async.bulk.prefetch.L2.global [%0], %1;\n"
                                     :: "l"(reinterpret_cast<const char*>(P.mask) + (((uint32_t)(win + MPF * P.npair) * 4802u) & ~15u)),
                                        "r"(4800) : "memory");
                }
                __syncwarp();
            }
        }
        if (!elect_one()) return;
        if (warp == 0) {
          if (attn) {
            int kmax = 1 << 20, rows = 1 << 30;
            uint32_t cur = pair, pos1 = pos_add(cur, P.npair), pos2 = pos_add(pos1, P.npair);
#pragma unroll 1
            for (int k = -4; k + 4 <= kmax; k++) {
                const int row0 = (k + 4) * TOK;
                const uint32_t dst = sbase + SM_QK + ((k + 3) & 3) * XCH, bar = bars + B_XFULL + ((row0 >> 6) & 3) * 8;
                const bool alone = (row0 & 63) >= 64 - TOK && (row0 & 63) < TOK;
                const int wh = cur >> 7, ww = cur & 127;
                uint32_t claim = NWINDOWS;
                if (k + 7 >= NSTATIC && k + 7 < NSTATIC + 15 && pos2 < POS_END)
                    asm volatile("atom.relaxed.gpu.global.add.u32 %0, [%1], 1;\n" : "=r"(claim) : "l"(g_next + half) : "memory");
                const int x0 = 7 * ww + 3, y0 = 7 * wh + 3;
                const bool done = k < NEARLY - 4 && ww < NWS - 1;
                if (k >= 0) mbar_wait(bars + B_QKFREE + ((k + 3) & 3) * 8, (k >> 2) & 1);
                if (alone && !done) mbar_arrive(bar);
                if (row0 >= rows || ((EXP & 32) && k >= 0)) {
                    mbar_arrive(bar);
                    continue;
                }
                TR(20, k + 4);
                const bool inner = wh < NWS - 1 && ww < NWS - 1;
                if (done) {
                } else if (XSPLIT && inner && (row0 & 63) >= 64 - 21) {
                    const uint32_t bar2 = bars + B_XFULL + (((row0 >> 6) + 1) & 3) * 8;
                    mbar_arrive_expect_tx(bar, 3 * 21 * 128);
#pragma unroll
                    for (int ch = 0; ch < 3; ch++) tma_3d(dst + ch * QK_CHUNK, &xmapa, bar, ch * 64, x0, y0);
                    asm volatile("mbarrier.expect_tx.relaxed.cta.shared::cta.b64 [%0], %1;\n" :: "r"(bar2), "r"(3 * 28 * 128) : "memory");
#pragma unroll
                    for (int ch = 0; ch < 3; ch++) tma_3d(dst + ch * QK_CHUNK + 21 * 128, &xmapb, bar2, ch * 64, x0, y0 + 3);
                } else if (inner) {
                    mbar_arrive_expect_tx(bar, 3 * XCH);
#pragma unroll
                    for (int ch = 0; ch < 3; ch++) tma_3d(dst + ch * QK_CHUNK, &xmap, bar, ch * 64, x0, y0);
                } else if (ww < NWS - 1) {
                    mbar_arrive_expect_tx(bar, 3 * XCH);
#pragma unroll
                    for (int ch = 0; ch < 3; ch++) {
                        tma_3d(dst + ch * QK_CHUNK, &xmapb, bar, ch * 64, x0, y0);
                        tma_3d(dst + ch * QK_CHUNK + 28 * 128, &xmapa, bar, ch * 64, x0, 0);
                    }
                } else {
                    mbar_arrive_expect_tx(bar, 3 * XCH);
                    const int x1 = (ww == NWS - 1) ? 0 : x0 + 4;
#pragma unroll 1
                    for (int i = 0; i < 7; i++) {
                        const int y = (y0 + i >= IMG) ? y0 + i - IMG : y0 + i;
#pragma unroll
                        for (int ch = 0; ch < 3; ch++) {
                            tma_3d(dst + ch * QK_CHUNK + i * 896, &xmap4, bar, ch * 64, x0, y);
                            tma_3d(dst + ch * QK_CHUNK + i * 896 + 512, &xmap3, bar, ch * 64, x1, y);
                        }
                    }
                }
                if (pos1 < POS_END) cur = pos1;
                pos1 = pos2;
                if (k + 7 < NSTATIC) {
                    pos2 = pos_add(pos2, P.npair);
                } else if (pos2 < POS_END) {
                    sts32(bars + B_NTILES + 4, claim);
                    const uint32_t w = lds32v(bars + B_NTILES + 4) + NSTATIC * P.npair;
                    pos2 = w < NWINDOWS ? w + __umulhi(w, 58835169u) * (128 - NWS) : POS_END;
                    sts16(bars + B_DYN + (k + 7 - NSTATIC) * 2, pos2);
                    if (pos2 == POS_END) {
                        rows = (row0 + 3 * TOK + 63) & ~63;
                        kmax = (rows + 63) / TOK;
                        sts32(bars + B_MSTATE + 4, k + 7);
                        sts32(bars + B_NTILES, rows >> 6);
                        if (role < SM_STAGE / 1024)
                            asm volatile("cp.async.bulk.prefetch.L2.global [%0], 1024;\n" :: "l"(g_wo + role * 1024) : "memory");
                    }
                }
                if (!NOPF && half == 0 && pos2 < POS_END) {
#pragma unroll
                    for (int ch = 0; ch < 3; ch++)
                        asm volatile("cp.async.bulk.prefetch.tensor.3d.L2.global.tile [%0, {%1, %2, %3}];\n"
                                     :: "l"(reinterpret_cast<uint64_t>(&xmap)), "r"(ch * 64), "r"(7 * (pos2 & 127) + 3), "r"(7 * (pos2 >> 7) + 3)
                                     : "memory");
                }
            }
            {
#pragma unroll 1
                for (uint32_t n = 0; n < (1u << 22); n++) {
                    uint32_t a, b;
                    asm volatile("ld.relaxed.gpu.global.u32 %0, [%1];\n" : "=r"(b) : "l"(g_guard) : "memory");
                    asm volatile("ld.acquire.gpu.global.u32 %0, [%1];\n" : "=r"(a) : "l"(g_guard + 3) : "memory");
                    if (a == (b | 255)) break;
                }
                asm volatile("fence.proxy.async.global;\n" ::: "memory");
                mbar_arrive_expect_tx(bars + B_WRAW, SM_STAGE);
                mbar_wait(bars + B_GDONE, 0);
#pragma unroll
                for (int i = 0; i < WOSPLIT; i++)
                    asm volatile("cp.async.bulk.shared::cluster.global.mbarrier::complete_tx::bytes [%0], [%1], %2, [%3];\n"
                                 :: "r"(sbase + SM_WO + i * (SM_STAGE / WOSPLIT)), "l"(g_wo + i * (SM_STAGE / WOSPLIT)),
                                    "n"(SM_STAGE / WOSPLIT), "r"(bars + B_WRAW) : "memory");
            }
            mbar_wait(sbase + SM_PBAR + 96, 0);
            ST(15);
            fence_async_smem();
          }
            PROJ_SCHEDULE
            int st = 0, ready = -1, want = -6 * PSM, freed = 0;
            uint32_t ph = 1;
#pragma unroll 1
            for (int t = tile0; t < tend; t += tstep) {
                const int p0 = (t < TILES_A) ? SEG_B + 64 * (t & PWRAP) : 64 * (t - TILES_A);
                const int w1 = (t < TILES_A) ? min((64 * t + 63) / (7 * IMG), NWS - 1) : NWS - 1;
#pragma unroll 1
                for (uint32_t n = 0; n < (1u << 24) && ready < w1; n++) ready = (int)lds32v(bars + B_ROWS);
#pragma unroll
                for (int ch = 0; ch < PSM; ch++) {
                    want++;
#pragma unroll 1
                    for (uint32_t n = 0; n < (1u << 22) && freed < want; n++) freed = (int)lds32v(sbase + SM_PBAR + 48);
                    if (ch == 0) mbar_arrive_expect_tx(sbase + SM_PBAR + st * 8, STAGE_BYTES);
                    tma_2d(sbase + SM_STAGE + st * STAGE_BYTES + ch * 8192, &omap, sbase + SM_PBAR + st * 8, ch * 64, p0);
                    if (ch == 0) {
#pragma unroll
                        for (int c2 = PSM; c2 < 3; c2++)
                            tma_2d(sbase + SM_STAGE + st * STAGE_BYTES + c2 * 8192, &omap, sbase + SM_PBAR + st * 8, c2 * 64, p0);
                    }
                }
                if (++st == 6) st = 0;
            }
            if (!POLLER) finish(nfinish);
        } else if (warp == 2 && (POLLER || attn)) {
            CK(0);
            uint32_t rows = 0, cur = attn ? pair : POS_END;
#pragma unroll 1
            for (int k = 0; cur < POS_END; k++) {
                const uint32_t wh = cur >> 7;
                mbar_wait(bars + B_STORED + (k & 1) * 8, (k >> 1) & 1);
                mbar_arrive(bars + B_PUBD + (k & 1) * 8);
                rows = rows * 128 + wh + 1;
                cur = k + 1 < NSTATIC ? pos_add(cur, P.npair) : lds16v(bars + B_DYN + (k + 1 - NSTATIC) * 2);
                if (rows >= (1u << (7 * PUBN - 7)) || k < 2 || cur >= (NWS - PUBT) * 128) {
                    asm volatile("fence.acq_rel.gpu;\n" ::: "memory");
#pragma unroll 1
                    for (; rows; rows >>= 7)
                        asm volatile("red.relaxed.gpu.global.add.u32 [%0], 1;\n" :: "l"(g_cnt + ((rows & 127) - 1)) : "memory");
                }
                TR(24, k);
                CK(k + 1);
                if (k == 30) { ST(9); SC(29); }
                if (k == 60) { ST(10); SC(30); }
                if (k == 90) { ST(11); SC(31); }
            }
            ST(14);
            const int r1 = attn ? NWS - 1 : min((64 * P.t1 - 1) / (7 * IMG), NWS - 1);
#pragma unroll 1
            for (int r = attn ? min(64 * P.t1 / (7 * IMG), NWS - 1) : 0; r <= r1; r++) {
#pragma unroll 1
                for (uint32_t n = 0; n < (1u << 22); n++) {
                    uint32_t a;
                    asm volatile("ld.acquire.gpu.global.u32 %0, [%1];\n" : "=r"(a) : "l"(g_cnt + r) : "memory");
                    if (a >= P.need) break;
                    __nanosleep(64);
                }
                asm volatile("fence.proxy.async.global;\n" ::: "memory");
                asm volatile("st.volatile.shared.b32 [%0], %1;\n" :: "r"(bars + B_ROWS), "r"(r) : "memory");
                if (r >= 66) ST(20 + r - 66);
            }
            finish(nfinish);
        } else if (warp == 3 && attn) {
            for (int t = 0; t < 3; t++) mbar_arrive_n(bars + B_VFREE + t * 8, 2);
            uint32_t cur = pair;
#pragma unroll 1
            for (int k = 0; cur < POS_END; k++) {
                const int wh = cur >> 7, ww = cur & 127;
                const uint32_t src = sbase + SM_V + (k & 3) * V_STRIDE;
                const int x0 = 7 * ww + 3, y0 = 7 * wh + 3;
                mbar_wait(bars + B_ODONE + (k & 3) * 8, (k >> 2) & 1);
                fence_async_smem();
                TR(22, k);
#if !(EXP & 4)
                tma_store_4d(&smap, src, 0, half, x0, y0);
                tma_store_4d(&smap3, src + 28 * O_PITCH + 64, 0, half, x0, wh == NWS - 1 ? 0 : y0 + 4);
#endif
                if (ww == NWS - 1) {
#pragma unroll 1
                    for (int i = 0; i < 7; i++) {
                        char* const d = reinterpret_cast<char*>(P.out) + (uint32_t)((y0 + i >= IMG ? y0 + i - IMG : y0 + i) * IMG) * 384u + half * 192;
#pragma unroll
                        for (int j = 0; j < 3; j++)
                            asm volatile("cp.async.bulk.global.shared::cta.bulk_group [%0], [%1], 192;\n"
                                         :: "l"(d + j * 384), "r"(src + (7 * i + 4 + j) * O_PITCH + (i >= 4 ? 64 : 0)) : "memory");
                    }
                }
                asm volatile("cp.async.bulk.commit_group;\n" ::: "memory");
                asm volatile("cp.async.bulk.wait_group.read 0;\n" ::: "memory");
                {
                    const int row0 = (k + 4) * TOK;
                    mbar_arrive_n(bars + B_VFREE + ((row0 >> 6) & 3) * 8, ((row0 & 63) >= 64 - TOK && (row0 & 63) < TOK) ? 2 : 1);
                }
                TR(23, k);
                cur = k + 1 < NSTATIC ? pos_add(cur, P.npair) : lds16v(bars + B_DYN + (k + 1 - NSTATIC) * 2);
                asm volatile("cp.async.bulk.wait_group 0;\n" ::: "memory");
                asm volatile("fence.proxy.async.global;\n" ::: "memory");
                mbar_wait(bars + B_PUBD + (k & 1) * 8, ((k >> 1) + 1) & 1);
                mbar_arrive(bars + B_STORED + (k & 1) * 8);
            }
            mbar_arrive(sbase + SM_PBAR + 96);
        }
        if (PSTORE && warp == 1) {
            PROJ_SCHEDULE
            int st = 0, prev = -1, done = 0;
            uint32_t ph = 0;
            if (bid == gridDim.x - 1) { g_guard[2] = 0; __threadfence(); }
#pragma unroll 1
            for (int t = tile0; t < tend; t += tstep) {
                const int p0 = (t < TILES_A) ? SEG_B + 64 * (t & PWRAP) : 64 * (t - TILES_A);
                mbar_wait(sbase + SM_PBAR + 104 + st * 8, ph);
                fence_async_smem();
                if (!at) TR(22, (t - tile0) / tstep);
                if (!at && done == 40 * PSM) ST(9);
                if (!at && done == 90 * PSM) ST(10);
                if (!at && done == 130 * PSM) ST(11);
                if (!at && done == 140 * PSM) ST(12);
#pragma unroll
                for (int ch = 0; ch < PSM; ch++) {
                    asm volatile("cp.async.bulk.tensor.2d.global.shared::cta.tile.bulk_group [%0, {%2, %3}], [%1];\n"
                                 :: "l"(reinterpret_cast<uint64_t>(t < TILES_A ? &omap : &omapb)),
                                    "r"(sbase + SM_STAGE + st * STAGE_BYTES + ch * 8192), "r"(ch * 64), "r"(p0) : "memory");
                    asm volatile("cp.async.bulk.commit_group;\n" ::: "memory");
                    asm volatile("cp.async.bulk.wait_group.read %0;\n" :: "n"(PCHUNK) : "memory");
                    asm volatile("st.volatile.shared.b32 [%0], %1;\n" :: "r"(sbase + SM_PBAR + 48), "r"(max(done + ch + 1 - PCHUNK, 0)) : "memory");
                }
                done += PSM;
                if (!mbar_test(sbase + SM_PBAR + 104 + (st == 5 ? 0 : st + 1) * 8, st == 5 ? ph ^ 1 : ph)) {
                    if (PCHUNK > 1) {
                        asm volatile("cp.async.bulk.wait_group.read 1;\n" ::: "memory");
                        asm volatile("st.volatile.shared.b32 [%0], %1;\n" :: "r"(sbase + SM_PBAR + 48), "r"(done - 1) : "memory");
                    }
                    asm volatile("cp.async.bulk.wait_group.read 0;\n" ::: "memory");
                    asm volatile("st.volatile.shared.b32 [%0], %1;\n" :: "r"(sbase + SM_PBAR + 48), "r"(done) : "memory");
                }
                prev = st;
                if (++st == 6) { st = 0; ph ^= 1; }
            }
            mbar_wait(sbase + SM_PBAR + 56, 0);
            asm volatile("fence.acq_rel.gpu;\n" ::: "memory");
            asm volatile("cp.async.bulk.wait_group 0;\n" ::: "memory");
            asm volatile("red.relaxed.gpu.global.add.u32 [%0], %1;\n" :: "l"(g_guard), "r"(bid == 0 ? 257 - gridDim.x : 1) : "memory");
            TR(30, 0);
            ST(13);
        }
        return;
    }
    bool bad = false;
    if (!attn) {
        asm volatile("setmaxnreg.inc.sync.aligned.u32 160;\n");
        uint32_t lo = 0x7F807F80u, hi = 0;
#pragma unroll 1
        for (int i = (role - 2 * P.npair) * 384 + tid; i < 192 * 96; i += (gridDim.x - 2 * P.npair) * 384) {
            const bool o = i >= 192 * 72;
            const uint4 w = o ? reinterpret_cast<const uint4*>(P.wo)[i - 192 * 72] : reinterpret_cast<const uint4*>(P.wqkv)[i];
            const uint32_t m = __vmaxu2(__vmaxu2(w.x & 0x7FFF7FFFu, w.y & 0x7FFF7FFFu), __vmaxu2(w.z & 0x7FFF7FFFu, w.w & 0x7FFF7FFFu));
            lo = __vminu2(lo, m);
            hi = __vmaxu2(hi, m + (o ? 0x02000200u : 0u));
        }
        bad = __vminu2(lo, 0x38803880u) != 0x38803880u || __vmaxu2(hi, 0x42004200u) != 0x42004200u;
    } else if (wg == 0) {
        asm volatile("setmaxnreg.inc.sync.aligned.u32 %0;\n" :: "n"(REG_G));
        float qs = 1.f;
        if (c < 2) qs = round_bf16(expf(round_bf16(fminf(fmaxf(__bfloat162float(P.logit_scale[2 * half + c]), -100.f), 4.6052f)))) * LOG2E;
        uint32_t xa[8][4];
        uint32_t qk[2][48], vv[24];
        uint32_t rho = warp * 16 + (lane & 15), rq = warp * 16 + g;
        uint32_t rx = rho + 3 * TOK - (rho >= TOK ? 4 * TOK : 0);
        uint32_t hi = lane >> 4, lane0 = lane == 0, c2 = 2 * c;
        asm volatile("" : "+r"(hi), "+r"(lane0), "+r"(c2));
        auto row_addr = [&](uint32_t (&ax)[4], uint32_t r) {
            ax[0] = sbase + SM_QK + r * 128 + (((r & 7) ^ hi) << 4);
#pragma unroll
            for (int i = 1; i < 4; i++) ax[i] = ax[0] ^ (32 * i);
        };
#define XADDR(ax, s) ((ax)[((s) & 3) ^ (((s) >> 1) & 2)] + ((s) >> 2) * QK_CHUNK)
        uint64_t descW = make_desc(sbase, W_ATOM, 256, 3);
        const uint32_t zero = (uint32_t)P.z1;
        const uint32_t vbase = sbase + SM_V + (lane >> 4) * GRP;
        uint32_t ones = 0x3C003C00u | zero, ones2 = ones | (zero >> 1);
        asm volatile("" : "+r"(ones), "+r"(ones2));
        const uint32_t mh[2] = {0xFFFF0000u, 0xFFFF0000u}, ml[2] = {0x10000u, 0x10000u};
        uint32_t raw[48], xb[4][4];
        auto cvt = [&](auto& dst, int d0, const uint32_t (&raw)[48], int s0) {
#pragma unroll
            for (int s = 0; s < 4; s++) {
#pragma unroll
                for (int i = 0; i < 4; i++)
                    dst[d0 + s][i] = pack_f16(__uint_as_float(raw[4 * (s0 + s) + i] * ml[i & 1]), __uint_as_float(raw[4 * (s0 + s) + i] & mh[i & 1]));
                reg_fence(dst[d0 + s]);
            }
        };
        uint32_t ax[4];
        auto load_x = [&](int s0) {
#pragma unroll
            for (int s = s0; s < s0 + 4; s++) ldsm_x4(reinterpret_cast<uint32_t (&)[4]>(raw[4 * s]), XADDR(ax, s));
        };
        auto next_x = [&]() {
            row_addr(ax, rx);
            rx += 64;
            if (rx >= 4 * TOK) rx -= 4 * TOK;
        };
        permute_w();
        TR(26, 10);
        mbar_wait(bars + B_XFULL, 0);
        next_x();
        load_x(0); load_x(4); load_x(8);
        cvt(xa, 0, raw, 0); cvt(xa, 4, raw, 4); cvt(xb, 0, raw, 8);
        __syncwarp();
        mbar_arrive_if(bars + B_QKFREE + 24, lane0);
        TR(26, 8);
        asm volatile("bar.sync 7, 384;\n" ::: "memory");
        fence_async_smem();
        TR(26, 9);
        wgmma_fence();
        mma_qk_first<SM_WA, 0>(qk[0], xa, descW);
        mma_qk_next<SM_WA + 2048, 4>(qk[0], xa, descW);
        mma_qk_next<SM_WA + 4096, 0>(qk[0], xb, descW);
        wgmma_commit();
        TR(26, 11);
        asm volatile("bar.sync 11, 384;\n" ::: "memory");
        fence_async_smem();
        TR(26, 12);
        wgmma_fence();
        mma_v_first<SM_WV, 0>(vv, xa, descW);
        mma_v_next<SM_WV + 2048, 4>(vv, xa, descW);
        wgmma_commit();
        wgmma_wait<0>();
        ST(1); SC(28);
        uint32_t xok = 0, range = 0;
        int ntiles;
        auto body = [&](auto U_, int t) {
            constexpr int U = decltype(U_)::value;
            uint32_t (&cur)[48] = qk[U];
            uint32_t (&nxt)[48] = qk[U ^ 1];
            descW += P.z1;
            const uint32_t bt = bars + (t & 3) * 8, pt = (t >> 2) & 1;
            TR(1, t);
            wgmma_fence();
            mma_v_next<SM_WV + 4096, 0>(vv, xb, descW);
            wgmma_commit();
            next_x();
            mbar_wait_unless(xok, bars + ((t + 1) & 3) * 8 + B_XFULL, ((t + 1) >> 2) & 1);
            TR(2, t);
            load_x(0);
            load_x(4);
            uint32_t av = vbase + rho * 16 + ((rho * 1338) >> 16) * (V_STRIDE - GRP);
            uint32_t aq[2];
            aq[0] = sbase + SM_QK + rq * 128 + (((rq & 7) ^ c2) << 4);
            aq[1] = aq[0] + 1024;
            if (rq >= 4 * TOK - 8) aq[1] = (aq[1] - QK_CHUNK) ^ 64;
            rho += 64;
            if (rho >= 4 * TOK) rho -= 4 * TOK;
            rq += 64;
            if (rq >= 4 * TOK) rq -= 4 * TOK;
            asm volatile("" : "+r"(av), "+r"(aq[0]), "+r"(aq[1]), "+r"(rho), "+r"(rq));
            cvt(xa, 0, raw, 0);
            wgmma_fence();
            mma_qk_first<SM_WA, 0>(nxt, xa, descW);
            wgmma_commit();
            load_x(8);
            __syncwarp();
            mbar_arrive_if(bars + B_XCONS, lane0);
            const uint32_t vok = mbar_test(bt + B_VFREE, pt);
            ntiles = lds32v(bars + B_NTILES);
            cvt(xa, 4, raw, 4);
            TR(5, t);
            wgmma_fence();
            mma_qk_next<SM_WA + 2048, 4>(nxt, xa, descW);
            wgmma_commit();
            wgmma_wait<2>();
            reg_fence(cur);
            reg_fence(vv);
            TR(6, t);
            mbar_wait_unless(vok, bt + B_VFREE, pt);
            if (U == 0 && t == 2) asm volatile("bar.sync 3, 384;\n" ::: "memory");
#pragma unroll
            for (int p = 0; p < 6; p++)
                stsm_x4(av + (p < 3 ? 2 * p : 2 * p + 1) * GRP, vv[4 * p], vv[4 * p + 1], vv[4 * p + 2], vv[4 * p + 3]);
            stsm_x2(av + 6 * GRP, ones, ones2);
            __syncwarp();
            mbar_arrive_if(bt + B_VRAW, lane0);
            const uint32_t cok = mbar_test(bars + B_XCONS, U);
            TR(4, t);
            cvt(xb, 0, raw, 8);
            uint32_t ss[4];
#pragma unroll
            for (int i = 0; i < 4; i++) ss[i] = hmul2_f16(cur[i], cur[i]);
#pragma unroll
            for (int i = 4; i < ((EXP & 16) ? 4 : 48); i++) ss[i & 3] = hfma2_f16(cur[i], cur[i], ss[i & 3]);
            ss[0] = hadd2_f16(ss[0], ss[2]);
            ss[1] = hadd2_f16(ss[1], ss[3]);
            const float s0 = f16lo(ss[0]) + f16hi(ss[0]) + 1e-12f, s1 = f16lo(ss[1]) + f16hi(ss[1]) + 1e-12f;
            range = __viaddmax_u32(__float_as_uint(s0), 0u - SS_MIN, __viaddmax_u32(__float_as_uint(s1), 0u - SS_MIN, range));
            const float f0 = rsqrt_ftz(s0) * qs, f1 = rsqrt_ftz(s1) * qs;
            uint32_t f2[2] = {pack_f16_sat(f0, f0), pack_f16_sat(f1, f1)};
            reg_fence(f2);
            sched_fence16(zero, xb, f2[0], f2[1]);
            wgmma_fence();
            mma_v_first<SM_WV, 0>(vv, xa, descW);
            wgmma_commit();
            mbar_wait_unless_dep(cok, bars + B_XCONS, U, zero, f2[0], f2[1], aq[0], aq[1]);
            TR(7, t);
#pragma unroll
            for (int u = 0; u < 6; u++)
#pragma unroll
                for (int r = 0; r < 2; r++)
                    sts128((aq[r] ^ ((u & 1) * 16 + (u & 2) * 32)) + (u >> 1) * QK_CHUNK,
                           hmul2_f16(cur[8 * u + r], f2[r]), hmul2_f16(cur[8 * u + 2 + r], f2[r]),
                           hmul2_f16(cur[8 * u + 4 + r], f2[r]), hmul2_f16(cur[8 * u + 6 + r], f2[r]));
            __syncwarp();
            mbar_arrive_if(bt + B_QKRAW, lane0);
            TR(3, t);
            wgmma_fence();
            mma_v_next<SM_WV + 2048, 4>(vv, xa, descW);
            wgmma_commit();
            xok = mbar_test(bars + ((t + 2) & 3) * 8 + B_XFULL, ((t + 2) >> 2) & 1);
            mma_qk_next<SM_WA + 4096, 0>(nxt, xb, descW);
            wgmma_commit();
            TR(0, t + 1);
            wgmma_wait<1>();
        };
        for (int t = 0;; t += 2) {
            body(std::integral_constant<int, 0>(), t);
            if (__any_sync(0xffffffffu, t + 1 >= ntiles)) { wgmma_wait<0>(); reg_fence(qk[1]); break; }
            body(std::integral_constant<int, 1>(), t + 1);
            if (__any_sync(0xffffffffu, t + 2 >= ntiles)) { wgmma_wait<0>(); reg_fence(qk[0]); break; }
        }
        reg_fence(vv);
        bad = range >= F32_INF - SS_MIN;
        __syncwarp();
        mbar_arrive_if(bars + B_GDONE, lane0);
        asm volatile("setmaxnreg.dec.sync.aligned.u32 160;\n");
    } else {
        if (REG_A > 128) asm volatile("setmaxnreg.inc.sync.aligned.u32 %0;\n" :: "n"(REG_A));
        if (REG_A < 128) asm volatile("setmaxnreg.dec.sync.aligned.u32 %0;\n" :: "n"(REG_A));
        {
            const float c0 = bf16lo(rc), c1 = bf16hi(rc);
            float a0 = 0.f, a1 = 0.f;
#pragma unroll
            for (int u = 0; u < 16; u++) {
                const uint32_t p = reinterpret_cast<const uint32_t*>(w1)[u >> 1], q = reinterpret_cast<const uint32_t*>(w1)[8 + (u >> 1)];
                float h = round_bf16(c0 * ((u & 1) ? bf16hi(p) : bf16lo(p)) + c1 * ((u & 1) ? bf16hi(q) : bf16lo(q)));
                h = fmaxf(h, 0.f);
                a0 += h * bf16lo(w2[u]);
                a1 += h * bf16hi(w2[u]);
            }
            const float s0 = round_bf16(__fdividef(1.f, 1.f + expf(-round_bf16(a0))));
            const float s1 = round_bf16(__fdividef(1.f, 1.f + expf(-round_bf16(a1))));
            if (tid - 128 < 169) sts32(sbase + SM_TAB + (tid - 128) * 4, pack_f16(16.f * LOG2E * s0, 16.f * LOG2E * s1));
        }
        permute_w();
        asm volatile("bar.arrive 7, 384;\n" ::: "memory");
        {
            mbar_wait(bars + B_WFULL, 0);
#pragma unroll 1
            for (int i = 0; i < 9 - 9 * T_NOWV; i++) {
                uint4* q = reinterpret_cast<uint4*>(smem + SM_WV + (tid - 128) * 16 + i * 4096);
                const uint4 w = *q;
                *q = make_uint4(bf2h(w.x), bf2h(w.y), bf2h(w.z), bf2h(w.w));
            }
            asm volatile("bar.arrive 11, 384;\n" ::: "memory");
        }
        asm volatile("bar.sync 1, 256;\n" ::: "memory");
        uint32_t bias[28];
        {
            const uint32_t* tab = reinterpret_cast<const uint32_t*>(smem + SM_TAB);
#pragma unroll
            for (int rh = 0; rh < 2; rh++) {
#pragma unroll
                for (int j = 0; j < 6; j++) {
                    const uint32_t lo = tab[min(max(ridx[13 * rh + 2 * j], 0), 168)];
                    const uint32_t hi = tab[min(max(ridx[13 * rh + 2 * j + 1], 0), 168)];
                    bias[2 * j + rh]      = prmt(lo, hi, 0x5410);
                    bias[14 + 2 * j + rh] = prmt(lo, hi, 0x7632);
                }
                const uint32_t l = (c == 0) ? tab[min(max(ridx[13 * rh + 12], 0), 168)] : 0xFC00FC00u;
                bias[12 + rh] = (l & 0xFFFFu) | 0xFC000000u;
                bias[26 + rh] = (l >> 16) | 0xFC000000u;
            }
        }
        reg_fence(bias);
        asm volatile("bar.arrive 3, 384;\n" ::: "memory");
        const bool ov = warp * 16 + (lane & 15) < TOK;
        const int orow = warp * 16 + (lane & 15);
        const uint32_t orel = sbase + (ov ? SM_V + orow * O_PITCH + (orow >= 28 ? 64 : 0) : SM_DUMP + (lane & 7) * 16) + (lane >> 4) * 16;
        const uint32_t omul = ov ? V_STRIDE : 0;
        const uint64_t descK0 = make_desc(sbase + SM_QK, 16, 1024, 1);
        const uint64_t descV0 = make_desc(sbase + SM_V, 128, GRP, 0);
        const uint32_t mrel = sbase + SM_MASK + t0 * 98 + c * 4;
        const uint32_t mrow = (warp < 3) ? 784 : 0;
        const uint32_t pmask = (c == 0) ? 0xFFFFu : 0u;

        uint32_t mstate = 0;
        int nwin;
        const uint32_t barw = bars + (wg - 1) * 8;
        const uint64_t descKw = descK0 + (uint64_t)((wg - 1) * (XCH >> 4)), descVw = descV0 + (uint64_t)((wg - 1) * (V_STRIDE >> 4));
        uint32_t oa = orel + (wg - 1) * omul;
        const uint32_t oflip = oa ^ (oa + 2 * omul);
        uint32_t qok = 0;
        const uint32_t zero = (uint32_t)P.z1;
        auto window = [&](auto IT_, int k) {
            constexpr int IT = decltype(IT_)::value;
            const uint32_t bar = barw + 16 * IT;
            const int tl = (k * TOK + TOK - 1) >> 6, tn = ((k + 2) * TOK + TOK - 1) >> 6;
            const uint32_t bt = bars + (tl & 3) * 8, pt = (tl >> 2) & 1;
            TR(8, k);
            uint32_t sc0[14], sc1[14];
#pragma unroll
            for (int i = 0; i < 14; i++) { sc0[i] = bias[i]; sc1[i] = bias[14 + i]; }
            if (mstate < 32 * k + 32) {
#pragma unroll 1
                for (uint32_t n = 0; n < (1u << 22) && mstate < 32 * k + 16; n++) mstate = lds32v(bars + B_MSTATE);
                if (mstate < 32 * k + 32) {
                    mbar_wait(bars + B_MFULL, k & 1);
                    const uint32_t ma = mrel + (mstate & 14);
#pragma unroll
                    for (int i = 0; i < 14; i++) {
                        const uint32_t lo = lds16(ma + (i & 1) * mrow + (i >> 1) * 16);
                        const uint32_t hi = i < 12 ? lds16(ma + (i & 1) * mrow + (i >> 1) * 16 + 2) : 0u;
                        const uint32_t mk = pack_f16(__uint_as_float(lo << 16), __uint_as_float(hi << 16));
                        sc0[i] = hfma2_f16(mk, 0x3DC53DC5u, sc0[i]);
                        sc1[i] = hfma2_f16(mk, 0x3DC53DC5u, sc1[i]);
                    }
                    __syncwarp();
                    if (lane == 0) mbar_arrive(bars + B_MCONS);
                }
            }
            reg_fence(sc0);
            reg_fence(sc1);
            TR(10, k);
            mbar_wait_unless(qok, bt + B_QKRAW, pt);
            fence_async_smem();
            TR(11, k);
            wgmma_fence();
#if !(EXP & 128)
            mma_s0_f16<2 * IT * XCH, 2 * IT * XCH>(sc0, descKw, descKw);
            mma_s1_f16<2 * IT * XCH, 2 * IT * XCH>(sc1, descKw, descKw);
#endif
            wgmma_commit();
            const uint32_t vok = mbar_test(bt + B_VRAW, pt);
            uint32_t m[2];
            auto rowmax = [&](const uint32_t (&S)[14], int h) {
                uint32_t a[2];
#pragma unroll
                for (int o = 0; o < 2; o++)
                    a[o] = hmax2_f16(hmax2_f16(hmax2_f16(hmax2_f16(S[o], S[2 + o]), S[4 + o]), hmax2_f16(hmax2_f16(S[6 + o], S[8 + o]), S[10 + o])), S[12 + o]);
                m[h] = hmax2_f16(prmt(a[0], a[1], 0x5410), prmt(a[0], a[1], 0x7632));
            };
            wgmma_wait<0>();
            reg_fence(sc0);
            reg_fence(sc1);
            if (lane == 0) mbar_arrive(bar + B_QKFREE);
            TR(12, k);
            rowmax(sc0, 0);
            rowmax(sc1, 1);
#pragma unroll
            for (int i = 0; i < 2; i++) m[i] = hmax2_f16(m[i], __shfl_xor_sync(0xffffffffu, m[i], 1));
#pragma unroll
            for (int i = 0; i < 2; i++) m[i] = hmax2_f16(m[i], __shfl_xor_sync(0xffffffffu, m[i], 2));
            auto probs = [&](const uint32_t (&S)[14], uint32_t mm, uint32_t (&pa)[4][4]) {
#pragma unroll
                for (int j = 0; j < 6; j++) {
                    pa[j >> 1][(j & 1) * 2]     = ex2_f16x2(hsub2_bc<0>(S[2 * j], mm));
                    pa[j >> 1][(j & 1) * 2 + 1] = ex2_f16x2(hsub2_bc<1>(S[2 * j + 1], mm));
                }
                pa[3][0] = ex2_f16lo(hsub2_bc<0>(S[12], mm)) & pmask;
                pa[3][1] = ex2_f16lo(hsub2_bc<1>(S[13], mm)) & pmask;
                pa[3][2] = 0u; pa[3][3] = 0u;
                reg_fence(pa);
            };
            uint32_t pa0[4][4], pa1[4][4];
            uint32_t o0[14], o1[14];
            TR(13, k);
            mbar_wait_unless(vok, bt + B_VRAW, pt);
            fence_async_smem();
            TR(14, k);
            probs(sc0, m[0], pa0);
            wgmma_fence();
            mma_pv<2 * IT * V_STRIDE, 0>(o0, pa0, descVw);
            wgmma_commit();
            probs(sc1, m[1], pa1);
            wgmma_fence();
            mma_pv<2 * IT * V_STRIDE + 6 * GRP, 0>(o1, pa1, descVw);
            wgmma_commit();
            uint32_t w[24];
            wgmma_wait<1>();
            reg_fence(o0);
            {
                const float il0 = rcp_ftz(f16lo(o0[12])), il1 = rcp_ftz(f16lo(o0[13]));
                const uint32_t l0 = pack_f16(il0, il0), l1 = pack_f16(il1, il1);
#pragma unroll
                for (int j = 0; j < 12; j++) w[j] = hmul2_f16(o0[j], (j & 1) ? l1 : l0);
            }
            wgmma_wait<0>();
            reg_fence(o1);
            TR(15, k);
            asm volatile("{\n.reg .pred p;\nsetp.eq.u32 p, %0, 1;\n@p bar.sync 4, 128;\n@!p bar.sync 5, 128;\n}\n"
                         :: "r"(wg) : "memory");
            qok = mbar_test(bars + (tn & 3) * 8 + B_QKRAW, (tn >> 2) & 1);
            asm volatile("ld.volatile.shared.v2.b32 {%0, %1}, [%2];\n" : "=r"(mstate), "=r"(nwin) : "r"(bars + B_MSTATE) : "memory");
            {
                const float il2 = rcp_ftz(f16lo(o1[0])), il3 = rcp_ftz(f16lo(o1[1]));
                const uint32_t l2 = pack_f16(il2, il2), l3 = pack_f16(il3, il3);
#pragma unroll
                for (int j = 0; j < 12; j++) w[12 + j] = hmul2_f16(o1[j + 2], (j & 1) ? l3 : l2);
#pragma unroll
                for (int p = 0; p < 6; p++) stsm_x4(oa + p * 32, w[4 * p], w[4 * p + 1], w[4 * p + 2], w[4 * p + 3]);
            }
            __syncwarp();
            if (lane == 0) mbar_arrive(bar + B_ODONE);
            TR(16, k);
            oa ^= oflip;
            asm volatile("" : "+r"(oa));
        };
        for (int k = wg - 1;; k += 4) {
            window(std::integral_constant<int, 0>(), k);
            if (__any_sync(0xffffffffu, k + 2 >= nwin)) break;
            window(std::integral_constant<int, 1>(), k + 2);
            if (__any_sync(0xffffffffu, k + 4 >= nwin)) break;
        }
        (void)zero;
        asm volatile("setmaxnreg.inc.sync.aligned.u32 160;\n");
    }

    TR(27, wg);
    ST(2 + wg);
    uint32_t tag, seen;
    asm volatile("ld.relaxed.gpu.global.v2.u32 {%0, %1}, [%2];\n" : "=r"(tag), "=r"(seen) : "l"(g_guard) : "memory");
    if (attn) {
        __syncwarp();
        if (lane == 0) mbar_arrive(sbase + SM_PBAR + 96);
    }
    if (!attn) {
#pragma unroll
        for (int row = tid >> 2; row < 192; row += 96) {
            uint4 w[6];
#pragma unroll
            for (int a = 0; a < 6; a++) w[a] = *reinterpret_cast<const uint4*>(P.wo + row * 192 + 32 * a + 8 * c);
            float s = 0.f;
#pragma unroll
            for (int a = 0; a < 6; a++)
                s += ((bf16lo(w[a].x) + bf16hi(w[a].x)) + (bf16lo(w[a].y) + bf16hi(w[a].y))) +
                     ((bf16lo(w[a].z) + bf16hi(w[a].z)) + (bf16lo(w[a].w) + bf16hi(w[a].w)));
            s += __shfl_xor_sync(0xffffffffu, s, 1);
            s += __shfl_xor_sync(0xffffffffu, s, 2);
            s *= (1.f / 192.f);
            const uint32_t sw = (row >> 1) & 3;
            const uint32_t d = sbase + SM_WO + row * 64 + ((c ^ sw) << 4), e = sbase + SM_WO + row * 64 + c * 4;
#pragma unroll
            for (int a = 0; a < 6; a++) {
                const uint32_t h[4] = {pack_f16(bf16lo(w[a].x) - s, bf16hi(w[a].x) - s), pack_f16(bf16lo(w[a].y) - s, bf16hi(w[a].y) - s),
                                       pack_f16(bf16lo(w[a].z) - s, bf16hi(w[a].z) - s), pack_f16(bf16lo(w[a].w) - s, bf16hi(w[a].w) - s)};
                if (a < 2 * PSM) {
                    sts128(d + a * 12288, h[0], h[1], h[2], h[3]);
                } else {
#pragma unroll
                    for (int i = 0; i < 4; i++) sts32(e + a * 12288 + ((i ^ sw) << 4), h[i]);
                }
            }
        }
        fence_async_smem();
        asm volatile("bar.sync 6, 384;\n" ::: "memory");
        if (role == 2 * P.npair && tid == 0) {
            asm volatile("cp.async.bulk.global.shared::cta.bulk_group [%0], [%1], %2;\n"
                         :: "l"(g_wo), "r"(sbase + SM_WO), "n"(SM_STAGE) : "memory");
            asm volatile("cp.async.bulk.commit_group;\n" ::: "memory");
            asm volatile("cp.async.bulk.wait_group 0;\n" ::: "memory");
            asm volatile("fence.proxy.async.global;\n" ::: "memory");
            asm volatile("st.release.gpu.global.u32 [%0], %1;\n" :: "l"(g_guard + 3), "r"(tag | 255) : "memory");
        }
        __syncwarp();
    } else {
        mbar_wait(bars + B_WRAW, 1);
    }
    tag |= 255;
    if (bad) g_guard[1] = tag;
    bad |= seen == tag;
    TR(27, 4 + wg);
    if (wg == 0) ST(5);
    {
        PROJ_SCHEDULE
        uint64_t descW = make_desc(sbase + SM_WO, 12288, 512, 2);
        const uint64_t descA = make_desc(sbase + SM_STAGE + wg * STAGE_BYTES, 16, 1024, 1);
        const uint32_t bar = sbase + SM_PBAR + wg * 8;
        const uint32_t yrel = sbase + SM_STAGE + wg * STAGE_BYTES + (warp * 16 + (lane & 15)) * 128 + (((lane & 7) ^ (lane >> 4)) << 4);
        float acc[96];
#pragma unroll
        for (int i = 0; i < 96; i++) acc[i] = 0.f;
        uint32_t it = 0;
        for (int tile = tile0 + wg * tstep; tile < tend; tile += 3 * tstep, it++) {
            descW += P.z1;
            mbar_wait(bar + (it & 1) * 24, (it >> 1) & 1);
            TR(28, it * 3 + wg);
            ST(6 + wg);
            if (it > 0 || wg > 0) asm volatile("bar.sync %0, 256;\n" :: "r"(8 + wg) : "memory");
            wgmma_fence();
            mma_proj<0, 0>(acc, descA + (uint64_t)((it & 1) * (3 * STAGE_BYTES >> 4)), descW);
            wgmma_commit();
            if (tile + tstep < tend) asm volatile("bar.arrive %0, 256;\n" :: "r"(wg == 2 ? 8 : 9 + wg) : "memory");
            wgmma_wait<0>();
            reg_fence(acc);
            TR(18, it * 3 + wg);
            float a[4];
#pragma unroll
            for (int i = 0; i < 4; i++) a[i] = acc[i] * acc[i];
#pragma unroll
            for (int j = 1; j < 24; j++)
#pragma unroll
                for (int i = 0; i < 4; i++) a[i] = fmaf(acc[4 * j + i], acc[4 * j + i], a[i]);
            float s0 = a[0] + a[1], s1 = a[2] + a[3];
            s0 += __shfl_xor_sync(0xffffffffu, s0, 1);
            s1 += __shfl_xor_sync(0xffffffffu, s1, 1);
            s0 += __shfl_xor_sync(0xffffffffu, s0, 2);
            s1 += __shfl_xor_sync(0xffffffffu, s1, 2);
            if (max(__float_as_uint(s0) - VAR_MIN, __float_as_uint(s1) - VAR_MIN) >= F32_INF - VAR_MIN) {
                const int rem = ((tile < TILES_A) ? NPIX - SEG_B - 64 * tile : SEG_B - 64 * (tile - TILES_A)) - warp * 16 - g;
                if ((__float_as_uint(s0) - VAR_MIN >= F32_INF - VAR_MIN && rem > 0) ||
                    (__float_as_uint(s1) - VAR_MIN >= F32_INF - VAR_MIN && rem > 8)) {
                    bad = true;
                    g_guard[1] = tag;
                }
            }
            const float rs0 = rsqrt_ftz(fmaf(s0, 1.f / 192.f, 1e-5f));
            const float rs1 = rsqrt_ftz(fmaf(s1, 1.f / 192.f, 1e-5f));
            const uint32_t ya = yrel + (it & 1) * 3 * STAGE_BYTES;
            auto direct = [&]() {
                const int p0 = (tile < TILES_A) ? SEG_B + 64 * (tile & PWRAP) : 64 * (tile - TILES_A);
                const int lim = ((tile < TILES_A) ? NPIX : SEG_B) - p0;
                char* const po = reinterpret_cast<char*>(P.out) + (uint32_t)((p0 + warp * 16 + g) * 384 + c * 16);
                const bool v0 = warp * 16 + g < lim, v1 = warp * 16 + g + 8 < lim;
#pragma unroll
                for (int i = 2 * PSM; i < 6; i++) {
                    const int j = 16 * i;
                    stg128_if(v0, po + 64 * i, pack_bf16(acc[j] * rs0, acc[j + 1] * rs0), pack_bf16(acc[j + 4] * rs0, acc[j + 5] * rs0),
                              pack_bf16(acc[j + 8] * rs0, acc[j + 9] * rs0), pack_bf16(acc[j + 12] * rs0, acc[j + 13] * rs0));
                    stg128_if(v1, po + 8 * 384 + 64 * i, pack_bf16(acc[j + 2] * rs1, acc[j + 3] * rs1),
                              pack_bf16(acc[j + 6] * rs1, acc[j + 7] * rs1), pack_bf16(acc[j + 10] * rs1, acc[j + 11] * rs1),
                              pack_bf16(acc[j + 14] * rs1, acc[j + 15] * rs1));
                }
            };
            if (PSM < 3 && PDF) direct();
#pragma unroll
            for (int p = 0; p < 4 * PSM; p++)
                stsm_x4((ya ^ (32 * (p & 3))) + (p >> 2) * 8192,
                        pack_bf16(acc[8 * p] * rs0, acc[8 * p + 1] * rs0), pack_bf16(acc[8 * p + 2] * rs1, acc[8 * p + 3] * rs1),
                        pack_bf16(acc[8 * p + 4] * rs0, acc[8 * p + 5] * rs0), pack_bf16(acc[8 * p + 6] * rs1, acc[8 * p + 7] * rs1));
            __syncwarp();
            if (lane == 0) mbar_arrive(bar + 104 + (it & 1) * 24);
            if (PSM < 3 && !PDF) direct();
            TR(29, it * 3 + wg);
            ST(16 + wg);
        }
        __syncwarp();
        if (lane == 0) mbar_arrive(sbase + SM_PBAR + 56);
    }

    {
        uint32_t any;
        asm volatile("{\n.reg .pred p, q;\nsetp.ne.u32 q, %1, 0;\nbarrier.cta.red.or.pred.aligned p, %2, 128, q;\nselp.u32 %0, 1, 0, p;\n}\n"
                     : "=r"(any) : "r"((uint32_t)bad), "r"(12 + wg) : "memory");
        if (!any) return;
    }
    redo(P, smem + wg * FB_BYTES, tag, 12 + wg);
}

}

typedef CUresult (*PFN_encodeTiled)(CUtensorMap*, CUtensorMapDataType, cuuint32_t, void*, const cuuint64_t*,
                                    const cuuint64_t*, const cuuint32_t*, const cuuint32_t*, CUtensorMapInterleave,
                                    CUtensorMapSwizzle, CUtensorMapL2promotion, CUtensorMapFloatOOBfill);

extern "C" void kernel_launch(void* const* d_in, const int* in_sizes, int n_in, void* d_out, int out_size) {
    swin::Params P;
    P.x           = (const __nv_bfloat16*)d_in[0];
    P.wqkv        = (const __nv_bfloat16*)d_in[1];
    P.wo          = (const __nv_bfloat16*)d_in[2];
    P.logit_scale = (const __nv_bfloat16*)d_in[3];
    P.cpb_w1      = (const __nv_bfloat16*)d_in[4];
    P.cpb_w2      = (const __nv_bfloat16*)d_in[5];
    P.rel_coords  = (const __nv_bfloat16*)d_in[6];
    P.rel_idx     = (const int*)d_in[7];
    P.mask        = (const __nv_bfloat16*)d_in[8];
    P.out         = (__nv_bfloat16*)d_out;
    P.z1 = 0;
    static PFN_encodeTiled encode = nullptr;
    if (!encode) {
        cudaFuncSetAttribute(swin::swin_window_attn_kernel, cudaFuncAttributeMaxDynamicSharedMemorySize, swin::SM_TOTAL);
        cudaDriverEntryPointQueryResult qr;
        cudaGetDriverEntryPoint("cuTensorMapEncodeTiled", (void**)&encode, cudaEnableDefault, &qr);
    }
    CUtensorMap xmap, xmap4, xmap3, omap, wmap, smap, omapb, xmapa, xmapb, smap3, wraw;
    const cuuint32_t estr[4] = {1, 1, 1, 1};
    auto make = [&](CUtensorMap* m, const void* base, int rank, const cuuint64_t* gdim, const cuuint64_t* gstr,
                    const cuuint32_t* box, CUtensorMapSwizzle swz = CU_TENSOR_MAP_SWIZZLE_128B) {
        CUresult r = encode(m, CU_TENSOR_MAP_DATA_TYPE_BFLOAT16, rank, const_cast<void*>(base), gdim, gstr, box, estr,
               CU_TENSOR_MAP_INTERLEAVE_NONE, swz, CU_TENSOR_MAP_L2_PROMOTION_L2_128B,
               CU_TENSOR_MAP_FLOAT_OOB_FILL_NONE);
        (void)r;
    };
    {
        const cuuint64_t gdim[3] = {192, swin::IMG, swin::IMG}, gstr[2] = {384, swin::IMG * 384};
        const cuuint32_t box[3] = {64, 7, 7}, box4[3] = {64, 4, 1}, box3[3] = {64, 3, 1};
        make(&xmap, P.x, 3, gdim, gstr, box);
        make(&xmap4, P.x, 3, gdim, gstr, box4);
        make(&xmap3, P.x, 3, gdim, gstr, box3);
        const cuuint32_t boxa[3] = {64, 7, 3}, boxb[3] = {64, 7, 4};
        make(&xmapa, P.x, 3, gdim, gstr, boxa);
        make(&xmapb, P.x, 3, gdim, gstr, boxb);
    }
    {
        const cuuint64_t gdim[2] = {192, (cuuint64_t)swin::NPIX}, gstr[1] = {384};
        const cuuint32_t box64[2] = {64, 64};
        make(&omap, d_out, 2, gdim, gstr, box64);
        const cuuint64_t gdimb[2] = {192, (cuuint64_t)swin::SEG_B};
        make(&omapb, d_out, 2, gdimb, gstr, box64);
    }
    {
        const cuuint64_t gdim[2] = {576, 192}, gstr[1] = {1152};
        const cuuint32_t box[2] = {16, 192};
        make(&wmap, P.wqkv, 2, gdim, gstr, box, CU_TENSOR_MAP_SWIZZLE_32B);
        const cuuint64_t gdim3[3] = {96, 6, 192}, gstr3[2] = {192, 1152};
        const cuuint32_t box3[3] = {104, 1, 96};
        make(&wraw, P.wqkv, 3, gdim3, gstr3, box3, CU_TENSOR_MAP_SWIZZLE_NONE);
    }
    {
        const cuuint64_t gdim[4] = {96, 2, swin::IMG, swin::IMG}, gstr[3] = {192, 384, swin::IMG * 384};
        const cuuint32_t box4[4] = {104, 1, 7, 4}, box3[4] = {104, 1, 7, 3};
        make(&smap, d_out, 4, gdim, gstr, box4, CU_TENSOR_MAP_SWIZZLE_NONE);
        make(&smap3, d_out, 4, gdim, gstr, box3, CU_TENSOR_MAP_SWIZZLE_NONE);
    }
    P.npair = NPAIR; P.need = swin::ROW_DONE;
    P.t1 = swin::TILES - NTAIL;
    P.spread = ((132 - 2 * NPAIR) * 65536 + 131) / 132;
    swin::swin_window_attn_kernel<<<132, swin::NTHREADS, swin::SM_TOTAL>>>(P, xmap, xmap4, xmap3, omap, wmap, smap, omapb, xmapa, xmapb, smap3, wraw);
}
```

```cpp
#include <cuda_runtime.h>
#include <cuda.h>
#include <cuda_bf16.h>
#include <stdint.h>
#include <type_traits>

namespace swin {

#define NPAIR 53
#define QFP32 0
#define PF_DIST 3
#define EXP 0
#define QSPLIT 3
#define SSPLIT 0
#define LATEMASK 0
#define CLUSTER 0
#define NOPF 0
#define NTAIL 340
#define PSTORE 1
#define PORDER 1
#define GORD 0
#define GMERGE 0
#define XSPLIT 1
#define EARLYW 1
#define NEARLY 4
#define W1 1
#define W2 2
#define W3 2
#define T_ONEBUF 0
#define T_NOWV 0
#define MPF 3
#define MRND 5
#define PX_L 3
#define PX_S 3
#define PX_W 0
#define PCHUNK 1
#define SPREAD 2
#define PSM 2
#define PDF 0
#define PWRAP -1
#define POLLER 1
#define PUBN 2
#define PUBT 4
#define NSTATIC 92
#define RSLEEP 800
#define AROLL 0
#define WOSPLIT 4
#define PADZ 1
#define MPRE 10
#define MEND 60
#define HOUT 1
#define HX 0
#define HM 0
#define OONE 1
#define VSTR 10256
#define MALIGN 128
#define MBUFS 3
#define HINT 0
#define HINT_A ""
#define HINT_B ""
#define REG_G 232
#define REG_A 120
#define REG_H 32
constexpr int IMG      = 511;
constexpr int NWS      = 73;
constexpr int NWINDOWS = NWS * NWS;
constexpr int TOK      = 49;
constexpr int NPIX     = IMG * IMG;
constexpr int NTHREADS = 512;

constexpr int W_ATOM = 6144;
constexpr int SM_WA = 0, SM_WB = 6 * W_ATOM, SM_WV = 12 * W_ATOM;
constexpr int GRP   = TOK * 16;
constexpr int XCH   = TOK * 128;
constexpr int SM_V  = 18 * W_ATOM, V_STRIDE = VSTR, O_STRIDE = 10240, O_PITCH = 208;
constexpr int SM_QK = SM_V + 4 * O_STRIDE, QK_CHUNK = 4 * XCH;
constexpr int SM_MASK = SM_QK + 3 * QK_CHUNK;
constexpr int SM_TAB  = SM_V + 3 * V_STRIDE + 256;
constexpr int SM_DUMP = SM_MASK + 4816;
constexpr int SM_BAR  = SM_DUMP + 320;
constexpr int B_XFULL = 0, B_WRAW = 32, B_XCONS = 40, B_NTILES = 48, B_GDONE = 56, B_DYN = 192, B_ROWS = 384, B_QKRAW = 64, B_QKFREE = 96, B_VFREE = 128, B_ODONE = 160,
              B_VRAW = 224, B_MFULL = 256, B_MSTATE = 264, B_MCONS = 272, B_WFULL = 280, B_STORED = 288, B_PUBD = 304;
constexpr int SM_A_END = SM_BAR + 320;
static_assert(SM_QK % 1024 == 0 && TOK * O_PITCH + 64 - 16 <= O_STRIDE && (28 * O_PITCH + 64) % 128 == 0, "layout");
static_assert(3 * V_STRIDE + 13 * GRP <= 4 * O_STRIDE && V_STRIDE >= O_STRIDE && SM_DUMP % 128 == 80, "layout");
constexpr int SM_WO    = 0;
constexpr int SM_STAGE = 73728;
constexpr int STAGE_BYTES = 24576;
constexpr int SM_MBAR  = SM_STAGE + 6 * STAGE_BYTES, M_BUF = 4992;
constexpr int SM_PBAR  = SM_A_END;
constexpr int SM_TOTAL = SM_PBAR + 152;
static_assert(SM_STAGE + 6 * STAGE_BYTES <= SM_BAR, "smem");
static_assert(SM_TOTAL <= 232448, "smem");
static_assert(SM_BAR % 8 == 0, "barrier alignment");

constexpr int SEG_B   = 3 * IMG;
constexpr int TILES_A = (NPIX - SEG_B + 63) / 64;
constexpr int TILES   = TILES_A + (SEG_B + 63) / 64;
constexpr uint32_t ROW_DONE = NWS * 2;

__device__ uint32_t g_cnt[NWS + 7];
__device__ __align__(128) uint8_t g_wo[SM_STAGE];
__device__ uint32_t g_mz[64 * 128];
__device__ uint32_t g_next[2];
__device__ uint32_t g_done;
__device__ __align__(16) uint32_t g_guard[4];
constexpr uint32_t F32_INF = 0x7F800000u;
constexpr uint32_t SS_MIN  = 0x3B800000u;
constexpr uint32_t VAR_MIN = 0x3D400000u;

#define TR(ev, idx)
#define ST(i)
#define SC(i)
#define CK(k)
constexpr uint64_t EVICT_FIRST = 0x12F0000000000000ull;
constexpr float LOG2E = 1.4426950408889634f;

__device__ __forceinline__ uint32_t smem_u32(const void* p) {
    return (uint32_t)__cvta_generic_to_shared(p);
}
__device__ __forceinline__ uint64_t make_desc(uint32_t saddr, uint32_t lbo, uint32_t sbo, uint32_t swz = 0) {
    return (uint64_t)((saddr & 0x3FFFF) >> 4) | ((uint64_t)(lbo >> 4) << 16) | ((uint64_t)(sbo >> 4) << 32) |
           ((uint64_t)swz << 62);
}
__host__ __device__ constexpr uint64_t make_desc_c(uint32_t saddr, uint32_t lbo, uint32_t sbo, uint32_t swz) {
    return (uint64_t)(saddr >> 4) | ((uint64_t)(lbo >> 4) << 16) | ((uint64_t)(sbo >> 4) << 32) | ((uint64_t)swz << 62);
}
__device__ __forceinline__ void wgmma_fence()  { asm volatile("wgmma.fence.sync.aligned;\n" ::: "memory"); }
__device__ __forceinline__ void wgmma_commit() { asm volatile("wgmma.commit_group.sync.aligned;\n" ::: "memory"); }
template <int N> __device__ __forceinline__ void wgmma_wait() {
    asm volatile("wgmma.wait_group.sync.aligned %0;\n" :: "n"(N) : "memory");
}
__device__ __forceinline__ void fence_async_smem() { asm volatile("fence.proxy.async.shared::cta;\n" ::: "memory"); }
__device__ __forceinline__ void wg_bar(int id) { asm volatile("bar.sync %0, 128;\n" :: "r"(id) : "memory"); }

template <int N> __device__ __forceinline__ void reg_fence(float (&v)[N]) {
#pragma unroll
    for (int i = 0; i < N; i++) asm volatile("" : "+f"(v[i]) :: "memory");
}
template <int N> __device__ __forceinline__ void reg_fence(uint32_t (&v)[N]) {
#pragma unroll
    for (int i = 0; i < N; i++) asm volatile("" : "+r"(v[i]) :: "memory");
}
template <int N, int M> __device__ __forceinline__ void reg_fence(uint32_t (&v)[N][M]) {
#pragma unroll
    for (int i = 0; i < N; i++) reg_fence(v[i]);
}

__device__ __forceinline__ uint32_t pack_bf16(float lo, float hi) {
    uint32_t r;
    asm("cvt.rn.bf16x2.f32 %0, %1, %2;\n" : "=r"(r) : "f"(hi), "f"(lo));
    return r;
}
__device__ __forceinline__ uint32_t pack_f16(float lo, float hi) {
    uint32_t r;
    asm("cvt.rn.f16x2.f32 %0, %1, %2;\n" : "=r"(r) : "f"(hi), "f"(lo));
    return r;
}
__device__ __forceinline__ uint32_t pack_f16_sat(float lo, float hi) {
    uint32_t r;
    asm("cvt.rn.satfinite.f16x2.f32 %0, %1, %2;\n" : "=r"(r) : "f"(hi), "f"(lo));
    return r;
}
__device__ __forceinline__ uint32_t hmul2_f16(uint32_t a, uint32_t b) {
    uint32_t r;
    asm("mul.rn.f16x2 %0, %1, %2;\n" : "=r"(r) : "r"(a), "r"(b));
    return r;
}
__device__ __forceinline__ uint32_t hadd2_f16(uint32_t a, uint32_t b) {
    uint32_t r;
    asm("add.rn.f16x2 %0, %1, %2;\n" : "=r"(r) : "r"(a), "r"(b));
    return r;
}
__device__ __forceinline__ uint32_t hfma2_f16(uint32_t a, uint32_t b, uint32_t c) {
    uint32_t r;
    asm("fma.rn.f16x2 %0, %1, %2, %3;\n" : "=r"(r) : "r"(a), "r"(b), "r"(c));
    return r;
}
__device__ __forceinline__ uint32_t hmax2_f16(uint32_t a, uint32_t b) {
    uint32_t r;
    asm("max.f16x2 %0, %1, %2;\n" : "=r"(r) : "r"(a), "r"(b));
    return r;
}
template <int H> __device__ __forceinline__ uint32_t hsub2_bc(uint32_t a, uint32_t b) {
    uint32_t r;
    if (H == 0) asm("{\n.reg .b16 l, h;\n.reg .b32 t;\nmov.b32 {l, h}, %2;\nmov.b32 t, {l, l};\nsub.rn.f16x2 %0, %1, t;\n}\n" : "=r"(r) : "r"(a), "r"(b));
    else        asm("{\n.reg .b16 l, h;\n.reg .b32 t;\nmov.b32 {l, h}, %2;\nmov.b32 t, {h, h};\nsub.rn.f16x2 %0, %1, t;\n}\n" : "=r"(r) : "r"(a), "r"(b));
    return r;
}
__device__ __forceinline__ uint32_t ex2_f16x2(uint32_t a) {
    uint32_t r;
    asm("ex2.approx.f16x2 %0, %1;\n" : "=r"(r) : "r"(a));
    return r;
}
__device__ __forceinline__ uint32_t ex2_f16lo(uint32_t a) {
    uint32_t r;
    asm("{\n.reg .b16 l, h;\nmov.b32 {l, h}, %1;\nex2.approx.f16 l, l;\nmov.b32 %0, {l, h};\n}\n" : "=r"(r) : "r"(a));
    return r;
}
__device__ __forceinline__ uint32_t lds16(uint32_t addr) {
    uint32_t v;
    asm volatile("ld.shared.u16 %0, [%1];\n" : "=r"(v) : "r"(addr) : "memory");
    return v;
}
__device__ __forceinline__ uint32_t lds16v(uint32_t addr) {
    uint32_t v;
    asm volatile("ld.volatile.shared.u16 %0, [%1];\n" : "=r"(v) : "r"(addr) : "memory");
    return v;
}
__device__ __forceinline__ void sts16(uint32_t addr, uint32_t v) {
    asm volatile("st.volatile.shared.u16 [%0], %1;\n" :: "r"(addr), "r"(v) : "memory");
}
__device__ __forceinline__ float f16lo(uint32_t v) {
    float r;
    asm("{\n.reg .b16 l, h;\nmov.b32 {l, h}, %1;\ncvt.f32.f16 %0, l;\n}\n" : "=f"(r) : "r"(v));
    return r;
}
__device__ __forceinline__ float f16hi(uint32_t v) {
    float r;
    asm("{\n.reg .b16 l, h;\nmov.b32 {l, h}, %1;\ncvt.f32.f16 %0, h;\n}\n" : "=f"(r) : "r"(v));
    return r;
}
__device__ __forceinline__ uint32_t bf2h(uint32_t v) {
    return pack_f16(__uint_as_float(v << 16), __uint_as_float(v & 0xFFFF0000u));
}
__device__ __forceinline__ float bf16lo(uint32_t v) { return __uint_as_float(v << 16); }
__device__ __forceinline__ float bf16hi(uint32_t v) { return __uint_as_float(v & 0xFFFF0000u); }
__device__ __forceinline__ uint32_t hadd2_bf16(uint32_t a, uint32_t b) {
    uint32_t r;
    asm("add.rn.bf16x2 %0, %1, %2;\n" : "=r"(r) : "r"(a), "r"(b));
    return r;
}
__device__ __forceinline__ uint32_t hmul2_bf16(uint32_t a, uint32_t b) {
    uint32_t r;
    asm("mul.rn.bf16x2 %0, %1, %2;\n" : "=r"(r) : "r"(a), "r"(b));
    return r;
}
__device__ __forceinline__ uint32_t hsub2_bf16(uint32_t a, uint32_t b) {
    uint32_t r;
    asm("sub.rn.bf16x2 %0, %1, %2;\n" : "=r"(r) : "r"(a), "r"(b));
    return r;
}
__device__ __forceinline__ uint32_t hfma2_bf16(uint32_t a, uint32_t b, uint32_t c) {
    uint32_t r;
    asm("fma.rn.bf16x2 %0, %1, %2, %3;\n" : "=r"(r) : "r"(a), "r"(b), "r"(c));
    return r;
}
__device__ __forceinline__ uint32_t hmax2_bf16(uint32_t a, uint32_t b) {
    uint32_t r;
    asm("max.bf16x2 %0, %1, %2;\n" : "=r"(r) : "r"(a), "r"(b));
    return r;
}
__device__ __forceinline__ uint32_t ex2_bf16x2(uint32_t a) {
    uint32_t r;
    asm("ex2.approx.ftz.bf16x2 %0, %1;\n" : "=r"(r) : "r"(a));
    return r;
}
__device__ __forceinline__ uint32_t ex2_bf16lo(uint32_t a) {
    uint32_t r;
    asm("{\n.reg .b16 l, h;\nmov.b32 {l, h}, %1;\nex2.approx.ftz.bf16 l, l;\ncvt.u32.u16 %0, l;\n}\n" : "=r"(r) : "r"(a));
    return r;
}
__device__ __forceinline__ uint32_t mbar_test(uint32_t bar, uint32_t parity) {
    uint32_t ok;
    asm volatile("{\n.reg .pred p;\nmbarrier.test_wait.parity.shared::cta.b64 p, [%1], %2;\nselp.u32 %0, 1, 0, p;\n}\n"
                 : "=r"(ok) : "r"(bar), "r"(parity) : "memory");
    return ok;
}
__device__ __forceinline__ uint32_t prmt(uint32_t a, uint32_t b, uint32_t sel) {
    uint32_t r;
    asm("prmt.b32 %0, %1, %2, %3;\n" : "=r"(r) : "r"(a), "r"(b), "r"(sel));
    return r;
}
__device__ __forceinline__ float round_bf16(float x) { return __bfloat162float(__float2bfloat16_rn(x)); }

__device__ __forceinline__ void mbar_init(uint32_t bar, uint32_t count) {
    asm volatile("mbarrier.init.shared::cta.b64 [%0], %1;\n" :: "r"(bar), "r"(count) : "memory");
}
__device__ __forceinline__ void mbar_wait(uint32_t bar, uint32_t parity) {
    asm volatile(
        "{\n"
        ".reg .pred p;\n"
        ".reg .u32 n;\n"
        "mov.u32 n, 0;\n"
        "WAIT_%=:\n"
        "mbarrier.try_wait.parity.shared::cta.b64 p, [%0], %1" HINT_A ";\n"
        "@p bra DONE_%=;\n"
        "add.u32 n, n, 1;\n"
        "setp.lt.u32 p, n, 4194304;\n"
        "@p bra WAIT_%=;\n"
        "exit;\n"
        "DONE_%=:\n"
        "}\n" :: "r"(bar), "r"(parity) : "memory");
}
__device__ __forceinline__ void mbar_wait4(uint32_t b0, uint32_t p0, uint32_t b1, uint32_t p1, uint32_t b2, uint32_t p2,
                                           uint32_t b3, uint32_t p3) {
    asm volatile(
        "{\n"
        ".reg .pred p, q, r, s;\n"
        ".reg .u32 n;\n"
        "mov.u32 n, 0;\n"
        "WAIT_%=:\n"
        "mbarrier.try_wait.parity.shared::cta.b64 p, [%0], %1;\n"
        "mbarrier.try_wait.parity.shared::cta.b64 q, [%2], %3;\n"
        "mbarrier.try_wait.parity.shared::cta.b64 r, [%4], %5;\n"
        "mbarrier.try_wait.parity.shared::cta.b64 s, [%6], %7;\n"
        "and.pred p, p, q;\n"
        "and.pred r, r, s;\n"
        "and.pred p, p, r;\n"
        "@p bra DONE_%=;\n"
        "add.u32 n, n, 1;\n"
        "setp.lt.u32 p, n, 4194304;\n"
        "@p bra WAIT_%=;\n"
        "exit;\n"
        "DONE_%=:\n"
        "}\n" :: "r"(b0), "r"(p0), "r"(b1), "r"(p1), "r"(b2), "r"(p2), "r"(b3), "r"(p3) : "memory");
}
__device__ __forceinline__ void mbar_wait2(uint32_t b0, uint32_t p0, uint32_t b1, uint32_t p1) {
    asm volatile(
        "{\n"
        ".reg .pred p, q;\n"
        ".reg .u32 n;\n"
        "mov.u32 n, 0;\n"
        "WAIT_%=:\n"
        "mbarrier.try_wait.parity.shared::cta.b64 p, [%0], %1;\n"
        "mbarrier.try_wait.parity.shared::cta.b64 q, [%2], %3;\n"
        "and.pred p, p, q;\n"
        "@p bra DONE_%=;\n"
        "add.u32 n, n, 1;\n"
        "setp.lt.u32 p, n, 4194304;\n"
        "@p bra WAIT_%=;\n"
        "exit;\n"
        "DONE_%=:\n"
        "}\n" :: "r"(b0), "r"(p0), "r"(b1), "r"(p1) : "memory");
}
__device__ __forceinline__ void mbar_wait_unless(uint32_t ok, uint32_t bar, uint32_t parity) {
    asm volatile(
        "{\n"
        ".reg .pred p;\n"
        ".reg .u32 n;\n"
        "setp.ne.u32 p, %2, 0;\n"
        "vote.sync.all.pred p, p, 0xffffffff;\n"
        "@p bra DONE_%=;\n"
        "mov.u32 n, 0;\n"
        "WAIT_%=:\n"
        "mbarrier.try_wait.parity.shared::cta.b64 p, [%0], %1" HINT_B ";\n"
        "@p bra DONE_%=;\n"
        "add.u32 n, n, 1;\n"
        "setp.lt.u32 p, n, 4194304;\n"
        "@p bra WAIT_%=;\n"
        "exit;\n"
        "DONE_%=:\n"
        "}\n" :: "r"(bar), "r"(parity), "r"(ok) : "memory");
}
__device__ __forceinline__ void mbar_wait_unless_dep(uint32_t ok, uint32_t bar, uint32_t parity, uint32_t zero, uint32_t& a,
                                                     uint32_t& b, uint32_t& c, uint32_t& d) {
    asm volatile(
        "{\n"
        ".reg .pred p;\n"
        ".reg .u32 n;\n"
        "setp.ne.u32 p, %6, 0;\n"
        "vote.sync.all.pred p, p, 0xffffffff;\n"
        "@p bra DONE_%=;\n"
        "mov.u32 n, 0;\n"
        "WAIT_%=:\n"
        "setp.ne.u32 p, %7, 0;\n"
        "@p ld.shared.v4.b32 {%0, %1, %2, %3}, [%7];\n"
        "mbarrier.try_wait.parity.shared::cta.b64 p, [%4], %5;\n"
        "@p bra DONE_%=;\n"
        "add.u32 n, n, 1;\n"
        "setp.lt.u32 p, n, 4194304;\n"
        "@p bra WAIT_%=;\n"
        "exit;\n"
        "DONE_%=:\n"
        "}\n" : "+r"(a), "+r"(b), "+r"(c), "+r"(d) : "r"(bar), "r"(parity), "r"(ok), "r"(zero) : "memory");
}
__device__ __forceinline__ void mbar_wait2_unless(uint32_t ok, uint32_t b0, uint32_t p0, uint32_t b1, uint32_t p1) {
    asm volatile(
        "{\n"
        ".reg .pred p, q;\n"
        ".reg .u32 n;\n"
        "setp.ne.u32 p, %4, 0;\n"
        "vote.sync.all.pred p, p, 0xffffffff;\n"
        "@p bra DONE_%=;\n"
        "mov.u32 n, 0;\n"
        "WAIT_%=:\n"
        "mbarrier.try_wait.parity.shared::cta.b64 p, [%0], %1" HINT_B ";\n"
        "mbarrier.try_wait.parity.shared::cta.b64 q, [%2], %3" HINT_B ";\n"
        "and.pred p, p, q;\n"
        "@p bra DONE_%=;\n"
        "add.u32 n, n, 1;\n"
        "setp.lt.u32 p, n, 4194304;\n"
        "@p bra WAIT_%=;\n"
        "exit;\n"
        "DONE_%=:\n"
        "}\n" :: "r"(b0), "r"(p0), "r"(b1), "r"(p1), "r"(ok) : "memory");
}
__device__ __forceinline__ void mbar_wait4_unless(uint32_t ok, uint32_t b0, uint32_t p0, uint32_t b1, uint32_t p1, uint32_t b2,
                                                  uint32_t p2, uint32_t b3, uint32_t p3) {
    asm volatile(
        "{\n"
        ".reg .pred p, q, r, s;\n"
        ".reg .u32 n;\n"
        "setp.ne.u32 p, %8, 0;\n"
        "vote.sync.all.pred p, p, 0xffffffff;\n"
        "@p bra DONE_%=;\n"
        "mov.u32 n, 0;\n"
        "WAIT_%=:\n"
        "mbarrier.try_wait.parity.shared::cta.b64 p, [%0], %1;\n"
        "mbarrier.try_wait.parity.shared::cta.b64 q, [%2], %3;\n"
        "mbarrier.try_wait.parity.shared::cta.b64 r, [%4], %5;\n"
        "mbarrier.try_wait.parity.shared::cta.b64 s, [%6], %7;\n"
        "and.pred p, p, q;\n"
        "and.pred r, r, s;\n"
        "and.pred p, p, r;\n"
        "@p bra DONE_%=;\n"
        "add.u32 n, n, 1;\n"
        "setp.lt.u32 p, n, 4194304;\n"
        "@p bra WAIT_%=;\n"
        "exit;\n"
        "DONE_%=:\n"
        "}\n" :: "r"(b0), "r"(p0), "r"(b1), "r"(p1), "r"(b2), "r"(p2), "r"(b3), "r"(p3), "r"(ok) : "memory");
}
__device__ __forceinline__ void sched_fence(uint32_t zero, uint32_t a, uint32_t b, uint32_t c, uint32_t d, uint32_t e = 0,
                                            uint32_t f = 0, uint32_t g = 0, uint32_t h = 0, uint32_t i = 0, uint32_t j = 0,
                                            uint32_t k = 0) {
    asm volatile("{\n.reg .pred p;\n.reg .u32 n;\nsetp.eq.u32 p, %0, 0;\n@p bra.uni DONE_%=;\nmov.u32 n, %0;\nSPIN_%=:\n"
                 "nanosleep.u32 %1;\nnanosleep.u32 %2;\nnanosleep.u32 %3;\nnanosleep.u32 %4;\nnanosleep.u32 %5;\n"
                 "nanosleep.u32 %6;\nnanosleep.u32 %7;\nnanosleep.u32 %8;\nnanosleep.u32 %9;\nnanosleep.u32 %10;\n"
                 "nanosleep.u32 %11;\nsub.u32 n, n, 1;\nsetp.ne.u32 p, n, 0;\n@p bra.uni SPIN_%=;\nDONE_%=:\n}\n"
                 :: "r"(zero), "r"(a), "r"(b), "r"(c), "r"(d), "r"(e), "r"(f), "r"(g), "r"(h), "r"(i), "r"(j), "r"(k) : "memory");
}
__device__ __forceinline__ void sched_fence16(uint32_t zero, const uint32_t (&v)[4][4], uint32_t a = 0, uint32_t b = 0) {
    asm volatile("{\n.reg .pred p;\n.reg .u32 n;\nsetp.eq.u32 p, %0, 0;\n@p bra.uni DONE_%=;\nmov.u32 n, %0;\nSPIN_%=:\n"
                 "nanosleep.u32 %17;\nnanosleep.u32 %18;\n"
                 "st.shared.v4.b32 [n], {%1, %2, %3, %4};\nst.shared.v4.b32 [n + 16], {%5, %6, %7, %8};\n"
                 "st.shared.v4.b32 [n + 32], {%9, %10, %11, %12};\nst.shared.v4.b32 [n + 48], {%13, %14, %15, %16};\n"
                 "sub.u32 n, n, 1;\nsetp.ne.u32 p, n, 0;\n@p bra.uni SPIN_%=;\nDONE_%=:\n}\n"
                 :: "r"(zero), "r"(v[0][0]), "r"(v[0][1]), "r"(v[0][2]), "r"(v[0][3]), "r"(v[1][0]), "r"(v[1][1]), "r"(v[1][2]), "r"(v[1][3]),
                    "r"(v[2][0]), "r"(v[2][1]), "r"(v[2][2]), "r"(v[2][3]), "r"(v[3][0]), "r"(v[3][1]), "r"(v[3][2]), "r"(v[3][3]),
                    "r"(a), "r"(b) : "memory");
}
__device__ __forceinline__ void sched_dep(uint32_t zero, uint32_t& a, uint32_t& b, uint32_t& c, uint32_t& d) {
    asm volatile("{\n.reg .pred p;\n.reg .u32 n;\nsetp.eq.u32 p, %4, 0;\n@p bra.uni DONE_%=;\nmov.u32 n, %4;\nSPIN_%=:\n"
                 "ld.shared.v4.b32 {%0, %1, %2, %3}, [n];\n"
                 "sub.u32 n, n, 1;\nsetp.ne.u32 p, n, 0;\n@p bra.uni SPIN_%=;\nDONE_%=:\n}\n"
                 : "+r"(a), "+r"(b), "+r"(c), "+r"(d) : "r"(zero) : "memory");
}
__device__ __forceinline__ void mbar_arrive(uint32_t bar) {
    asm volatile("mbarrier.arrive.shared::cta.b64 _, [%0];\n" :: "r"(bar) : "memory");
}
__device__ __forceinline__ void mbar_arrive_n(uint32_t bar, uint32_t n) {
    asm volatile("mbarrier.arrive.shared::cta.b64 _, [%0], %1;\n" :: "r"(bar), "r"(n) : "memory");
}
__device__ __forceinline__ void mbar_arrive_expect_tx(uint32_t bar, uint32_t bytes) {
    asm volatile("mbarrier.arrive.expect_tx.shared::cta.b64 _, [%0], %1;\n" :: "r"(bar), "r"(bytes) : "memory");
}
__device__ __forceinline__ void stg128_if(bool p, void* addr, uint32_t x, uint32_t y, uint32_t z, uint32_t w) {
    asm volatile("{\n.reg .pred q;\nsetp.ne.b32 q, %5, 0;\n@q st.global.L1::no_allocate.L2::cache_hint.v4.b32 [%0], {%1, %2, %3, %4}, %6;\n}\n"
                 :: "l"(addr), "r"(x), "r"(y), "r"(z), "r"(w), "r"((uint32_t)p), "l"(EVICT_FIRST) : "memory");
}
__device__ __forceinline__ void stsm_x4(uint32_t addr, uint32_t r0, uint32_t r1, uint32_t r2, uint32_t r3) {
    asm volatile("stmatrix.sync.aligned.m8n8.x4.shared.b16 [%0], {%1, %2, %3, %4};\n"
                 :: "r"(addr), "r"(r0), "r"(r1), "r"(r2), "r"(r3) : "memory");
}
__device__ __forceinline__ void stsm_x4_if(bool p, uint32_t addr, uint32_t r0, uint32_t r1, uint32_t r2, uint32_t r3) {
    asm volatile("{\n.reg .pred q;\nsetp.ne.b32 q, %5, 0;\n@q stmatrix.sync.aligned.m8n8.x4.shared.b16 [%0], {%1, %2, %3, %4};\n}\n"
                 :: "r"(addr), "r"(r0), "r"(r1), "r"(r2), "r"(r3), "r"((uint32_t)p) : "memory");
}
__device__ __forceinline__ void stsm_x2(uint32_t addr, uint32_t r0, uint32_t r1) {
    asm volatile("stmatrix.sync.aligned.m8n8.x2.shared.b16 [%0], {%1, %2};\n" :: "r"(addr), "r"(r0), "r"(r1) : "memory");
}
__device__ __forceinline__ void sts128(uint32_t addr, uint32_t r0, uint32_t r1, uint32_t r2, uint32_t r3) {
    asm volatile("st.shared.v4.b32 [%0], {%1, %2, %3, %4};\n" :: "r"(addr), "r"(r0), "r"(r1), "r"(r2), "r"(r3) : "memory");
}
__device__ __forceinline__ void sts32(uint32_t addr, uint32_t v) {
    asm volatile("st.shared.b32 [%0], %1;\n" :: "r"(addr), "r"(v) : "memory");
}
__device__ __forceinline__ uint32_t lds32(uint32_t addr) {
    uint32_t v;
    asm volatile("ld.shared.b32 %0, [%1];\n" : "=r"(v) : "r"(addr) : "memory");
    return v;
}
__device__ __forceinline__ void lds128(uint32_t (&r)[4], uint32_t addr) {
    asm volatile("ld.shared.v4.b32 {%0, %1, %2, %3}, [%4];\n" : "=r"(r[0]), "=r"(r[1]), "=r"(r[2]), "=r"(r[3]) : "r"(addr) : "memory");
}
__device__ __forceinline__ uint32_t lds32v(uint32_t addr) {
    uint32_t v;
    asm volatile("ld.volatile.shared.b32 %0, [%1];\n" : "=r"(v) : "r"(addr) : "memory");
    return v;
}
__device__ __forceinline__ void ldg_nc_v4(uint32_t (&r)[4], const void* p) {
    asm volatile("ld.global.nc.L1::no_allocate.v4.u32 {%0, %1, %2, %3}, [%4];\n"
                 : "=r"(r[0]), "=r"(r[1]), "=r"(r[2]), "=r"(r[3]) : "l"(p));
}
__device__ __forceinline__ uint32_t ldg_u32(const void* p) {
    uint32_t v;
    asm volatile("ld.global.nc.L1::evict_first.u32 %0, [%1];\n" : "=r"(v) : "l"(p));
    return v;
}
__device__ __forceinline__ void ldg_u64(const void* p, uint32_t& a, uint32_t& b) {
    asm volatile("ld.global.nc.L1::evict_first.v2.u32 {%0, %1}, [%2];\n" : "=r"(a), "=r"(b) : "l"(p));
}
__device__ __forceinline__ void prefetch_l2(const void* p) {
    asm volatile("prefetch.global.L2 [%0];\n" :: "l"(p));
}
__device__ __forceinline__ void cp_async16(uint32_t dst, const void* src) {
    asm volatile("cp.async.cg.shared.global [%0], [%1], 16;\n" :: "r"(dst), "l"(src) : "memory");
}
__device__ __forceinline__ float ex2_ftz(float x) {
    float y;
    asm("ex2.approx.ftz.f32 %0, %1;\n" : "=f"(y) : "f"(x));
    return y;
}
__device__ __forceinline__ float rcp_ftz(float x) {
    float y;
    asm("rcp.approx.ftz.f32 %0, %1;\n" : "=f"(y) : "f"(x));
    return y;
}
__device__ __forceinline__ float rsqrt_ftz(float x) {
    float y;
    asm("rsqrt.approx.ftz.f32 %0, %1;\n" : "=f"(y) : "f"(x));
    return y;
}

__device__ __forceinline__ bool elect_one() {
    uint32_t p;
    asm volatile("{\n.reg .pred q;\nelect.sync _|q, 0xffffffff;\nselp.u32 %0, 1, 0, q;\n}\n" : "=r"(p));
    return p != 0;
}
__device__ __forceinline__ void ldsm_x4(uint32_t (&r)[4], uint32_t addr) {
    asm volatile("ldmatrix.sync.aligned.m8n8.x4.shared.b16 {%0, %1, %2, %3}, [%4];\n"
                 : "=r"(r[0]), "=r"(r[1]), "=r"(r[2]), "=r"(r[3]) : "r"(addr) : "memory");
}
__device__ __forceinline__ void ldsm_x2(uint32_t& r0, uint32_t& r1, uint32_t addr) {
    asm volatile("ldmatrix.sync.aligned.m8n8.x2.shared.b16 {%0, %1}, [%2];\n" : "=r"(r0), "=r"(r1) : "r"(addr) : "memory");
}
__device__ __forceinline__ void tma_2d(uint32_t dst, const CUtensorMap* map, uint32_t bar, int c0, int c1) {
    asm volatile("cp.async.bulk.tensor.2d.shared::cluster.global.mbarrier::complete_tx::bytes [%0], [%1, {%3, %4}], [%2];\n"
                 :: "r"(dst), "l"(reinterpret_cast<uint64_t>(map)), "r"(bar), "r"(c0), "r"(c1) : "memory");
}
__device__ __forceinline__ void tma_3d(uint32_t dst, const CUtensorMap* map, uint32_t bar, int c0, int c1, int c2) {
    asm volatile("cp.async.bulk.tensor.3d.shared::cluster.global.mbarrier::complete_tx::bytes [%0], [%1, {%3, %4, %5}], [%2];\n"
                 :: "r"(dst), "l"(reinterpret_cast<uint64_t>(map)), "r"(bar), "r"(c0), "r"(c1), "r"(c2) : "memory");
}
__device__ __forceinline__ void tma_store_4d(const CUtensorMap* map, uint32_t src, int c0, int c1, int c2, int c3) {
    asm volatile("cp.async.bulk.tensor.4d.global.shared::cta.tile.bulk_group [%0, {%2, %3, %4, %5}], [%1];\n"
                 :: "l"(reinterpret_cast<uint64_t>(map)), "r"(src), "r"(c0), "r"(c1), "r"(c2), "r"(c3) : "memory");
}
__device__ __forceinline__ void mbar_arrive_if(uint32_t bar, uint32_t cnt) {
    asm volatile("{\n.reg .pred q;\nsetp.ne.b32 q, %1, 0;\n@q mbarrier.arrive.shared::cta.b64 _, [%0], %1;\n}\n"
                 :: "r"(bar), "r"(cnt) : "memory");
}

template <int BOFF, int AOFF, int NA>
__device__ __forceinline__ void mma_qk_first(uint32_t (&d)[48], const uint32_t (&a)[NA][4], uint64_t descB) {
    asm volatile(
        "{\n"
        ".reg .pred p0, p1;\n"
        ".reg .b64 ta, ta0, tb, tb0;\n"
        "setp.ne.b32 p0, 0, 0;\n"
        "setp.eq.b32 p1, 0, 0;\n"
        "add.s64 tb0, %64, %65;\n"
        "add.s64 tb, tb0, 0;\n"
        "wgmma.mma_async.sync.aligned.m64n192k16.f16.f16.f16 {%0, %1, %2, %3, %4, %5, %6, %7, %8, %9, %10, %11, %12, %13, %14, %15, %16, %17, %18, %19, %20, %21, %22, %23, %24, %25, %26, %27, %28, %29, %30, %31, %32, %33, %34, %35, %36, %37, %38, %39, %40, %41, %42, %43, %44, %45, %46, %47}, {%48, %49, %50, %51}, tb, p0, 1, 1, 1;\n"
        "add.s64 tb, tb0, 32;\n"
        "wgmma.mma_async.sync.aligned.m64n192k16.f16.f16.f16 {%0, %1, %2, %3, %4, %5, %6, %7, %8, %9, %10, %11, %12, %13, %14, %15, %16, %17, %18, %19, %20, %21, %22, %23, %24, %25, %26, %27, %28, %29, %30, %31, %32, %33, %34, %35, %36, %37, %38, %39, %40, %41, %42, %43, %44, %45, %46, %47}, {%52, %53, %54, %55}, tb, p1, 1, 1, 1;\n"
        "add.s64 tb, tb0, 64;\n"
        "wgmma.mma_async.sync.aligned.m64n192k16.f16.f16.f16 {%0, %1, %2, %3, %4, %5, %6, %7, %8, %9, %10, %11, %12, %13, %14, %15, %16, %17, %18, %19, %20, %21, %22, %23, %24, %25, %26, %27, %28, %29, %30, %31, %32, %33, %34, %35, %36, %37, %38, %39, %40, %41, %42, %43, %44, %45, %46, %47}, {%56, %57, %58, %59}, tb, p1, 1, 1, 1;\n"
        "add.s64 tb, tb0, 96;\n"
        "wgmma.mma_async.sync.aligned.m64n192k16.f16.f16.f16 {%0, %1, %2, %3, %4, %5, %6, %7, %8, %9, %10, %11, %12, %13, %14, %15, %16, %17, %18, %19, %20, %21, %22, %23, %24, %25, %26, %27, %28, %29, %30, %31, %32, %33, %34, %35, %36, %37, %38, %39, %40, %41, %42, %43, %44, %45, %46, %47}, {%60, %61, %62, %63}, tb, p1, 1, 1, 1;\n"
        "}\n"
        : "=r"(d[0]), "=r"(d[1]), "=r"(d[2]), "=r"(d[3]), "=r"(d[4]), "=r"(d[5]), "=r"(d[6]), "=r"(d[7]), "=r"(d[8]), "=r"(d[9]), "=r"(d[10]), "=r"(d[11]), "=r"(d[12]), "=r"(d[13]), "=r"(d[14]), "=r"(d[15]), "=r"(d[16]), "=r"(d[17]), "=r"(d[18]), "=r"(d[19]), "=r"(d[20]), "=r"(d[21]), "=r"(d[22]), "=r"(d[23]), "=r"(d[24]), "=r"(d[25]), "=r"(d[26]), "=r"(d[27]), "=r"(d[28]), "=r"(d[29]), "=r"(d[30]), "=r"(d[31]), "=r"(d[32]), "=r"(d[33]), "=r"(d[34]), "=r"(d[35]), "=r"(d[36]), "=r"(d[37]), "=r"(d[38]), "=r"(d[39]), "=r"(d[40]), "=r"(d[41]), "=r"(d[42]), "=r"(d[43]), "=r"(d[44]), "=r"(d[45]), "=r"(d[46]), "=r"(d[47])
        : "r"(a[AOFF + 0][0]), "r"(a[AOFF + 0][1]), "r"(a[AOFF + 0][2]), "r"(a[AOFF + 0][3]), "r"(a[AOFF + 1][0]), "r"(a[AOFF + 1][1]), "r"(a[AOFF + 1][2]), "r"(a[AOFF + 1][3]), "r"(a[AOFF + 2][0]), "r"(a[AOFF + 2][1]), "r"(a[AOFF + 2][2]), "r"(a[AOFF + 2][3]), "r"(a[AOFF + 3][0]), "r"(a[AOFF + 3][1]), "r"(a[AOFF + 3][2]), "r"(a[AOFF + 3][3]), "l"(descB), "n"(BOFF >> 4));
}

template <int BOFF, int AOFF, int NA>
__device__ __forceinline__ void mma_qk_next(uint32_t (&d)[48], const uint32_t (&a)[NA][4], uint64_t descB) {
    asm volatile(
        "{\n"
        ".reg .pred p0, p1;\n"
        ".reg .b64 ta, ta0, tb, tb0;\n"
        "setp.ne.b32 p0, 0, 0;\n"
        "setp.eq.b32 p1, 0, 0;\n"
        "add.s64 tb0, %64, %65;\n"
        "add.s64 tb, tb0, 0;\n"
        "wgmma.mma_async.sync.aligned.m64n192k16.f16.f16.f16 {%0, %1, %2, %3, %4, %5, %6, %7, %8, %9, %10, %11, %12, %13, %14, %15, %16, %17, %18, %19, %20, %21, %22, %23, %24, %25, %26, %27, %28, %29, %30, %31, %32, %33, %34, %35, %36, %37, %38, %39, %40, %41, %42, %43, %44, %45, %46, %47}, {%48, %49, %50, %51}, tb, p1, 1, 1, 1;\n"
        "add.s64 tb, tb0, 32;\n"
        "wgmma.mma_async.sync.aligned.m64n192k16.f16.f16.f16 {%0, %1, %2, %3, %4, %5, %6, %7, %8, %9, %10, %11, %12, %13, %14, %15, %16, %17, %18, %19, %20, %21, %22, %23, %24, %25, %26, %27, %28, %29, %30, %31, %32, %33, %34, %35, %36, %37, %38, %39, %40, %41, %42, %43, %44, %45, %46, %47}, {%52, %53, %54, %55}, tb, p1, 1, 1, 1;\n"
        "add.s64 tb, tb0, 64;\n"
        "wgmma.mma_async.sync.aligned.m64n192k16.f16.f16.f16 {%0, %1, %2, %3, %4, %5, %6, %7, %8, %9, %10, %11, %12, %13, %14, %15, %16, %17, %18, %19, %20, %21, %22, %23, %24, %25, %26, %27, %28, %29, %30, %31, %32, %33, %34, %35, %36, %37, %38, %39, %40, %41, %42, %43, %44, %45, %46, %47}, {%56, %57, %58, %59}, tb, p1, 1, 1, 1;\n"
        "add.s64 tb, tb0, 96;\n"
        "wgmma.mma_async.sync.aligned.m64n192k16.f16.f16.f16 {%0, %1, %2, %3, %4, %5, %6, %7, %8, %9, %10, %11, %12, %13, %14, %15, %16, %17, %18, %19, %20, %21, %22, %23, %24, %25, %26, %27, %28, %29, %30, %31, %32, %33, %34, %35, %36, %37, %38, %39, %40, %41, %42, %43, %44, %45, %46, %47}, {%60, %61, %62, %63}, tb, p1, 1, 1, 1;\n"
        "}\n"
        : "+r"(d[0]), "+r"(d[1]), "+r"(d[2]), "+r"(d[3]), "+r"(d[4]), "+r"(d[5]), "+r"(d[6]), "+r"(d[7]), "+r"(d[8]), "+r"(d[9]), "+r"(d[10]), "+r"(d[11]), "+r"(d[12]), "+r"(d[13]), "+r"(d[14]), "+r"(d[15]), "+r"(d[16]), "+r"(d[17]), "+r"(d[18]), "+r"(d[19]), "+r"(d[20]), "+r"(d[21]), "+r"(d[22]), "+r"(d[23]), "+r"(d[24]), "+r"(d[25]), "+r"(d[26]), "+r"(d[27]), "+r"(d[28]), "+r"(d[29]), "+r"(d[30]), "+r"(d[31]), "+r"(d[32]), "+r"(d[33]), "+r"(d[34]), "+r"(d[35]), "+r"(d[36]), "+r"(d[37]), "+r"(d[38]), "+r"(d[39]), "+r"(d[40]), "+r"(d[41]), "+r"(d[42]), "+r"(d[43]), "+r"(d[44]), "+r"(d[45]), "+r"(d[46]), "+r"(d[47])
        : "r"(a[AOFF + 0][0]), "r"(a[AOFF + 0][1]), "r"(a[AOFF + 0][2]), "r"(a[AOFF + 0][3]), "r"(a[AOFF + 1][0]), "r"(a[AOFF + 1][1]), "r"(a[AOFF + 1][2]), "r"(a[AOFF + 1][3]), "r"(a[AOFF + 2][0]), "r"(a[AOFF + 2][1]), "r"(a[AOFF + 2][2]), "r"(a[AOFF + 2][3]), "r"(a[AOFF + 3][0]), "r"(a[AOFF + 3][1]), "r"(a[AOFF + 3][2]), "r"(a[AOFF + 3][3]), "l"(descB), "n"(BOFF >> 4));
}

template <int BOFF, int AOFF, int NA>
__device__ __forceinline__ void mma_v_first(uint32_t (&d)[24], const uint32_t (&a)[NA][4], uint64_t descB) {
    asm volatile(
        "{\n"
        ".reg .pred p0, p1;\n"
        ".reg .b64 ta, ta0, tb, tb0;\n"
        "setp.ne.b32 p0, 0, 0;\n"
        "setp.eq.b32 p1, 0, 0;\n"
        "add.s64 tb0, %40, %41;\n"
        "add.s64 tb, tb0, 0;\n"
        "wgmma.mma_async.sync.aligned.m64n96k16.f16.f16.f16 {%0, %1, %2, %3, %4, %5, %6, %7, %8, %9, %10, %11, %12, %13, %14, %15, %16, %17, %18, %19, %20, %21, %22, %23}, {%24, %25, %26, %27}, tb, p0, 1, 1, 1;\n"
        "add.s64 tb, tb0, 32;\n"
        "wgmma.mma_async.sync.aligned.m64n96k16.f16.f16.f16 {%0, %1, %2, %3, %4, %5, %6, %7, %8, %9, %10, %11, %12, %13, %14, %15, %16, %17, %18, %19, %20, %21, %22, %23}, {%28, %29, %30, %31}, tb, p1, 1, 1, 1;\n"
        "add.s64 tb, tb0, 64;\n"
        "wgmma.mma_async.sync.aligned.m64n96k16.f16.f16.f16 {%0, %1, %2, %3, %4, %5, %6, %7, %8, %9, %10, %11, %12, %13, %14, %15, %16, %17, %18, %19, %20, %21, %22, %23}, {%32, %33, %34, %35}, tb, p1, 1, 1, 1;\n"
        "add.s64 tb, tb0, 96;\n"
        "wgmma.mma_async.sync.aligned.m64n96k16.f16.f16.f16 {%0, %1, %2, %3, %4, %5, %6, %7, %8, %9, %10, %11, %12, %13, %14, %15, %16, %17, %18, %19, %20, %21, %22, %23}, {%36, %37, %38, %39}, tb, p1, 1, 1, 1;\n"
        "}\n"
        : "=r"(d[0]), "=r"(d[1]), "=r"(d[2]), "=r"(d[3]), "=r"(d[4]), "=r"(d[5]), "=r"(d[6]), "=r"(d[7]), "=r"(d[8]), "=r"(d[9]), "=r"(d[10]), "=r"(d[11]), "=r"(d[12]), "=r"(d[13]), "=r"(d[14]), "=r"(d[15]), "=r"(d[16]), "=r"(d[17]), "=r"(d[18]), "=r"(d[19]), "=r"(d[20]), "=r"(d[21]), "=r"(d[22]), "=r"(d[23])
        : "r"(a[AOFF + 0][0]), "r"(a[AOFF + 0][1]), "r"(a[AOFF + 0][2]), "r"(a[AOFF + 0][3]), "r"(a[AOFF + 1][0]), "r"(a[AOFF + 1][1]), "r"(a[AOFF + 1][2]), "r"(a[AOFF + 1][3]), "r"(a[AOFF + 2][0]), "r"(a[AOFF + 2][1]), "r"(a[AOFF + 2][2]), "r"(a[AOFF + 2][3]), "r"(a[AOFF + 3][0]), "r"(a[AOFF + 3][1]), "r"(a[AOFF + 3][2]), "r"(a[AOFF + 3][3]), "l"(descB), "n"(BOFF >> 4));
}

template <int BOFF, int AOFF, int NA>
__device__ __forceinline__ void mma_v_next(uint32_t (&d)[24], const uint32_t (&a)[NA][4], uint64_t descB) {
    asm volatile(
        "{\n"
        ".reg .pred p0, p1;\n"
        ".reg .b64 ta, ta0, tb, tb0;\n"
        "setp.ne.b32 p0, 0, 0;\n"
        "setp.eq.b32 p1, 0, 0;\n"
        "add.s64 tb0, %40, %41;\n"
        "add.s64 tb, tb0, 0;\n"
        "wgmma.mma_async.sync.aligned.m64n96k16.f16.f16.f16 {%0, %1, %2, %3, %4, %5, %6, %7, %8, %9, %10, %11, %12, %13, %14, %15, %16, %17, %18, %19, %20, %21, %22, %23}, {%24, %25, %26, %27}, tb, p1, 1, 1, 1;\n"
        "add.s64 tb, tb0, 32;\n"
        "wgmma.mma_async.sync.aligned.m64n96k16.f16.f16.f16 {%0, %1, %2, %3, %4, %5, %6, %7, %8, %9, %10, %11, %12, %13, %14, %15, %16, %17, %18, %19, %20, %21, %22, %23}, {%28, %29, %30, %31}, tb, p1, 1, 1, 1;\n"
        "add.s64 tb, tb0, 64;\n"
        "wgmma.mma_async.sync.aligned.m64n96k16.f16.f16.f16 {%0, %1, %2, %3, %4, %5, %6, %7, %8, %9, %10, %11, %12, %13, %14, %15, %16, %17, %18, %19, %20, %21, %22, %23}, {%32, %33, %34, %35}, tb, p1, 1, 1, 1;\n"
        "add.s64 tb, tb0, 96;\n"
        "wgmma.mma_async.sync.aligned.m64n96k16.f16.f16.f16 {%0, %1, %2, %3, %4, %5, %6, %7, %8, %9, %10, %11, %12, %13, %14, %15, %16, %17, %18, %19, %20, %21, %22, %23}, {%36, %37, %38, %39}, tb, p1, 1, 1, 1;\n"
        "}\n"
        : "+r"(d[0]), "+r"(d[1]), "+r"(d[2]), "+r"(d[3]), "+r"(d[4]), "+r"(d[5]), "+r"(d[6]), "+r"(d[7]), "+r"(d[8]), "+r"(d[9]), "+r"(d[10]), "+r"(d[11]), "+r"(d[12]), "+r"(d[13]), "+r"(d[14]), "+r"(d[15]), "+r"(d[16]), "+r"(d[17]), "+r"(d[18]), "+r"(d[19]), "+r"(d[20]), "+r"(d[21]), "+r"(d[22]), "+r"(d[23])
        : "r"(a[AOFF + 0][0]), "r"(a[AOFF + 0][1]), "r"(a[AOFF + 0][2]), "r"(a[AOFF + 0][3]), "r"(a[AOFF + 1][0]), "r"(a[AOFF + 1][1]), "r"(a[AOFF + 1][2]), "r"(a[AOFF + 1][3]), "r"(a[AOFF + 2][0]), "r"(a[AOFF + 2][1]), "r"(a[AOFF + 2][2]), "r"(a[AOFF + 2][3]), "r"(a[AOFF + 3][0]), "r"(a[AOFF + 3][1]), "r"(a[AOFF + 3][2]), "r"(a[AOFF + 3][3]), "l"(descB), "n"(BOFF >> 4));
}

template <int AOFF, int BOFF>
__device__ __forceinline__ void mma_s0_f32(float (&d)[28], uint64_t descA, uint64_t descB) {
    asm volatile(
        "{\n"
        ".reg .pred p0, p1;\n"
        ".reg .b64 ta, ta0, tb, tb0;\n"
        "setp.ne.b32 p0, 0, 0;\n"
        "setp.eq.b32 p1, 0, 0;\n"
        "add.s64 tb0, %30, %31;\n"
        "add.s64 ta0, %28, %29;\n"
        "add.s64 tb, tb0, 4;\n"
        "add.s64 ta, ta0, 0;\n"
        "wgmma.mma_async.sync.aligned.m64n56k16.f32.f16.f16 {%0, %1, %2, %3, %4, %5, %6, %7, %8, %9, %10, %11, %12, %13, %14, %15, %16, %17, %18, %19, %20, %21, %22, %23, %24, %25, %26, %27}, ta, tb, p1, 1, 1, 0, 0;\n"
        "add.s64 tb, tb0, 1572;\n"
        "add.s64 ta, ta0, 1568;\n"
        "wgmma.mma_async.sync.aligned.m64n56k16.f32.f16.f16 {%0, %1, %2, %3, %4, %5, %6, %7, %8, %9, %10, %11, %12, %13, %14, %15, %16, %17, %18, %19, %20, %21, %22, %23, %24, %25, %26, %27}, ta, tb, p1, 1, 1, 0, 0;\n"
        "add.s64 tb, tb0, 3140;\n"
        "add.s64 ta, ta0, 3136;\n"
        "wgmma.mma_async.sync.aligned.m64n56k16.f32.f16.f16 {%0, %1, %2, %3, %4, %5, %6, %7, %8, %9, %10, %11, %12, %13, %14, %15, %16, %17, %18, %19, %20, %21, %22, %23, %24, %25, %26, %27}, ta, tb, p1, 1, 1, 0, 0;\n"
        "}\n"
        : "+f"(d[0]), "+f"(d[1]), "+f"(d[2]), "+f"(d[3]), "+f"(d[4]), "+f"(d[5]), "+f"(d[6]), "+f"(d[7]), "+f"(d[8]), "+f"(d[9]), "+f"(d[10]), "+f"(d[11]), "+f"(d[12]), "+f"(d[13]), "+f"(d[14]), "+f"(d[15]), "+f"(d[16]), "+f"(d[17]), "+f"(d[18]), "+f"(d[19]), "+f"(d[20]), "+f"(d[21]), "+f"(d[22]), "+f"(d[23]), "+f"(d[24]), "+f"(d[25]), "+f"(d[26]), "+f"(d[27])
        : "l"(descA), "n"(AOFF >> 4), "l"(descB), "n"(BOFF >> 4));
}

template <int AOFF, int BOFF>
__device__ __forceinline__ void mma_s0_f16(uint32_t (&d)[14], uint64_t descA, uint64_t descB) {
    asm volatile(
        "{\n"
        ".reg .pred p0, p1;\n"
        ".reg .b64 ta, ta0, tb, tb0;\n"
        "setp.ne.b32 p0, 0, 0;\n"
        "setp.eq.b32 p1, 0, 0;\n"
        "add.s64 tb0, %16, %17;\n"
        "add.s64 ta0, %14, %15;\n"
        "add.s64 tb, tb0, 4;\n"
        "add.s64 ta, ta0, 0;\n"
        "wgmma.mma_async.sync.aligned.m64n56k16.f16.f16.f16 {%0, %1, %2, %3, %4, %5, %6, %7, %8, %9, %10, %11, %12, %13}, ta, tb, p1, 1, 1, 0, 0;\n"
        "add.s64 tb, tb0, 1572;\n"
        "add.s64 ta, ta0, 1568;\n"
        "wgmma.mma_async.sync.aligned.m64n56k16.f16.f16.f16 {%0, %1, %2, %3, %4, %5, %6, %7, %8, %9, %10, %11, %12, %13}, ta, tb, p1, 1, 1, 0, 0;\n"
        "add.s64 tb, tb0, 3140;\n"
        "add.s64 ta, ta0, 3136;\n"
        "wgmma.mma_async.sync.aligned.m64n56k16.f16.f16.f16 {%0, %1, %2, %3, %4, %5, %6, %7, %8, %9, %10, %11, %12, %13}, ta, tb, p1, 1, 1, 0, 0;\n"
        "}\n"
        : "+r"(d[0]), "+r"(d[1]), "+r"(d[2]), "+r"(d[3]), "+r"(d[4]), "+r"(d[5]), "+r"(d[6]), "+r"(d[7]), "+r"(d[8]), "+r"(d[9]), "+r"(d[10]), "+r"(d[11]), "+r"(d[12]), "+r"(d[13])
        : "l"(descA), "n"(AOFF >> 4), "l"(descB), "n"(BOFF >> 4));
}

template <int AOFF, int BOFF>
__device__ __forceinline__ void mma_s1_f32(float (&d)[28], uint64_t descA, uint64_t descB) {
    asm volatile(
        "{\n"
        ".reg .pred p0, p1;\n"
        ".reg .b64 ta, ta0, tb, tb0;\n"
        "setp.ne.b32 p0, 0, 0;\n"
        "setp.eq.b32 p1, 0, 0;\n"
        "add.s64 tb0, %30, %31;\n"
        "add.s64 ta0, %28, %29;\n"
        "add.s64 tb, tb0, 6;\n"
        "add.s64 ta, ta0, 2;\n"
        "wgmma.mma_async.sync.aligned.m64n56k16.f32.f16.f16 {%0, %1, %2, %3, %4, %5, %6, %7, %8, %9, %10, %11, %12, %13, %14, %15, %16, %17, %18, %19, %20, %21, %22, %23, %24, %25, %26, %27}, ta, tb, p1, 1, 1, 0, 0;\n"
        "add.s64 tb, tb0, 1574;\n"
        "add.s64 ta, ta0, 1570;\n"
        "wgmma.mma_async.sync.aligned.m64n56k16.f32.f16.f16 {%0, %1, %2, %3, %4, %5, %6, %7, %8, %9, %10, %11, %12, %13, %14, %15, %16, %17, %18, %19, %20, %21, %22, %23, %24, %25, %26, %27}, ta, tb, p1, 1, 1, 0, 0;\n"
        "add.s64 tb, tb0, 3142;\n"
        "add.s64 ta, ta0, 3138;\n"
        "wgmma.mma_async.sync.aligned.m64n56k16.f32.f16.f16 {%0, %1, %2, %3, %4, %5, %6, %7, %8, %9, %10, %11, %12, %13, %14, %15, %16, %17, %18, %19, %20, %21, %22, %23, %24, %25, %26, %27}, ta, tb, p1, 1, 1, 0, 0;\n"
        "}\n"
        : "+f"(d[0]), "+f"(d[1]), "+f"(d[2]), "+f"(d[3]), "+f"(d[4]), "+f"(d[5]), "+f"(d[6]), "+f"(d[7]), "+f"(d[8]), "+f"(d[9]), "+f"(d[10]), "+f"(d[11]), "+f"(d[12]), "+f"(d[13]), "+f"(d[14]), "+f"(d[15]), "+f"(d[16]), "+f"(d[17]), "+f"(d[18]), "+f"(d[19]), "+f"(d[20]), "+f"(d[21]), "+f"(d[22]), "+f"(d[23]), "+f"(d[24]), "+f"(d[25]), "+f"(d[26]), "+f"(d[27])
        : "l"(descA), "n"(AOFF >> 4), "l"(descB), "n"(BOFF >> 4));
}

template <int AOFF, int BOFF>
__device__ __forceinline__ void mma_s1_f16(uint32_t (&d)[14], uint64_t descA, uint64_t descB) {
    asm volatile(
        "{\n"
        ".reg .pred p0, p1;\n"
        ".reg .b64 ta, ta0, tb, tb0;\n"
        "setp.ne.b32 p0, 0, 0;\n"
        "setp.eq.b32 p1, 0, 0;\n"
        "add.s64 tb0, %16, %17;\n"
        "add.s64 ta0, %14, %15;\n"
        "add.s64 tb, tb0, 6;\n"
        "add.s64 ta, ta0, 2;\n"
        "wgmma.mma_async.sync.aligned.m64n56k16.f16.f16.f16 {%0, %1, %2, %3, %4, %5, %6, %7, %8, %9, %10, %11, %12, %13}, ta, tb, p1, 1, 1, 0, 0;\n"
        "add.s64 tb, tb0, 1574;\n"
        "add.s64 ta, ta0, 1570;\n"
        "wgmma.mma_async.sync.aligned.m64n56k16.f16.f16.f16 {%0, %1, %2, %3, %4, %5, %6, %7, %8, %9, %10, %11, %12, %13}, ta, tb, p1, 1, 1, 0, 0;\n"
        "add.s64 tb, tb0, 3142;\n"
        "add.s64 ta, ta0, 3138;\n"
        "wgmma.mma_async.sync.aligned.m64n56k16.f16.f16.f16 {%0, %1, %2, %3, %4, %5, %6, %7, %8, %9, %10, %11, %12, %13}, ta, tb, p1, 1, 1, 0, 0;\n"
        "}\n"
        : "+r"(d[0]), "+r"(d[1]), "+r"(d[2]), "+r"(d[3]), "+r"(d[4]), "+r"(d[5]), "+r"(d[6]), "+r"(d[7]), "+r"(d[8]), "+r"(d[9]), "+r"(d[10]), "+r"(d[11]), "+r"(d[12]), "+r"(d[13])
        : "l"(descA), "n"(AOFF >> 4), "l"(descB), "n"(BOFF >> 4));
}

template <int BOFF, int AOFF, int NA>
__device__ __forceinline__ void mma_pv(uint32_t (&d)[14], const uint32_t (&a)[NA][4], uint64_t descB) {
    asm volatile(
        "{\n"
        ".reg .pred p0, p1;\n"
        ".reg .b64 ta, ta0, tb, tb0;\n"
        "setp.ne.b32 p0, 0, 0;\n"
        "setp.eq.b32 p1, 0, 0;\n"
        "add.s64 tb0, %30, %31;\n"
        "add.s64 tb, tb0, 0;\n"
        "wgmma.mma_async.sync.aligned.m64n56k16.f16.f16.f16 {%0, %1, %2, %3, %4, %5, %6, %7, %8, %9, %10, %11, %12, %13}, {%14, %15, %16, %17}, tb, p0, 1, 1, 1;\n"
        "add.s64 tb, tb0, 16;\n"
        "wgmma.mma_async.sync.aligned.m64n56k16.f16.f16.f16 {%0, %1, %2, %3, %4, %5, %6, %7, %8, %9, %10, %11, %12, %13}, {%18, %19, %20, %21}, tb, p1, 1, 1, 1;\n"
        "add.s64 tb, tb0, 32;\n"
        "wgmma.mma_async.sync.aligned.m64n56k16.f16.f16.f16 {%0, %1, %2, %3, %4, %5, %6, %7, %8, %9, %10, %11, %12, %13}, {%22, %23, %24, %25}, tb, p1, 1, 1, 1;\n"
        "add.s64 tb, tb0, 48;\n"
        "wgmma.mma_async.sync.aligned.m64n56k16.f16.f16.f16 {%0, %1, %2, %3, %4, %5, %6, %7, %8, %9, %10, %11, %12, %13}, {%26, %27, %28, %29}, tb, p1, 1, 1, 1;\n"
        "}\n"
        : "=r"(d[0]), "=r"(d[1]), "=r"(d[2]), "=r"(d[3]), "=r"(d[4]), "=r"(d[5]), "=r"(d[6]), "=r"(d[7]), "=r"(d[8]), "=r"(d[9]), "=r"(d[10]), "=r"(d[11]), "=r"(d[12]), "=r"(d[13])
        : "r"(a[AOFF + 0][0]), "r"(a[AOFF + 0][1]), "r"(a[AOFF + 0][2]), "r"(a[AOFF + 0][3]), "r"(a[AOFF + 1][0]), "r"(a[AOFF + 1][1]), "r"(a[AOFF + 1][2]), "r"(a[AOFF + 1][3]), "r"(a[AOFF + 2][0]), "r"(a[AOFF + 2][1]), "r"(a[AOFF + 2][2]), "r"(a[AOFF + 2][3]), "r"(a[AOFF + 3][0]), "r"(a[AOFF + 3][1]), "r"(a[AOFF + 3][2]), "r"(a[AOFF + 3][3]), "l"(descB), "n"(BOFF >> 4));
}

template <int AOFF, int BOFF>
__device__ __forceinline__ void mma_proj(float (&d)[96], uint64_t descA, uint64_t descB) {
    asm volatile(
        "{\n"
        ".reg .pred p0, p1;\n"
        ".reg .b64 ta, ta0, tb, tb0;\n"
        "setp.ne.b32 p0, 0, 0;\n"
        "setp.eq.b32 p1, 0, 0;\n"
        "add.s64 tb0, %98, %99;\n"
        "add.s64 ta0, %96, %97;\n"
        "add.s64 tb, tb0, 0;\n"
        "add.s64 ta, ta0, 0;\n"
        "wgmma.mma_async.sync.aligned.m64n192k16.f32.f16.f16 {%0, %1, %2, %3, %4, %5, %6, %7, %8, %9, %10, %11, %12, %13, %14, %15, %16, %17, %18, %19, %20, %21, %22, %23, %24, %25, %26, %27, %28, %29, %30, %31, %32, %33, %34, %35, %36, %37, %38, %39, %40, %41, %42, %43, %44, %45, %46, %47, %48, %49, %50, %51, %52, %53, %54, %55, %56, %57, %58, %59, %60, %61, %62, %63, %64, %65, %66, %67, %68, %69, %70, %71, %72, %73, %74, %75, %76, %77, %78, %79, %80, %81, %82, %83, %84, %85, %86, %87, %88, %89, %90, %91, %92, %93, %94, %95}, ta, tb, p0, 1, 1, 0, 1;\n"
        "add.s64 tb, tb0, 64;\n"
        "add.s64 ta, ta0, 2;\n"
        "wgmma.mma_async.sync.aligned.m64n192k16.f32.f16.f16 {%0, %1, %2, %3, %4, %5, %6, %7, %8, %9, %10, %11, %12, %13, %14, %15, %16, %17, %18, %19, %20, %21, %22, %23, %24, %25, %26, %27, %28, %29, %30, %31, %32, %33, %34, %35, %36, %37, %38, %39, %40, %41, %42, %43, %44, %45, %46, %47, %48, %49, %50, %51, %52, %53, %54, %55, %56, %57, %58, %59, %60, %61, %62, %63, %64, %65, %66, %67, %68, %69, %70, %71, %72, %73, %74, %75, %76, %77, %78, %79, %80, %81, %82, %83, %84, %85, %86, %87, %88, %89, %90, %91, %92, %93, %94, %95}, ta, tb, p1, 1, 1, 0, 1;\n"
        "add.s64 tb, tb0, 128;\n"
        "add.s64 ta, ta0, 4;\n"
        "wgmma.mma_async.sync.aligned.m64n192k16.f32.f16.f16 {%0, %1, %2, %3, %4, %5, %6, %7, %8, %9, %10, %11, %12, %13, %14, %15, %16, %17, %18, %19, %20, %21, %22, %23, %24, %25, %26, %27, %28, %29, %30, %31, %32, %33, %34, %35, %36, %37, %38, %39, %40, %41, %42, %43, %44, %45, %46, %47, %48, %49, %50, %51, %52, %53, %54, %55, %56, %57, %58, %59, %60, %61, %62, %63, %64, %65, %66, %67, %68, %69, %70, %71, %72, %73, %74, %75, %76, %77, %78, %79, %80, %81, %82, %83, %84, %85, %86, %87, %88, %89, %90, %91, %92, %93, %94, %95}, ta, tb, p1, 1, 1, 0, 1;\n"
        "add.s64 tb, tb0, 192;\n"
        "add.s64 ta, ta0, 6;\n"
        "wgmma.mma_async.sync.aligned.m64n192k16.f32.f16.f16 {%0, %1, %2, %3, %4, %5, %6, %7, %8, %9, %10, %11, %12, %13, %14, %15, %16, %17, %18, %19, %20, %21, %22, %23, %24, %25, %26, %27, %28, %29, %30, %31, %32, %33, %34, %35, %36, %37, %38, %39, %40, %41, %42, %43, %44, %45, %46, %47, %48, %49, %50, %51, %52, %53, %54, %55, %56, %57, %58, %59, %60, %61, %62, %63, %64, %65, %66, %67, %68, %69, %70, %71, %72, %73, %74, %75, %76, %77, %78, %79, %80, %81, %82, %83, %84, %85, %86, %87, %88, %89, %90, %91, %92, %93, %94, %95}, ta, tb, p1, 1, 1, 0, 1;\n"
        "add.s64 tb, tb0, 256;\n"
        "add.s64 ta, ta0, 512;\n"
        "wgmma.mma_async.sync.aligned.m64n192k16.f32.f16.f16 {%0, %1, %2, %3, %4, %5, %6, %7, %8, %9, %10, %11, %12, %13, %14, %15, %16, %17, %18, %19, %20, %21, %22, %23, %24, %25, %26, %27, %28, %29, %30, %31, %32, %33, %34, %35, %36, %37, %38, %39, %40, %41, %42, %43, %44, %45, %46, %47, %48, %49, %50, %51, %52, %53, %54, %55, %56, %57, %58, %59, %60, %61, %62, %63, %64, %65, %66, %67, %68, %69, %70, %71, %72, %73, %74, %75, %76, %77, %78, %79, %80, %81, %82, %83, %84, %85, %86, %87, %88, %89, %90, %91, %92, %93, %94, %95}, ta, tb, p1, 1, 1, 0, 1;\n"
        "add.s64 tb, tb0, 320;\n"
        "add.s64 ta, ta0, 514;\n"
        "wgmma.mma_async.sync.aligned.m64n192k16.f32.f16.f16 {%0, %1, %2, %3, %4, %5, %6, %7, %8, %9, %10, %11, %12, %13, %14, %15, %16, %17, %18, %19, %20, %21, %22, %23, %24, %25, %26, %27, %28, %29, %30, %31, %32, %33, %34, %35, %36, %37, %38, %39, %40, %41, %42, %43, %44, %45, %46, %47, %48, %49, %50, %51, %52, %53, %54, %55, %56, %57, %58, %59, %60, %61, %62, %63, %64, %65, %66, %67, %68, %69, %70, %71, %72, %73, %74, %75, %76, %77, %78, %79, %80, %81, %82, %83, %84, %85, %86, %87, %88, %89, %90, %91, %92, %93, %94, %95}, ta, tb, p1, 1, 1, 0, 1;\n"
        "add.s64 tb, tb0, 384;\n"
        "add.s64 ta, ta0, 516;\n"
        "wgmma.mma_async.sync.aligned.m64n192k16.f32.f16.f16 {%0, %1, %2, %3, %4, %5, %6, %7, %8, %9, %10, %11, %12, %13, %14, %15, %16, %17, %18, %19, %20, %21, %22, %23, %24, %25, %26, %27, %28, %29, %30, %31, %32, %33, %34, %35, %36, %37, %38, %39, %40, %41, %42, %43, %44, %45, %46, %47, %48, %49, %50, %51, %52, %53, %54, %55, %56, %57, %58, %59, %60, %61, %62, %63, %64, %65, %66, %67, %68, %69, %70, %71, %72, %73, %74, %75, %76, %77, %78, %79, %80, %81, %82, %83, %84, %85, %86, %87, %88, %89, %90, %91, %92, %93, %94, %95}, ta, tb, p1, 1, 1, 0, 1;\n"
        "add.s64 tb, tb0, 448;\n"
        "add.s64 ta, ta0, 518;\n"
        "wgmma.mma_async.sync.aligned.m64n192k16.f32.f16.f16 {%0, %1, %2, %3, %4, %5, %6, %7, %8, %9, %10, %11, %12, %13, %14, %15, %16, %17, %18, %19, %20, %21, %22, %23, %24, %25, %26, %27, %28, %29, %30, %31, %32, %33, %34, %35, %36, %37, %38, %39, %40, %41, %42, %43, %44, %45, %46, %47, %48, %49, %50, %51, %52, %53, %54, %55, %56, %57, %58, %59, %60, %61, %62, %63, %64, %65, %66, %67, %68, %69, %70, %71, %72, %73, %74, %75, %76, %77, %78, %79, %80, %81, %82, %83, %84, %85, %86, %87, %88, %89, %90, %91, %92, %93, %94, %95}, ta, tb, p1, 1, 1, 0, 1;\n"
        "add.s64 tb, tb0, 512;\n"
        "add.s64 ta, ta0, 1024;\n"
        "wgmma.mma_async.sync.aligned.m64n192k16.f32.f16.f16 {%0, %1, %2, %3, %4, %5, %6, %7, %8, %9, %10, %11, %12, %13, %14, %15, %16, %17, %18, %19, %20, %21, %22, %23, %24, %25, %26, %27, %28, %29, %30, %31, %32, %33, %34, %35, %36, %37, %38, %39, %40, %41, %42, %43, %44, %45, %46, %47, %48, %49, %50, %51, %52, %53, %54, %55, %56, %57, %58, %59, %60, %61, %62, %63, %64, %65, %66, %67, %68, %69, %70, %71, %72, %73, %74, %75, %76, %77, %78, %79, %80, %81, %82, %83, %84, %85, %86, %87, %88, %89, %90, %91, %92, %93, %94, %95}, ta, tb, p1, 1, 1, 0, 1;\n"
        "add.s64 tb, tb0, 576;\n"
        "add.s64 ta, ta0, 1026;\n"
        "wgmma.mma_async.sync.aligned.m64n192k16.f32.f16.f16 {%0, %1, %2, %3, %4, %5, %6, %7, %8, %9, %10, %11, %12, %13, %14, %15, %16, %17, %18, %19, %20, %21, %22, %23, %24, %25, %26, %27, %28, %29, %30, %31, %32, %33, %34, %35, %36, %37, %38, %39, %40, %41, %42, %43, %44, %45, %46, %47, %48, %49, %50, %51, %52, %53, %54, %55, %56, %57, %58, %59, %60, %61, %62, %63, %64, %65, %66, %67, %68, %69, %70, %71, %72, %73, %74, %75, %76, %77, %78, %79, %80, %81, %82, %83, %84, %85, %86, %87, %88, %89, %90, %91, %92, %93, %94, %95}, ta, tb, p1, 1, 1, 0, 1;\n"
        "add.s64 tb, tb0, 640;\n"
        "add.s64 ta, ta0, 1028;\n"
        "wgmma.mma_async.sync.aligned.m64n192k16.f32.f16.f16 {%0, %1, %2, %3, %4, %5, %6, %7, %8, %9, %10, %11, %12, %13, %14, %15, %16, %17, %18, %19, %20, %21, %22, %23, %24, %25, %26, %27, %28, %29, %30, %31, %32, %33, %34, %35, %36, %37, %38, %39, %40, %41, %42, %43, %44, %45, %46, %47, %48, %49, %50, %51, %52, %53, %54, %55, %56, %57, %58, %59, %60, %61, %62, %63, %64, %65, %66, %67, %68, %69, %70, %71, %72, %73, %74, %75, %76, %77, %78, %79, %80, %81, %82, %83, %84, %85, %86, %87, %88, %89, %90, %91, %92, %93, %94, %95}, ta, tb, p1, 1, 1, 0, 1;\n"
        "add.s64 tb, tb0, 704;\n"
        "add.s64 ta, ta0, 1030;\n"
        "wgmma.mma_async.sync.aligned.m64n192k16.f32.f16.f16 {%0, %1, %2, %3, %4, %5, %6, %7, %8, %9, %10, %11, %12, %13, %14, %15, %16, %17, %18, %19, %20, %21, %22, %23, %24, %25, %26, %27, %28, %29, %30, %31, %32, %33, %34, %35, %36, %37, %38, %39, %40, %41, %42, %43, %44, %45, %46, %47, %48, %49, %50, %51, %52, %53, %54, %55, %56, %57, %58, %59, %60, %61, %62, %63, %64, %65, %66, %67, %68, %69, %70, %71, %72, %73, %74, %75, %76, %77, %78, %79, %80, %81, %82, %83, %84, %85, %86, %87, %88, %89, %90, %91, %92, %93, %94, %95}, ta, tb, p1, 1, 1, 0, 1;\n"
        "}\n"
        : "+f"(d[0]), "+f"(d[1]), "+f"(d[2]), "+f"(d[3]), "+f"(d[4]), "+f"(d[5]), "+f"(d[6]), "+f"(d[7]), "+f"(d[8]), "+f"(d[9]), "+f"(d[10]), "+f"(d[11]), "+f"(d[12]), "+f"(d[13]), "+f"(d[14]), "+f"(d[15]), "+f"(d[16]), "+f"(d[17]), "+f"(d[18]), "+f"(d[19]), "+f"(d[20]), "+f"(d[21]), "+f"(d[22]), "+f"(d[23]), "+f"(d[24]), "+f"(d[25]), "+f"(d[26]), "+f"(d[27]), "+f"(d[28]), "+f"(d[29]), "+f"(d[30]), "+f"(d[31]), "+f"(d[32]), "+f"(d[33]), "+f"(d[34]), "+f"(d[35]), "+f"(d[36]), "+f"(d[37]), "+f"(d[38]), "+f"(d[39]), "+f"(d[40]), "+f"(d[41]), "+f"(d[42]), "+f"(d[43]), "+f"(d[44]), "+f"(d[45]), "+f"(d[46]), "+f"(d[47]), "+f"(d[48]), "+f"(d[49]), "+f"(d[50]), "+f"(d[51]), "+f"(d[52]), "+f"(d[53]), "+f"(d[54]), "+f"(d[55]), "+f"(d[56]), "+f"(d[57]), "+f"(d[58]), "+f"(d[59]), "+f"(d[60]), "+f"(d[61]), "+f"(d[62]), "+f"(d[63]), "+f"(d[64]), "+f"(d[65]), "+f"(d[66]), "+f"(d[67]), "+f"(d[68]), "+f"(d[69]), "+f"(d[70]), "+f"(d[71]), "+f"(d[72]), "+f"(d[73]), "+f"(d[74]), "+f"(d[75]), "+f"(d[76]), "+f"(d[77]), "+f"(d[78]), "+f"(d[79]), "+f"(d[80]), "+f"(d[81]), "+f"(d[82]), "+f"(d[83]), "+f"(d[84]), "+f"(d[85]), "+f"(d[86]), "+f"(d[87]), "+f"(d[88]), "+f"(d[89]), "+f"(d[90]), "+f"(d[91]), "+f"(d[92]), "+f"(d[93]), "+f"(d[94]), "+f"(d[95])
        : "l"(descA), "n"(AOFF >> 4), "l"(descB), "n"(BOFF >> 4));
}

struct Params {
    const __nv_bfloat16* x;
    const __nv_bfloat16* wqkv;
    const __nv_bfloat16* wo;
    const __nv_bfloat16* logit_scale;
    const __nv_bfloat16* cpb_w1;
    const __nv_bfloat16* cpb_w2;
    const __nv_bfloat16* rel_coords;
    const int*           rel_idx;
    const __nv_bfloat16* mask;
    __nv_bfloat16*       out;
    unsigned long long   z1;
    int                  npair;
    uint32_t             need;
    int                  spread;
    int                  t1;
};

constexpr uint32_t POS_END = 0x8000;
__device__ __forceinline__ uint32_t pos_add(uint32_t pos, int n) {
    pos += n;
    return (pos & 127) >= NWS ? pos + (128 - NWS) : pos;
}
__device__ __forceinline__ int role_of(const Params& P, int b) {
    const int n0 = ((b >> 1) * P.spread) >> 16, n1 = (((b >> 1) + 1) * P.spread) >> 16;
    return n1 != n0 ? 2 * P.npair + 2 * n0 + (b & 1) : b - 2 * n0;
}
__device__ __forceinline__ void finish(uint32_t total) {
    __threadfence();
    if (atomicAdd(&g_done, 1u) == total - 1) {
        for (int i = 0; i < NWS; i++) g_cnt[i] = 0;
        g_next[0] = 0; g_next[1] = 0;
        g_done = 0;
    }
}

constexpr int FB_PITCH = 584, FB_X = TOK * FB_PITCH * 2, FB_TAB = FB_X + TOK * 384, FB_BYTES = FB_TAB + 169 * 8 + 8;
static_assert(3 * FB_BYTES <= SM_PBAR && FB_BYTES % 16 == 0 && SM_BAR + B_ROWS == SM_PBAR + 64 && PCHUNK, "smem");
__device__ __forceinline__ void redo(const Params& P, uint8_t* sm, uint32_t tag, int barid) {
    typedef __nv_bfloat16 bf;
    const int t = threadIdx.x & 127, lane = t & 31;
    bf* const qkv = reinterpret_cast<bf*>(sm);
    bf* const xs = reinterpret_cast<bf*>(sm + FB_X);
    bf* const tab = reinterpret_cast<bf*>(sm + FB_TAB);
    volatile int* const next = reinterpret_cast<volatile int*>(sm + FB_TAB + 169 * 8);
#pragma unroll 1
    for (uint32_t n = 0; n < (1u << 22); n++) {
        uint32_t a;
        asm volatile("ld.acquire.gpu.global.u32 %0, [%1];\n" : "=r"(a) : "l"(g_guard) : "memory");
        if (a == tag + 1) break;
        __nanosleep(256);
    }
    asm volatile("fence.proxy.async;\n" ::: "memory");
#pragma unroll 1
    for (int i = t; i < 169 * 4; i += 128) {
        float a = 0.f;
#pragma unroll 1
        for (int u = 0; u < 16; u++) {
            const float h = round_bf16(__bfloat162float(P.rel_coords[(i >> 2) * 2]) * __bfloat162float(P.cpb_w1[u]) +
                                       __bfloat162float(P.rel_coords[(i >> 2) * 2 + 1]) * __bfloat162float(P.cpb_w1[16 + u]));
            a += (h > 0.f ? h : h * 0.f) * __bfloat162float(P.cpb_w2[u * 4 + (i & 3)]);
        }
        tab[i] = __float2bfloat16_rn(16.f * round_bf16(1.f / (1.f + expf(-round_bf16(a)))));
    }
#pragma unroll 1
    for (;;) {
        wg_bar(barid);
        if (t == 0) *next = (int)atomicAdd(g_guard + 2, 1u);
        wg_bar(barid);
        const int win = *next;
        if (win >= NWINDOWS) return;
        const int y0 = 7 * (win / NWS) + 3, x0 = 7 * (win % NWS) + 3;
        auto pixel = [&](int r) { return (size_t)(((y0 + r / 7) % IMG) * IMG + (x0 + r % 7) % IMG) * 192; };
#pragma unroll 1
        for (int i = t; i < TOK * 24; i += 128)
            reinterpret_cast<uint4*>(xs)[i] = reinterpret_cast<const uint4*>(P.x + pixel(i / 24))[i % 24];
#pragma unroll 1
        for (int ph = 0; ph < 2; ph++) {
            const bf* const a = ph ? qkv : xs;
            bf* const d = ph ? xs : qkv;
            const int n = ph ? 192 : 576, pa = ph ? FB_PITCH : 192, pd = ph ? 192 : FB_PITCH;
            wg_bar(barid);
#pragma unroll 1
            for (int col = t; col < n; col += 128) {
                const bf* w = (ph ? P.wo : P.wqkv) + col;
                float acc[TOK];
#pragma unroll
                for (int r = 0; r < TOK; r++) acc[r] = 0.f;
#pragma unroll 1
                for (int k = 0; k < 192; k += 2) {
                    const float w0 = __bfloat162float(w[k * n]), w1 = __bfloat162float(w[(k + 1) * n]);
#pragma unroll
                    for (int r = 0; r < TOK; r++) {
                        const uint32_t v = *reinterpret_cast<const uint32_t*>(a + r * pa + k);
                        acc[r] = fmaf(bf16hi(v), w1, fmaf(bf16lo(v), w0, acc[r]));
                    }
                }
#pragma unroll
                for (int r = 0; r < TOK; r++) d[r * pd + col] = __float2bfloat16_rn(acc[r]);
            }
            wg_bar(barid);
            if (ph) break;
#pragma unroll 1
            for (int i = t; i < TOK * 8; i += 128) {
                bf* const v = qkv + (i % TOK) * FB_PITCH + (i / TOK) * 48;
                float s = 0.f;
#pragma unroll 1
                for (int j = 0; j < 48; j++) s = fmaf(__bfloat162float(v[j]), __bfloat162float(v[j]), s);
                s = round_bf16(1.f / sqrtf(round_bf16(round_bf16(s) + 1e-12f)));
#pragma unroll 1
                for (int j = 0; j < 48; j++) v[j] = __float2bfloat16_rn(__bfloat162float(v[j]) * s);
            }
            wg_bar(barid);
#pragma unroll 1
            for (int i = t; i < TOK * 4; i += 128) {
                const int r = i % TOK, h = i / TOK;
                uint32_t* const q = reinterpret_cast<uint32_t*>(qkv + r * FB_PITCH + h * 48);
                const float tau = round_bf16(expf(round_bf16(fminf(fmaxf(__bfloat162float(P.logit_scale[h]), -100.f), 4.6052f))));
                float v[48], mx = -INFINITY, sum = 0.f;
#pragma unroll
                for (int j = 0; j < 24; j++) { v[2 * j] = bf16lo(q[j]); v[2 * j + 1] = bf16hi(q[j]); }
#pragma unroll 1
                for (int j = 0; j < TOK; j++) {
                    const uint32_t* kk = reinterpret_cast<const uint32_t*>(qkv + j * FB_PITCH + 192 + h * 48);
                    float s = 0.f;
#pragma unroll
                    for (int u = 0; u < 24; u++) s = fmaf(v[2 * u + 1], bf16hi(kk[u]), fmaf(v[2 * u], bf16lo(kk[u]), s));
                    s = round_bf16(round_bf16(s) * tau);
                    s = round_bf16(s + __bfloat162float(tab[min(max(P.rel_idx[r * TOK + j], 0), 168) * 4 + h]));
                    s = round_bf16(s + __bfloat162float(P.mask[(size_t)win * (TOK * TOK) + r * TOK + j]));
                    xs[j * 128 + t] = __float2bfloat16_rn(s);
                    mx = fmaxf(mx, s);
                }
#pragma unroll 1
                for (int j = 0; j < TOK; j++) sum += expf(__bfloat162float(xs[j * 128 + t]) - mx);
#pragma unroll
                for (int j = 0; j < 48; j++) v[j] = 0.f;
#pragma unroll 1
                for (int j = 0; j < TOK; j++) {
                    const uint32_t* vv = reinterpret_cast<const uint32_t*>(qkv + j * FB_PITCH + 384 + h * 48);
                    const float p = round_bf16(expf(__bfloat162float(xs[j * 128 + t]) - mx) / sum);
#pragma unroll
                    for (int u = 0; u < 24; u++) {
                        v[2 * u] = fmaf(p, bf16lo(vv[u]), v[2 * u]);
                        v[2 * u + 1] = fmaf(p, bf16hi(vv[u]), v[2 * u + 1]);
                    }
                }
#pragma unroll
                for (int j = 0; j < 24; j++) q[j] = pack_bf16(v[2 * j], v[2 * j + 1]);
            }
        }
#pragma unroll 1
        for (int r = t >> 5; r < TOK; r += 4) {
            float v[6], m = 0.f, s = 0.f;
#pragma unroll
            for (int j = 0; j < 6; j++) { v[j] = __bfloat162float(xs[r * 192 + j * 32 + lane]); m += v[j]; }
#pragma unroll
            for (int o = 16; o; o >>= 1) m += __shfl_xor_sync(0xffffffffu, m, o);
            m *= 1.f / 192.f;
#pragma unroll
            for (int j = 0; j < 6; j++) s = fmaf(v[j] - m, v[j] - m, s);
#pragma unroll
            for (int o = 16; o; o >>= 1) s += __shfl_xor_sync(0xffffffffu, s, o);
            s = round_bf16(sqrtf(round_bf16(round_bf16(s * (1.f / 192.f)) + 1e-5f)));
            m = round_bf16(m);
#pragma unroll
            for (int j = 0; j < 6; j++) P.out[pixel(r) + j * 32 + lane] = __float2bfloat16_rn(round_bf16(v[j] - m) / s);
        }
    }
}

__global__ void __launch_bounds__(NTHREADS, 1)
swin_window_attn_kernel(const Params P, const __grid_constant__ CUtensorMap xmap, const __grid_constant__ CUtensorMap xmap4,
                        const __grid_constant__ CUtensorMap xmap3,
                        const __grid_constant__ CUtensorMap omap, const __grid_constant__ CUtensorMap wmap,
                        const __grid_constant__ CUtensorMap smap, const __grid_constant__ CUtensorMap omapb,
                        const __grid_constant__ CUtensorMap xmapa, const __grid_constant__ CUtensorMap xmapb,
                        const __grid_constant__ CUtensorMap smap3, const __grid_constant__ CUtensorMap wraw) {
    extern __shared__ __align__(1024) uint8_t smem[];
    constexpr uint32_t sbase = 1024;
    if (smem_u32(smem) != sbase) return;
    const int tid = threadIdx.x;
    const int wg = __shfl_sync(0xffffffffu, tid >> 7, 0);
    const int warp = __shfl_sync(0xffffffffu, (tid >> 5) & 3, 0);
    const int lane = tid & 31;
    const int g = lane >> 2, c = lane & 3;

    TR(26, wg);
    if (wg == 0) { ST(0); SC(27); }
    const int role = role_of(P, blockIdx.x);
    const bool attn = role < 2 * P.npair;
    const int pair = role >> 1, half = role & 1;
    const uint32_t bars = sbase + SM_BAR;
    const int t0 = min(warp * 16 + g, TOK - 1), t1 = min(warp * 16 + g + 8, TOK - 1);
    int ridx[26];
    uint32_t rc, w2[16];
    uint4 w1[4];
    if (attn && (wg == 1 || wg == 2)) {
        rc = reinterpret_cast<const uint32_t*>(P.rel_coords)[min(tid - 128, 168)];
#pragma unroll
        for (int i = 0; i < 4; i++) w1[i] = reinterpret_cast<const uint4*>(P.cpb_w1)[i];
#pragma unroll
        for (int u = 0; u < 16; u++) w2[u] = reinterpret_cast<const uint32_t*>(P.cpb_w2)[2 * u + half];
#pragma unroll
        for (int rh = 0; rh < 2; rh++) {
            const int* ri = P.rel_idx + (rh ? t1 : t0) * TOK;
#pragma unroll
            for (int j = 0; j < 12; j++) ridx[13 * rh + j] = ri[8 * (j >> 1) + 2 * c + (j & 1)];
            ridx[13 * rh + 12] = ri[48];
        }
    }
    {
        if (tid == 416) {
            const CUtensorMap* maps[4] = {attn ? &smap : &omap, &smap3, &xmapa, &xmapb};
#pragma unroll
            for (int i = 0; i < 4; i++) asm volatile("prefetch.tensormap [%0];\n" :: "l"(reinterpret_cast<uint64_t>(maps[i])) : "memory");
        }
        if (tid == 384) {
            for (int b = 0; b < 4; b++) {
                mbar_init(bars + B_XFULL + b * 8, 2);
                mbar_init(bars + B_QKRAW + b * 8, 4);
                mbar_init(bars + B_VRAW + b * 8, 4);
                mbar_init(bars + B_VFREE + b * 8, 2);
                mbar_init(bars + B_QKFREE + b * 8, 4);
                mbar_init(bars + B_ODONE + b * 8, 4);
            }
            mbar_init(bars + B_MFULL, 1);
            sts32(bars + B_MSTATE, 0);
            sts32(bars + B_MSTATE + 4, 0x7FFFFFFF);
            sts32(bars + B_NTILES, 0x7FFFFFFF);
            sts128(bars + B_DYN, ~0u, ~0u, ~0u, ~0u);
            sts128(bars + B_DYN + 16, ~0u, ~0u, ~0u, ~0u);
            mbar_init(bars + B_GDONE, 4);
            sts32(bars + B_ROWS, 0xFFFFFFFFu);
            mbar_init(bars + B_MCONS, 4);
            mbar_init(bars + B_WFULL, 2);
            mbar_init(bars + B_WRAW, 1);
            mbar_init(bars + B_XCONS, 4);
            for (int b = 0; b < 4; b++) mbar_init(bars + B_STORED + b * 8, 1);
            for (int b = 0; b < 6; b++) {
                mbar_init(sbase + SM_PBAR + b * 8, 1);
                if (PCHUNK) sts32(sbase + SM_PBAR + 48, 0); else
                mbar_init(sbase + SM_PBAR + 48 + b * 8, PSTORE ? 1 : 4);
                mbar_init(sbase + SM_PBAR + 104 + b * 8, 4);
            }
            mbar_init(sbase + SM_PBAR + 96, attn ? 13 : 12);
            if (MPRE && !attn) for (int b = 0; b < 12 * MBUFS; b++) mbar_init(sbase + SM_MBAR + b * 8, 1);
            mbar_init(sbase + SM_PBAR + 56, 12);
            asm volatile("fence.mbarrier_init.release.cluster;\n" ::: "memory");
        }
        if (wg == 3) {
            if (attn && lane < (warp < 3 ? 16 : (4 * O_STRIDE - 3 * V_STRIDE - 13 * GRP) / 16))
                *reinterpret_cast<uint4*>(smem + SM_V + warp * V_STRIDE + 13 * GRP + lane * 16) = make_uint4(0, 0, 0, 0);
            fence_async_smem();
        }
        __syncthreads();
        TR(26, 4 + wg);
            if (attn && tid == 0) {
                const int nw = 4;
                mbar_arrive_expect_tx(bars + B_WRAW, nw * 96 * O_PITCH);
                TR(26, 30);
#pragma unroll
                for (int i = 0; i < 4; i++) if (i < nw) {
                    const int q = (i + pair) & 3;
                    tma_3d(sbase + q * 96 * O_PITCH, &wraw, bars + B_WRAW, 0, 2 * (q >> 1) + half, (q & 1) * 96);
                    TR(26, 31 + i);
                }
                int wh = 0, ww = pair;
#pragma unroll
                for (int j = 0; j < NEARLY; j++) {
                    if (ww < NWS - 1) {
                        const uint32_t bar = bars + B_XFULL + (j ? j - 1 : 0) * 8;
                        if (j >= 2) mbar_arrive(bar);
                        mbar_arrive_expect_tx(bar, 3 * XCH);
#pragma unroll
                        for (int ch = 0; ch < 3; ch++)
                            tma_3d(sbase + SM_QK + ((j + 3) & 3) * XCH + ch * QK_CHUNK, &xmap, bar, ch * 64, 7 * ww + 3, 7 * wh + 3);
                    }
                    ww += P.npair; if (ww >= NWS) { ww -= NWS; wh++; }
                    TR(26, 40 + j);
                    if (j == 1) {
                        mbar_arrive_expect_tx(bars + B_MFULL, 4816);
                        asm volatile("cp.async.bulk.shared::cluster.global.mbarrier::complete_tx::bytes [%0], [%1], 4816, [%2];\n"
                                     :: "r"(sbase + SM_MASK), "l"(reinterpret_cast<const char*>(P.mask) + (((uint32_t)pair * 4802u) & ~15u)),
                                        "r"(bars + B_MFULL) : "memory");
                        mbar_arrive_expect_tx(bars + B_WFULL, 5 * W_ATOM);
#pragma unroll
                        for (int a = 1; a < 6; a++)
                            tma_2d(sbase + SM_WV + a * W_ATOM, &wmap, bars + B_WFULL, 384 + half * 96 + a * 16, 0);
                        TR(26, 50);
                    }
                }
            }
        __syncwarp();
        TR(26, 13);
    }

    auto permute_w = [&]() {
        uint4 w[3][4];
        TR(26, 16 + wg);
        mbar_wait(bars + B_WRAW, 0);
        TR(26, 20 + wg);
#pragma unroll
        for (int it = 0; it < 3; it++) {
            const int o = ((tid >> 5) * 3 + it) * 4 + (lane >> 3);
            const uint8_t* src = smem + ((o / 6) * 8 + (lane & 7)) * O_PITCH + (o % 6) * 16;
#pragma unroll
            for (int m = 0; m < 4; m++) w[it][m] = *reinterpret_cast<const uint4*>(src + (m >> 1) * 192 * O_PITCH + (m & 1) * 96);
        }
        asm volatile("bar.sync 2, 384;\n" ::: "memory");
        if (tid == 0) {
            fence_async_smem();
            TR(26, 24);
            mbar_arrive_expect_tx(bars + B_WFULL, W_ATOM);
            tma_2d(sbase + SM_WV, &wmap, bars + B_WFULL, 384 + half * 96, 0);
        }
#pragma unroll
        for (int it = 0; it < 3; it++) {
            const int o = ((tid >> 5) * 3 + it) * 4 + (lane >> 3);
            const uint32_t d = sbase + (o % 6) * 2 * W_ATOM + ((o / 6) * 8 + (lane & 7)) * 32 + ((lane >> 2) & 1) * 16;
            sts128(d, bf2h(w[it][0].x), bf2h(w[it][1].x), bf2h(w[it][2].x), bf2h(w[it][3].x));
            sts128(d ^ 16, bf2h(w[it][0].y), bf2h(w[it][1].y), bf2h(w[it][2].y), bf2h(w[it][3].y));
            sts128(d + W_ATOM, bf2h(w[it][0].z), bf2h(w[it][1].z), bf2h(w[it][2].z), bf2h(w[it][3].z));
            sts128((d ^ 16) + W_ATOM, bf2h(w[it][0].w), bf2h(w[it][1].w), bf2h(w[it][2].w), bf2h(w[it][3].w));
        }
    };
    static_assert(2 * 192 * O_PITCH <= 13 * W_ATOM, "raw weights");
    const uint32_t nfinish = gridDim.x + (POLLER ? 0 : 2 * P.npair);
#define PROJ_SCHEDULE                                                                                   \
    int bid = blockIdx.x;                                                                               \
    asm volatile("" : "+r"(bid));                      \
    bid = role_of(P, bid);                                                                              \
    const bool at = bid < 2 * P.npair;                                                                  \
    const int tile0 = at ? P.t1 + bid : bid - 2 * P.npair;                                              \
    const int tstep = at ? 2 * P.npair : (int)gridDim.x - 2 * P.npair;                                  \
    const int tend = at ? TILES : P.t1;
    if (wg == 3) {
        asm volatile("setmaxnreg.dec.sync.aligned.u32 %0;\n" :: "n"(REG_H));
#define MST_OFF 0
        if (warp == 1 && attn) {
            const uint16_t mlast = reinterpret_cast<const uint16_t*>(P.mask)[NWINDOWS * TOK * TOK - 1];
            const uint32_t ma = sbase + SM_MASK + 16 + lane * 16, mb = sbase + SM_MASK + min(289 + lane, 299) * 16;
            const uint32_t mc = sbase + SM_MASK + (lane & 7) * 2 + (lane & 8) * 600;
            uint32_t ph = 0, win = pair, fp = 0, nzl = 0;
#pragma unroll 1
            for (int k = 0;; k++) {
                mbar_wait(bars + B_MFULL, fp);
                uint32_t acc = lds16(mc);
                if ((lane & 15) - (win & 7) > 8u) acc = 0;
#pragma unroll
                for (int i = 0; i < 10; i += MRND) {
                    uint32_t w[MRND][4];
#pragma unroll
                    for (int j = 0; j < MRND; j++) if (i + j < 10) lds128(w[j], i + j < 9 ? ma + (i + j) * 512 : mb);
#pragma unroll
                    for (int j = 0; j < MRND; j++) if (i + j < 10) acc |= w[j][0] | w[j][1] | w[j][2] | w[j][3];
                    asm volatile("" : "+r"(acc) :: "memory");
                }
                uint32_t nz = __any_sync(0xffffffffu, (acc & 0x7FFF7FFFu) != 0) ? 1 : 0;
                if (lane == 0) asm volatile("st.volatile.shared.b32 [%0], %1;\n" :: "r"(MST_OFF ? sbase + SM_DUMP : bars + B_MSTATE), "r"(32 * k + 32 - 16 * nz + (2 * win & 14) + fp) : "memory");
                fp ^= 1;
                if (k + 1 == MPRE) {
                    uint32_t tag;
                    asm volatile("ld.relaxed.gpu.global.u32 %0, [%1];\n" : "=r"(tag) : "l"(g_guard) : "memory");
#pragma unroll 1
                    for (uint32_t n = 0; n < (1u << 20); n++) {
                        bool ok = true;
                        nzl = 0;
#pragma unroll
                        for (int j = 0; j < 3; j++) {
                            uint32_t f;
                            asm volatile("ld.relaxed.gpu.global.u32 %0, [%1];\n" : "=r"(f) : "l"(g_mz + pair * 128 + 32 * j + lane) : "memory");
                            ok = ok && ((f | 1) == (tag | 255) || 32 * j + lane < MPRE || 32 * j + lane >= MEND);
                            nzl |= (~f & 1) << j;
                        }
                        if (__all_sync(0xffffffffu, ok)) break;
                        nzl = 7;
                        __nanosleep(RSLEEP);
                    }
                }
                if (k + 1 >= MPRE && k + 1 < MEND) {
                    uint32_t kn = MEND;
#pragma unroll
                    for (int j = 0; j < 3; j++) if ((nzl >> j & 1) && 32 * j + lane > k) kn = min(kn, 32 * j + lane);
                    kn = __reduce_min_sync(0xffffffffu, kn);
                    if (kn > k + 1) {
                        if (nz) { mbar_wait(bars + B_MCONS, ph); ph ^= 1; fence_async_smem(); nz = 0; }
                        if (lane == 0) asm volatile("st.volatile.shared.b32 [%0], %1;\n" :: "r"(bars + B_MSTATE), "r"(32 * kn) : "memory");
                        k = kn - 1;
                        win = pair + k * P.npair;
                    }
                }
                win += P.npair;
                if (k + 1 >= NSTATIC) {
                    uint32_t e = 0xFFFF;
#pragma unroll 1
                    for (uint32_t n = 0; n < (1u << 20); n++) {
                        e = lds16v(bars + B_DYN + (k + 1 - NSTATIC) * 2);
                        if (__all_sync(0xffffffffu, e != 0xFFFF)) break;
                        __nanosleep(RSLEEP);
                    }
                    if (__any_sync(0xffffffffu, e >= POS_END)) break;
                    win = e - (e >> 7) * (128 - NWS);
                }
                if (nz && !MST_OFF) { mbar_wait(bars + B_MCONS, ph); ph ^= 1; fence_async_smem(); }
                if (elect_one()) {
                    uint32_t bytes = 4816;
                    if (win == NWINDOWS - 1) {
                        bytes = 4800;
                        asm volatile("st.shared.u16 [%0], %1;\n" :: "r"(sbase + SM_MASK + 4800), "h"(mlast) : "memory");
                    }
                    TR(25, k + 1);
                    mbar_arrive_expect_tx(bars + B_MFULL, bytes);
                    asm volatile("cp.async.bulk.shared::cluster.global.mbarrier::complete_tx::bytes [%0], [%1], %2, [%3];\n"
                                 :: "r"(sbase + SM_MASK),
                                    "l"(reinterpret_cast<const char*>(P.mask) + (((uint32_t)win * 4802u) & ~15u)),
                                    "r"(bytes), "r"(bars + B_MFULL) : "memory");
                    if (MPF && half == (win & 1) && win + MPF * P.npair < NWINDOWS && (!MPRE || k + 1 + MPF < MPRE || k + 1 >= MEND))
                        asm volatile("cp.async.bulk.prefetch.L2.global [%0], %1;\n"
                                     :: "l"(reinterpret_cast<const char*>(P.mask) + (((uint32_t)(win + MPF * P.npair) * 4802u) & ~15u)),
                                        "r"(4800) : "memory");
                }
                __syncwarp();
            }
        }
        if (!elect_one()) return;
        if (warp == 0) {
          if (attn) {
            int kmax = 1 << 20, rows = 1 << 30;
            uint32_t cur = pair, pos1 = pos_add(cur, P.npair), pos2 = pos_add(pos1, P.npair);
#pragma unroll 1
            for (int k = -4; k + 4 <= kmax; k++) {
                const int row0 = (k + 4) * TOK;
                const uint32_t dst = sbase + SM_QK + ((k + 3) & 3) * XCH, bar = bars + B_XFULL + ((row0 >> 6) & 3) * 8;
                const bool alone = (row0 & 63) >= 64 - TOK && (row0 & 63) < TOK;
                const int wh = cur >> 7, ww = cur & 127;
                uint32_t claim = NWINDOWS;
                if (k + 7 >= NSTATIC && k + 7 < NSTATIC + 15 && pos2 < POS_END)
                    asm volatile("atom.relaxed.gpu.global.add.u32 %0, [%1], 1;\n" : "=r"(claim) : "l"(g_next + half) : "memory");
                const int x0 = 7 * ww + 3, y0 = 7 * wh + 3;
                const bool done = k < NEARLY - 4 && ww < NWS - 1;
                if (k >= 0) mbar_wait(bars + B_QKFREE + ((k + 3) & 3) * 8, (k >> 2) & 1);
                if (alone && !done) mbar_arrive(bar);
                if (row0 >= rows || ((EXP & 32) && k >= 0)) {
                    mbar_arrive(bar);
                    continue;
                }
                TR(20, k + 4);
                const bool inner = wh < NWS - 1 && ww < NWS - 1;
                if (done) {
                } else if (XSPLIT && inner && (row0 & 63) >= 64 - 21) {
                    const uint32_t bar2 = bars + B_XFULL + (((row0 >> 6) + 1) & 3) * 8;
                    mbar_arrive_expect_tx(bar, 3 * 21 * 128);
#pragma unroll
                    for (int ch = 0; ch < 3; ch++) tma_3d(dst + ch * QK_CHUNK, &xmapa, bar, ch * 64, x0, y0);
                    asm volatile("mbarrier.expect_tx.relaxed.cta.shared::cta.b64 [%0], %1;\n" :: "r"(bar2), "r"(3 * 28 * 128) : "memory");
#pragma unroll
                    for (int ch = 0; ch < 3; ch++) tma_3d(dst + ch * QK_CHUNK + 21 * 128, &xmapb, bar2, ch * 64, x0, y0 + 3);
                } else if (inner) {
                    mbar_arrive_expect_tx(bar, 3 * XCH);
#pragma unroll
                    for (int ch = 0; ch < 3; ch++) tma_3d(dst + ch * QK_CHUNK, &xmap, bar, ch * 64, x0, y0);
                } else if (ww < NWS - 1) {
                    mbar_arrive_expect_tx(bar, 3 * XCH);
#pragma unroll
                    for (int ch = 0; ch < 3; ch++) {
                        tma_3d(dst + ch * QK_CHUNK, &xmapb, bar, ch * 64, x0, y0);
                        tma_3d(dst + ch * QK_CHUNK + 28 * 128, &xmapa, bar, ch * 64, x0, 0);
                    }
                } else {
                    mbar_arrive_expect_tx(bar, 3 * XCH);
                    const int x1 = (ww == NWS - 1) ? 0 : x0 + 4;
#pragma unroll 1
                    for (int i = 0; i < 7; i++) {
                        const int y = (y0 + i >= IMG) ? y0 + i - IMG : y0 + i;
#pragma unroll
                        for (int ch = 0; ch < 3; ch++) {
                            tma_3d(dst + ch * QK_CHUNK + i * 896, &xmap4, bar, ch * 64, x0, y);
                            tma_3d(dst + ch * QK_CHUNK + i * 896 + 512, &xmap3, bar, ch * 64, x1, y);
                        }
                    }
                }
                if (pos1 < POS_END) cur = pos1;
                pos1 = pos2;
                if (k + 7 < NSTATIC) {
                    pos2 = pos_add(pos2, P.npair);
                } else if (pos2 < POS_END) {
                    sts32(bars + B_NTILES + 4, claim);
                    const uint32_t w = lds32v(bars + B_NTILES + 4) + NSTATIC * P.npair;
                    pos2 = w < NWINDOWS ? w + __umulhi(w, 58835169u) * (128 - NWS) : POS_END;
                    sts16(bars + B_DYN + (k + 7 - NSTATIC) * 2, pos2);
                    if (pos2 == POS_END) {
                        rows = (row0 + 3 * TOK + 63) & ~63;
                        kmax = (rows + 63) / TOK;
                        sts32(bars + B_MSTATE + 4, k + 7);
                        sts32(bars + B_NTILES, rows >> 6);
                        if (role < SM_STAGE / 1024)
                            asm volatile("cp.async.bulk.prefetch.L2.global [%0], 1024;\n" :: "l"(g_wo + role * 1024) : "memory");
                    }
                }
                if (!NOPF && half == 0 && pos2 < POS_END) {
#pragma unroll
                    for (int ch = 0; ch < 3; ch++)
                        asm volatile("cp.async.bulk.prefetch.tensor.3d.L2.global.tile [%0, {%1, %2, %3}];\n"
                                     :: "l"(reinterpret_cast<uint64_t>(&xmap)), "r"(ch * 64), "r"(7 * (pos2 & 127) + 3), "r"(7 * (pos2 >> 7) + 3)
                                     : "memory");
                }
            }
            {
#pragma unroll 1
                for (uint32_t n = 0; n < (1u << 22); n++) {
                    uint32_t a, b;
                    asm volatile("ld.relaxed.gpu.global.u32 %0, [%1];\n" : "=r"(b) : "l"(g_guard) : "memory");
                    asm volatile("ld.acquire.gpu.global.u32 %0, [%1];\n" : "=r"(a) : "l"(g_guard + 3) : "memory");
                    if (a == (b | 255)) break;
                }
                asm volatile("fence.proxy.async.global;\n" ::: "memory");
                mbar_arrive_expect_tx(bars + B_WRAW, SM_STAGE);
                mbar_wait(bars + B_GDONE, 0);
#pragma unroll
                for (int i = 0; i < WOSPLIT; i++)
                    asm volatile("cp.async.bulk.shared::cluster.global.mbarrier::complete_tx::bytes [%0], [%1], %2, [%3];\n"
                                 :: "r"(sbase + SM_WO + i * (SM_STAGE / WOSPLIT)), "l"(g_wo + i * (SM_STAGE / WOSPLIT)),
                                    "n"(SM_STAGE / WOSPLIT), "r"(bars + B_WRAW) : "memory");
            }
          }
            mbar_wait(sbase + SM_PBAR + 96, 0);
            ST(15);
            fence_async_smem();
            PROJ_SCHEDULE
            int st = 0, ready = -1, want = -6 * PSM, freed = 0;
            uint32_t ph = 1;
#pragma unroll 1
            for (int t = tile0; t < tend; t += tstep) {
                const int p0 = (t < TILES_A) ? SEG_B + 64 * (t & PWRAP) : 64 * (t - TILES_A);
                const int w1 = (t < TILES_A) ? min((64 * t + 63) / (7 * IMG), NWS - 1) : NWS - 1;
#pragma unroll 1
                for (uint32_t n = 0; n < (1u << 24) && ready < w1; n++) ready = (int)lds32v(bars + B_ROWS);
#pragma unroll
                for (int ch = 0; ch < PSM; ch++) {
                    want++;
#pragma unroll 1
                    for (uint32_t n = 0; n < (1u << 22) && freed < want; n++) freed = (int)lds32v(sbase + SM_PBAR + 48);
                    if (ch == 0) mbar_arrive_expect_tx(sbase + SM_PBAR + st * 8, STAGE_BYTES);
                    tma_2d(sbase + SM_STAGE + st * STAGE_BYTES + ch * 8192, &omap, sbase + SM_PBAR + st * 8, ch * 64, p0);
                    if (ch == 0) {
#pragma unroll
                        for (int c2 = PSM; c2 < 3; c2++)
                            tma_2d(sbase + SM_STAGE + st * STAGE_BYTES + c2 * 8192, &omap, sbase + SM_PBAR + st * 8, c2 * 64, p0);
                    }
                }
                if (++st == 6) st = 0;
            }
            if (!POLLER) finish(nfinish);
        } else if (warp == 2 && (POLLER || attn)) {
            CK(0);
            uint32_t rows = 0, cur = attn ? pair : POS_END;
#pragma unroll 1
            for (int k = 0; cur < POS_END; k++) {
                const uint32_t wh = cur >> 7;
                mbar_wait(bars + B_STORED + (k & 1) * 8, (k >> 1) & 1);
                mbar_arrive(bars + B_PUBD + (k & 1) * 8);
                rows = rows * 128 + wh + 1;
                cur = k + 1 < NSTATIC ? pos_add(cur, P.npair) : lds16v(bars + B_DYN + (k + 1 - NSTATIC) * 2);
                if (rows >= (1u << (7 * PUBN - 7)) || k < 2 || cur >= (NWS - PUBT) * 128) {
                    asm volatile("fence.acq_rel.gpu;\n" ::: "memory");
#pragma unroll 1
                    for (; rows; rows >>= 7)
                        asm volatile("red.relaxed.gpu.global.add.u32 [%0], 1;\n" :: "l"(g_cnt + ((rows & 127) - 1)) : "memory");
                }
                TR(24, k);
                CK(k + 1);
                if (k == 30) { ST(9); SC(29); }
                if (k == 60) { ST(10); SC(30); }
                if (k == 90) { ST(11); SC(31); }
            }
            ST(14);
            const int r1 = attn ? NWS - 1 : min((64 * P.t1 - 1) / (7 * IMG), NWS - 1);
#pragma unroll 1
            for (int r = attn ? min(64 * P.t1 / (7 * IMG), NWS - 1) : 0; r <= r1; r++) {
#pragma unroll 1
                for (uint32_t n = 0; n < (1u << 22); n++) {
                    uint32_t a;
                    asm volatile("ld.acquire.gpu.global.u32 %0, [%1];\n" : "=r"(a) : "l"(g_cnt + r) : "memory");
                    if (a >= P.need) break;
                    __nanosleep(64);
                }
                asm volatile("fence.proxy.async.global;\n" ::: "memory");
                asm volatile("st.volatile.shared.b32 [%0], %1;\n" :: "r"(bars + B_ROWS), "r"(r) : "memory");
                if (r >= 66) ST(20 + r - 66);
            }
            finish(nfinish);
        } else if (warp == 3 && attn) {
            for (int t = 0; t < 3; t++) mbar_arrive_n(bars + B_VFREE + t * 8, 2);
            uint32_t cur = pair;
#pragma unroll 1
            for (int k = 0; cur < POS_END; k++) {
                const int wh = cur >> 7, ww = cur & 127;
                const uint32_t src = sbase + SM_V + (k & 3) * O_STRIDE;
                const int x0 = 7 * ww + 3, y0 = 7 * wh + 3;
                mbar_wait(bars + B_ODONE + (k & 3) * 8, (k >> 2) & 1);
                fence_async_smem();
                TR(22, k);
#if !(EXP & 4)
                tma_store_4d(&smap, src, 0, half, x0, y0);
#endif
                if (ww == NWS - 1) {
#pragma unroll 1
                    for (int i = 0; i < 7; i++) {
                        char* const d = reinterpret_cast<char*>(P.out) + (uint32_t)((y0 + i >= IMG ? y0 + i - IMG : y0 + i) * IMG) * 384u + half * 192;
#pragma unroll
                        for (int j = 0; j < 3; j++)
                            asm volatile("cp.async.bulk.global.shared::cta.bulk_group [%0], [%1], 192;\n"
                                         :: "l"(d + j * 384), "r"(src + (7 * i + 4 + j) * O_PITCH) : "memory");
                    }
                }
                if (wh == NWS - 1) {
                    char* d = reinterpret_cast<char*>(P.out) + (uint32_t)x0 * 384u + half * 192;
#pragma unroll 1
                    for (int j = 0; j < (ww == NWS - 1 ? 4 : 7); j++, d += 384) {
#pragma unroll
                        for (int i = 0; i < 3; i++)
                            asm volatile("cp.async.bulk.global.shared::cta.bulk_group [%0], [%1], 192;\n"
                                         :: "l"(d + i * IMG * 384), "r"(src + (28 + 7 * i + j) * O_PITCH) : "memory");
                    }
                }
                asm volatile("cp.async.bulk.commit_group;\n" ::: "memory");
                asm volatile("cp.async.bulk.wait_group.read 0;\n" ::: "memory");
                {
                    const int row0 = (k + 4) * TOK;
                    mbar_arrive_n(bars + B_VFREE + ((row0 >> 6) & 3) * 8, ((row0 & 63) >= 64 - TOK && (row0 & 63) < TOK) ? 2 : 1);
                }
                TR(23, k);
                cur = k + 1 < NSTATIC ? pos_add(cur, P.npair) : lds16v(bars + B_DYN + (k + 1 - NSTATIC) * 2);
                asm volatile("cp.async.bulk.wait_group 0;\n" ::: "memory");
                asm volatile("fence.proxy.async.global;\n" ::: "memory");
                mbar_wait(bars + B_PUBD + (k & 1) * 8, ((k >> 1) + 1) & 1);
                mbar_arrive(bars + B_STORED + (k & 1) * 8);
            }
            mbar_arrive(sbase + SM_PBAR + 96);
        }
        if (PSTORE && warp == 1) {
            PROJ_SCHEDULE
            int st = 0, prev = -1, done = 0;
            uint32_t ph = 0;
            if (bid == gridDim.x - 1) { g_guard[2] = 0; __threadfence(); }
#pragma unroll 1
            for (int t = tile0; t < tend; t += tstep) {
                const int p0 = (t < TILES_A) ? SEG_B + 64 * (t & PWRAP) : 64 * (t - TILES_A);
                mbar_wait(sbase + SM_PBAR + 104 + st * 8, ph);
                fence_async_smem();
                if (!at) TR(22, (t - tile0) / tstep);
                if (!at && done == 40 * PSM) ST(9);
                if (!at && done == 90 * PSM) ST(10);
                if (!at && done == 130 * PSM) ST(11);
                if (!at && done == 140 * PSM) ST(12);
#pragma unroll
                for (int ch = 0; ch < PSM; ch++) {
                    asm volatile("cp.async.bulk.tensor.2d.global.shared::cta.tile.bulk_group.L2::cache_hint [%0, {%2, %3}], [%1], %4;\n"
                                 :: "l"(reinterpret_cast<uint64_t>(t < TILES_A ? &omap : &omapb)),
                                    "r"(sbase + SM_STAGE + st * STAGE_BYTES + ch * 8192), "r"(ch * 64), "r"(p0), "l"(EVICT_FIRST) : "memory");
                    asm volatile("cp.async.bulk.commit_group;\n" ::: "memory");
                    asm volatile("cp.async.bulk.wait_group.read %0;\n" :: "n"(PCHUNK) : "memory");
                    asm volatile("st.volatile.shared.b32 [%0], %1;\n" :: "r"(sbase + SM_PBAR + 48), "r"(max(done + ch + 1 - PCHUNK, 0)) : "memory");
                }
                done += PSM;
                if (!mbar_test(sbase + SM_PBAR + 104 + (st == 5 ? 0 : st + 1) * 8, st == 5 ? ph ^ 1 : ph)) {
                    if (PCHUNK > 1) {
                        asm volatile("cp.async.bulk.wait_group.read 1;\n" ::: "memory");
                        asm volatile("st.volatile.shared.b32 [%0], %1;\n" :: "r"(sbase + SM_PBAR + 48), "r"(done - 1) : "memory");
                    }
                    asm volatile("cp.async.bulk.wait_group.read 0;\n" ::: "memory");
                    asm volatile("st.volatile.shared.b32 [%0], %1;\n" :: "r"(sbase + SM_PBAR + 48), "r"(done) : "memory");
                }
                prev = st;
                if (++st == 6) { st = 0; ph ^= 1; }
            }
            mbar_wait(sbase + SM_PBAR + 56, 0);
            asm volatile("fence.acq_rel.gpu;\n" ::: "memory");
            asm volatile("cp.async.bulk.wait_group 0;\n" ::: "memory");
            asm volatile("red.relaxed.gpu.global.add.u32 [%0], %1;\n" :: "l"(g_guard), "r"(bid == 0 ? 257 - gridDim.x : 1) : "memory");
            TR(30, 0);
            ST(13);
        }
        return;
    }
    bool bad = false;
    if (!attn) {
        asm volatile("setmaxnreg.inc.sync.aligned.u32 160;\n");
        uint32_t lo = 0x7F807F80u, hi = 0;
#pragma unroll 1
        for (int i = (role - 2 * P.npair) * 384 + tid; i < 192 * 96; i += (gridDim.x - 2 * P.npair) * 384) {
            const bool o = i >= 192 * 72;
            const uint4 w = o ? reinterpret_cast<const uint4*>(P.wo)[i - 192 * 72] : reinterpret_cast<const uint4*>(P.wqkv)[i];
            const uint32_t m = __vmaxu2(__vmaxu2(w.x & 0x7FFF7FFFu, w.y & 0x7FFF7FFFu), __vmaxu2(w.z & 0x7FFF7FFFu, w.w & 0x7FFF7FFFu));
            lo = __vminu2(lo, m);
            hi = __vmaxu2(hi, m + (o ? 0x02000200u : 0u));
        }
        bad = __vminu2(lo, 0x38803880u) != 0x38803880u || __vmaxu2(hi, 0x42004200u) != 0x42004200u;
    } else if (wg == 0) {
        asm volatile("setmaxnreg.inc.sync.aligned.u32 %0;\n" :: "n"(REG_G));
        float qs = 1.f;
        if (c < 2) qs = round_bf16(expf(round_bf16(fminf(fmaxf(__bfloat162float(P.logit_scale[2 * half + c]), -100.f), 4.6052f)))) * LOG2E;
        uint32_t xa[8][4];
        uint32_t qk[2][48], vv[24];
        uint32_t rho = warp * 16 + (lane & 15), rq = warp * 16 + g;
        uint32_t rx = rho + 3 * TOK - (rho >= TOK ? 4 * TOK : 0);
        uint32_t hi = lane >> 4, lane0 = lane == 0, c2 = 2 * c;
        asm volatile("" : "+r"(hi), "+r"(lane0), "+r"(c2));
        auto row_addr = [&](uint32_t (&ax)[4], uint32_t r) {
            ax[0] = sbase + SM_QK + r * 128 + (((r & 7) ^ hi) << 4);
#pragma unroll
            for (int i = 1; i < 4; i++) ax[i] = ax[0] ^ (32 * i);
        };
#define XADDR(ax, s) ((ax)[((s) & 3) ^ (((s) >> 1) & 2)] + ((s) >> 2) * QK_CHUNK)
        uint64_t descW = make_desc(sbase, W_ATOM, 256, 3);
        const uint32_t zero = (uint32_t)P.z1;
        const uint32_t vbase = sbase + SM_V + (lane >> 4) * GRP;
        uint32_t ones = 0x3C003C00u | zero, ones2 = ones | (zero >> 1);
        asm volatile("" : "+r"(ones), "+r"(ones2));
        const uint32_t mh[2] = {0xFFFF0000u, 0xFFFF0000u}, ml[2] = {0x10000u, 0x10000u};
        uint32_t raw[48], xb[4][4];
        auto cvt = [&](auto& dst, int d0, const uint32_t (&raw)[48], int s0) {
#pragma unroll
            for (int s = 0; s < 4; s++) {
#pragma unroll
                for (int i = 0; i < 4; i++)
                    dst[d0 + s][i] = pack_f16(__uint_as_float(raw[4 * (s0 + s) + i] * ml[i & 1]), __uint_as_float(raw[4 * (s0 + s) + i] & mh[i & 1]));
                reg_fence(dst[d0 + s]);
            }
        };
        uint32_t ax[4];
        auto load_x = [&](int s0) {
#pragma unroll
            for (int s = s0; s < s0 + 4; s++) ldsm_x4(reinterpret_cast<uint32_t (&)[4]>(raw[4 * s]), XADDR(ax, s));
        };
        auto next_x = [&]() {
            row_addr(ax, rx);
            rx += 64;
            if (rx >= 4 * TOK) rx -= 4 * TOK;
        };
        permute_w();
        TR(26, 10);
        mbar_wait(bars + B_XFULL, 0);
        next_x();
        load_x(0); load_x(4); load_x(8);
        cvt(xa, 0, raw, 0); cvt(xa, 4, raw, 4); cvt(xb, 0, raw, 8);
        __syncwarp();
        mbar_arrive_if(bars + B_QKFREE + 24, lane0);
        TR(26, 8);
        asm volatile("bar.sync 7, 384;\n" ::: "memory");
        fence_async_smem();
        TR(26, 9);
        wgmma_fence();
        mma_qk_first<SM_WA, 0>(qk[0], xa, descW);
        mma_qk_next<SM_WA + 2048, 4>(qk[0], xa, descW);
        mma_qk_next<SM_WA + 4096, 0>(qk[0], xb, descW);
        wgmma_commit();
        TR(26, 11);
        asm volatile("bar.sync 11, 384;\n" ::: "memory");
        fence_async_smem();
        TR(26, 12);
        wgmma_fence();
        mma_v_first<SM_WV, 0>(vv, xa, descW);
        mma_v_next<SM_WV + 2048, 4>(vv, xa, descW);
        wgmma_commit();
        wgmma_wait<0>();
        ST(1); SC(28);
        uint32_t xok = 0, range = 0;
        int ntiles;
        auto body = [&](auto U_, int t) {
            constexpr int U = decltype(U_)::value;
            uint32_t (&cur)[48] = qk[U];
            uint32_t (&nxt)[48] = qk[U ^ 1];
            descW += P.z1;
            const uint32_t bt = bars + (t & 3) * 8, pt = (t >> 2) & 1;
            TR(1, t);
            wgmma_fence();
            mma_v_next<SM_WV + 4096, 0>(vv, xb, descW);
            wgmma_commit();
            next_x();
            mbar_wait_unless(xok, bars + ((t + 1) & 3) * 8 + B_XFULL, ((t + 1) >> 2) & 1);
            TR(2, t);
            load_x(0);
            load_x(4);
            uint32_t av = vbase + rho * 16 + ((rho * 1338) >> 16) * (V_STRIDE - GRP);
            uint32_t aq[2];
            aq[0] = sbase + SM_QK + rq * 128 + (((rq & 7) ^ c2) << 4);
            aq[1] = aq[0] + 1024;
            if (rq >= 4 * TOK - 8) aq[1] = (aq[1] - QK_CHUNK) ^ 64;
            rho += 64;
            if (rho >= 4 * TOK) rho -= 4 * TOK;
            rq += 64;
            if (rq >= 4 * TOK) rq -= 4 * TOK;
            asm volatile("" : "+r"(av), "+r"(aq[0]), "+r"(aq[1]), "+r"(rho), "+r"(rq));
            cvt(xa, 0, raw, 0);
            wgmma_fence();
            mma_qk_first<SM_WA, 0>(nxt, xa, descW);
            wgmma_commit();
            load_x(8);
            __syncwarp();
            mbar_arrive_if(bars + B_XCONS, lane0);
            const uint32_t vok = mbar_test(bt + B_VFREE, pt);
            ntiles = lds32v(bars + B_NTILES);
            cvt(xa, 4, raw, 4);
            TR(5, t);
            wgmma_fence();
            mma_qk_next<SM_WA + 2048, 4>(nxt, xa, descW);
            wgmma_commit();
            wgmma_wait<2>();
            reg_fence(cur);
            reg_fence(vv);
            TR(6, t);
            mbar_wait_unless(vok, bt + B_VFREE, pt);
            if (U == 0 && t == 2) asm volatile("bar.sync 3, 384;\n" ::: "memory");
#pragma unroll
            for (int p = 0; p < 6; p++)
                stsm_x4(av + (p < 3 ? 2 * p : 2 * p + 1) * GRP, vv[4 * p], vv[4 * p + 1], vv[4 * p + 2], vv[4 * p + 3]);
            stsm_x2(av + 6 * GRP, ones, ones2);
            __syncwarp();
            mbar_arrive_if(bt + B_VRAW, lane0);
            const uint32_t cok = mbar_test(bars + B_XCONS, U);
            TR(4, t);
            cvt(xb, 0, raw, 8);
            uint32_t ss[4];
#pragma unroll
            for (int i = 0; i < 4; i++) ss[i] = hmul2_f16(cur[i], cur[i]);
#pragma unroll
            for (int i = 4; i < ((EXP & 16) ? 4 : 48); i++) ss[i & 3] = hfma2_f16(cur[i], cur[i], ss[i & 3]);
            ss[0] = hadd2_f16(ss[0], ss[2]);
            ss[1] = hadd2_f16(ss[1], ss[3]);
            const float s0 = f16lo(ss[0]) + f16hi(ss[0]) + 1e-12f, s1 = f16lo(ss[1]) + f16hi(ss[1]) + 1e-12f;
            range = __viaddmax_u32(__float_as_uint(s0), 0u - SS_MIN, __viaddmax_u32(__float_as_uint(s1), 0u - SS_MIN, range));
            const float f0 = rsqrt_ftz(s0) * qs, f1 = rsqrt_ftz(s1) * qs;
            uint32_t f2[2] = {pack_f16_sat(f0, f0), pack_f16_sat(f1, f1)};
            reg_fence(f2);
            sched_fence16(zero, xb, f2[0], f2[1]);
            wgmma_fence();
            mma_v_first<SM_WV, 0>(vv, xa, descW);
            wgmma_commit();
            mbar_wait_unless_dep(cok, bars + B_XCONS, U, zero, f2[0], f2[1], aq[0], aq[1]);
            TR(7, t);
#pragma unroll
            for (int u = 0; u < 6; u++)
#pragma unroll
                for (int r = 0; r < 2; r++)
                    sts128((aq[r] ^ ((u & 1) * 16 + (u & 2) * 32)) + (u >> 1) * QK_CHUNK,
                           hmul2_f16(cur[8 * u + r], f2[r]), hmul2_f16(cur[8 * u + 2 + r], f2[r]),
                           hmul2_f16(cur[8 * u + 4 + r], f2[r]), hmul2_f16(cur[8 * u + 6 + r], f2[r]));
            __syncwarp();
            mbar_arrive_if(bt + B_QKRAW, lane0);
            TR(3, t);
            wgmma_fence();
            mma_v_next<SM_WV + 2048, 4>(vv, xa, descW);
            wgmma_commit();
            xok = mbar_test(bars + ((t + 2) & 3) * 8 + B_XFULL, ((t + 2) >> 2) & 1);
            mma_qk_next<SM_WA + 4096, 0>(nxt, xb, descW);
            wgmma_commit();
            TR(0, t + 1);
            wgmma_wait<GORD == 4 ? 2 : 1>();
        };
        for (int t = 0;; t += 2) {
            body(std::integral_constant<int, 0>(), t);
            if (__any_sync(0xffffffffu, t + 1 >= ntiles)) { wgmma_wait<0>(); reg_fence(qk[1]); break; }
            body(std::integral_constant<int, 1>(), t + 1);
            if (__any_sync(0xffffffffu, t + 2 >= ntiles)) { wgmma_wait<0>(); reg_fence(qk[0]); break; }
        }
        reg_fence(vv);
        bad = range >= F32_INF - SS_MIN;
        __syncwarp();
        mbar_arrive_if(bars + B_GDONE, lane0);
        asm volatile("setmaxnreg.dec.sync.aligned.u32 160;\n");
    } else {
        if (REG_A > 128) asm volatile("setmaxnreg.inc.sync.aligned.u32 %0;\n" :: "n"(REG_A));
        if (REG_A < 128) asm volatile("setmaxnreg.dec.sync.aligned.u32 %0;\n" :: "n"(REG_A));
        {
            const float c0 = bf16lo(rc), c1 = bf16hi(rc);
            float a0 = 0.f, a1 = 0.f;
#pragma unroll
            for (int u = 0; u < 16; u++) {
                const uint32_t p = reinterpret_cast<const uint32_t*>(w1)[u >> 1], q = reinterpret_cast<const uint32_t*>(w1)[8 + (u >> 1)];
                float h = round_bf16(c0 * ((u & 1) ? bf16hi(p) : bf16lo(p)) + c1 * ((u & 1) ? bf16hi(q) : bf16lo(q)));
                h = fmaxf(h, 0.f);
                a0 += h * bf16lo(w2[u]);
                a1 += h * bf16hi(w2[u]);
            }
            const float s0 = round_bf16(__fdividef(1.f, 1.f + expf(-round_bf16(a0))));
            const float s1 = round_bf16(__fdividef(1.f, 1.f + expf(-round_bf16(a1))));
            if (tid - 128 < 169) sts32(sbase + SM_TAB + (tid - 128) * 4, pack_f16(16.f * LOG2E * s0, 16.f * LOG2E * s1));
        }
        permute_w();
        asm volatile("bar.arrive 7, 384;\n" ::: "memory");
        {
            mbar_wait(bars + B_WFULL, 0);
#pragma unroll 1
            for (int i = 0; i < 9 - 9 * T_NOWV; i++) {
                uint4* q = reinterpret_cast<uint4*>(smem + SM_WV + (tid - 128) * 16 + i * 4096);
                const uint4 w = *q;
                *q = make_uint4(bf2h(w.x), bf2h(w.y), bf2h(w.z), bf2h(w.w));
            }
            asm volatile("bar.arrive 11, 384;\n" ::: "memory");
        }
        asm volatile("bar.sync 1, 256;\n" ::: "memory");
        uint32_t bias[28];
        {
            const uint32_t* tab = reinterpret_cast<const uint32_t*>(smem + SM_TAB);
#pragma unroll
            for (int rh = 0; rh < 2; rh++) {
#pragma unroll
                for (int j = 0; j < 6; j++) {
                    const uint32_t lo = tab[min(max(ridx[13 * rh + 2 * j], 0), 168)];
                    const uint32_t hi = tab[min(max(ridx[13 * rh + 2 * j + 1], 0), 168)];
                    bias[2 * j + rh]      = prmt(lo, hi, 0x5410);
                    bias[14 + 2 * j + rh] = prmt(lo, hi, 0x7632);
                }
                const uint32_t l = (c == 0) ? tab[min(max(ridx[13 * rh + 12], 0), 168)] : 0xFC00FC00u;
                bias[12 + rh] = (l & 0xFFFFu) | 0xFC000000u;
                bias[26 + rh] = (l >> 16) | 0xFC000000u;
            }
        }
#pragma unroll
        for (int i = 0; i < 28; i++)
            if (warp * 16 + g + (i & 1) * 8 >= TOK && i % 14 < 12) bias[i] = 0xFC00FC00u;
        reg_fence(bias);
        asm volatile("bar.arrive 3, 384;\n" ::: "memory");
        const int orow = warp * 16 + (lane & 7);
        const bool ov = orow < TOK;
        const uint32_t orel = sbase + (ov ? SM_V + orow * O_PITCH + (OONE == 2 && orow >= 28 ? 64 : 0) : SM_DUMP + ((lane + (OONE == 2 ? 7 : 3)) & 7) * 16) + (lane >> 3) * 16;
        const uint32_t oup = (OONE == 2 && warp == 1) ? (lane & 4) * 16 : 0;
        const uint32_t omul = ov ? O_STRIDE : 0;
        const uint64_t descK0 = make_desc(sbase + SM_QK, 16, 1024, 1);
        const uint64_t descV0 = make_desc(sbase + SM_V, 128, GRP, 0);
        const uint32_t mrel = sbase + SM_MASK + t0 * 98 + c * 4;
        const uint32_t mrow = (warp < 3) ? 784 : 0;
        const uint32_t pmask = (c == 0) ? 0xFFFFu : 0u;

        uint32_t mstate = 0;
        int nwin;
        const uint32_t barw = bars + (wg - 1) * 8;
        const uint64_t descKw = descK0 + (uint64_t)((wg - 1) * (XCH >> 4)), descVw = descV0 + (uint64_t)((wg - 1) * (V_STRIDE >> 4));
        uint32_t oa = orel + (wg - 1) * omul;
        const uint32_t oflip = oa ^ (oa + 2 * omul);
        uint32_t qok = 0;
        const uint32_t zero = (uint32_t)P.z1;
        auto window = [&](auto IT_, int k) {
            constexpr int IT = decltype(IT_)::value;
            const uint32_t bar = barw + 16 * IT;
            const int tl = (k * TOK + TOK - 1) >> 6, tn = ((k + 2) * TOK + TOK - 1) >> 6;
            const uint32_t bt = bars + (tl & 3) * 8, pt = (tl >> 2) & 1;
            TR(8, k);
            uint32_t sc0[14], sc1[14];
#pragma unroll
            for (int i = 0; i < 14; i++) { sc0[i] = bias[i]; sc1[i] = bias[14 + i]; }
            if (mstate < 32 * k + 32) {
#pragma unroll 1
                for (uint32_t n = 0; n < (1u << 22) && mstate < 32 * k + 16; n++) mstate = lds32v(bars + B_MSTATE);
                if (mstate < 32 * k + 32) {
                    mbar_wait(bars + B_MFULL, mstate & 1);
                    const uint32_t ma = mrel + (mstate & 14);
#pragma unroll
                    for (int i = 0; i < 14; i++) {
                        const uint32_t lo = lds16(ma + (i & 1) * mrow + (i >> 1) * 16);
                        const uint32_t hi = i < 12 ? lds16(ma + (i & 1) * mrow + (i >> 1) * 16 + 2) : 0u;
                        const uint32_t mk = pack_f16(__uint_as_float(lo << 16), __uint_as_float(hi << 16));
                        sc0[i] = hfma2_f16(mk, 0x3DC53DC5u, sc0[i]);
                        sc1[i] = hfma2_f16(mk, 0x3DC53DC5u, sc1[i]);
                    }
                    __syncwarp();
                    if (lane == 0) mbar_arrive(bars + B_MCONS);
                }
            }
            reg_fence(sc0);
            reg_fence(sc1);
            TR(10, k);
            mbar_wait_unless(qok, bt + B_QKRAW, pt);
            fence_async_smem();
            TR(11, k);
            wgmma_fence();
#if !(EXP & 128)
            mma_s0_f16<2 * IT * XCH, 2 * IT * XCH>(sc0, descKw, descKw);
            mma_s1_f16<2 * IT * XCH, 2 * IT * XCH>(sc1, descKw, descKw);
#endif
            wgmma_commit();
            const uint32_t vok = mbar_test(bt + B_VRAW, pt);
            uint32_t m[2];
            auto rowmax = [&](const uint32_t (&S)[14], int h) {
                uint32_t a[2];
#pragma unroll
                for (int o = 0; o < 2; o++)
                    a[o] = hmax2_f16(hmax2_f16(hmax2_f16(hmax2_f16(S[o], S[2 + o]), S[4 + o]), hmax2_f16(hmax2_f16(S[6 + o], S[8 + o]), S[10 + o])), S[12 + o]);
                m[h] = hmax2_f16(prmt(a[0], a[1], 0x5410), prmt(a[0], a[1], 0x7632));
            };
            wgmma_wait<0>();
            reg_fence(sc0);
            reg_fence(sc1);
            if (lane == 0) mbar_arrive(bar + B_QKFREE);
            TR(12, k);
            rowmax(sc0, 0);
            rowmax(sc1, 1);
#pragma unroll
            for (int i = 0; i < 2; i++) m[i] = hmax2_f16(m[i], __shfl_xor_sync(0xffffffffu, m[i], 1));
#pragma unroll
            for (int i = 0; i < 2; i++) m[i] = hmax2_f16(m[i], __shfl_xor_sync(0xffffffffu, m[i], 2));
            auto probs = [&](const uint32_t (&S)[14], uint32_t mm, uint32_t (&pa)[4][4]) {
#pragma unroll
                for (int j = 0; j < 6; j++) {
                    pa[j >> 1][(j & 1) * 2]     = ex2_f16x2(hsub2_bc<0>(S[2 * j], mm));
                    pa[j >> 1][(j & 1) * 2 + 1] = ex2_f16x2(hsub2_bc<1>(S[2 * j + 1], mm));
                }
                pa[3][0] = ex2_f16lo(hsub2_bc<0>(S[12], mm)) & pmask;
                pa[3][1] = ex2_f16lo(hsub2_bc<1>(S[13], mm)) & pmask;
                pa[3][2] = 0u; pa[3][3] = 0u;
                reg_fence(pa);
            };
            uint32_t pa0[4][4], pa1[4][4];
            uint32_t o0[14], o1[14];
            TR(13, k);
            mbar_wait_unless(vok, bt + B_VRAW, pt);
            fence_async_smem();
            TR(14, k);
            probs(sc0, m[0], pa0);
            wgmma_fence();
            mma_pv<2 * IT * V_STRIDE, 0>(o0, pa0, descVw);
            wgmma_commit();
            probs(sc1, m[1], pa1);
            wgmma_fence();
            mma_pv<2 * IT * V_STRIDE + 6 * GRP, 0>(o1, pa1, descVw);
            wgmma_commit();
            uint32_t w[24];
            wgmma_wait<1>();
            reg_fence(o0);
            {
                const float il0 = rcp_ftz(f16lo(o0[12])), il1 = rcp_ftz(f16lo(o0[13]));
                const uint32_t l0 = pack_f16(il0, il0), l1 = pack_f16(il1, il1);
#pragma unroll
                for (int j = 0; j < 12; j++) w[j] = hmul2_f16(o0[j], (j & 1) ? l1 : l0);
            }
            wgmma_wait<0>();
            reg_fence(o1);
            TR(15, k);
            asm volatile("{\n.reg .pred p;\nsetp.eq.u32 p, %0, 1;\n@p bar.sync 4, 128;\n@!p bar.sync 5, 128;\n}\n"
                         :: "r"(wg) : "memory");
            qok = mbar_test(bars + (tn & 3) * 8 + B_QKRAW, (tn >> 2) & 1);
            asm volatile("ld.volatile.shared.v2.b32 {%0, %1}, [%2];\n" : "=r"(mstate), "=r"(nwin) : "r"(bars + B_MSTATE) : "memory");
            {
                const float il2 = rcp_ftz(f16lo(o1[0])), il3 = rcp_ftz(f16lo(o1[1]));
                const uint32_t l2 = pack_f16(il2, il2), l3 = pack_f16(il3, il3);
#pragma unroll
                for (int j = 0; j < 12; j++) w[12 + j] = hmul2_f16(o1[j + 2], (j & 1) ? l3 : l2);
#pragma unroll
                for (int p = 0; p < 3; p++) stsm_x4(oa + p * 64, w[8 * p], w[8 * p + 2], w[8 * p + 4], w[8 * p + 6]);
#pragma unroll
                for (int p = 0; p < 3; p++) stsm_x4_if(warp < 3, oa + oup + 8 * O_PITCH + p * 64, w[8 * p + 1], w[8 * p + 3], w[8 * p + 5], w[8 * p + 7]);
            }
            __syncwarp();
            if (lane == 0) mbar_arrive(bar + B_ODONE);
            TR(16, k);
            oa ^= oflip;
            asm volatile("" : "+r"(oa));
        };
        for (int k = wg - 1;; k += 4) {
            window(std::integral_constant<int, 0>(), k);
            if (__any_sync(0xffffffffu, k + 2 >= nwin)) break;
            window(std::integral_constant<int, 1>(), k + 2);
            if (__any_sync(0xffffffffu, k + 4 >= nwin)) break;
        }
        (void)zero;
        asm volatile("setmaxnreg.inc.sync.aligned.u32 160;\n");
    }

    TR(27, wg);
    ST(2 + wg);
    uint32_t tag, seen;
    asm volatile("ld.relaxed.gpu.global.v2.u32 {%0, %1}, [%2];\n" : "=r"(tag), "=r"(seen) : "l"(g_guard) : "memory");
    if (attn || !MPRE) {
        __syncwarp();
        if (lane == 0) mbar_arrive(sbase + SM_PBAR + 96);
    }
    if (!attn) {
        uint4 wor[2][6];
#pragma unroll
        for (int i = 0; i < 12; i++)
            ldg_nc_v4(reinterpret_cast<uint32_t (&)[4]>(wor[i / 6][i % 6]), P.wo + ((tid >> 2) + i / 6 * 96) * 192 + 32 * (i % 6) + 8 * c);
        {
            const uint32_t wstep = (gridDim.x - 2 * P.npair) * 12, wend = MEND * P.npair;
            const uint32_t mbuf = sbase + (tid >> 5) * MBUFS * M_BUF, mbar = sbase + SM_MBAR + (tid >> 5) * MBUFS * 8;
            uint32_t w = MPRE * P.npair + (role - 2 * P.npair) * 12 + (tid >> 5);
            auto load = [&](uint32_t w, uint32_t i) {
                if (w < wend) {
                    const uint32_t o = (w * 4802u) & ~(MALIGN - 1), n = MALIGN == 16 ? 4816 : ((w * 4802u & ~15u) + 4816 - o + MALIGN - 1) & ~(MALIGN - 1);
                    mbar_arrive_expect_tx(mbar + i * 8, n);
                    asm volatile("cp.async.bulk.shared::cluster.global.mbarrier::complete_tx::bytes [%0], [%1], %3, [%2];\n"
                                 :: "r"(mbuf + i * M_BUF), "l"(reinterpret_cast<const char*>(P.mask) + o),
                                    "r"(mbar + i * 8), "r"(n) : "memory");
                }
            };
            if (elect_one()) {
#pragma unroll 1
                for (int i = 0; i < MBUFS; i++) load(w + i * wstep, i);
            }
            __syncwarp();
            uint32_t i = 0, ph = 0;
#pragma unroll 1
            for (; w < wend; w += wstep) {
                const uint32_t b = mbuf + i * M_BUF + ((w * 4802u) & (MALIGN - 16));
                mbar_wait(mbar + i * 8, ph);
                uint32_t acc = lds16(b + (lane & 7) * 2 + (lane & 8) * 600);
                if ((lane & 15) - (w & 7) > 8u) acc = 0;
                uint32_t v[10][4];
#pragma unroll
                for (int j = 0; j < 10; j++) lds128(v[j], b + 16 * (j < 9 ? 1 + lane + 32 * j : min(289 + lane, 299)));
#pragma unroll
                for (int j = 0; j < 10; j++) acc |= v[j][0] | v[j][1] | v[j][2] | v[j][3];
                const uint32_t nz = __any_sync(0xffffffffu, (acc & 0x7FFF7FFFu) != 0) ? 1 : 0;
                if (elect_one()) {
                    load(w + MBUFS * wstep, i);
                    const uint32_t k = w / (uint32_t)P.npair;
                    asm volatile("st.relaxed.gpu.global.u32 [%0], %1;\n" :: "l"(g_mz + (w - k * P.npair) * 128 + k), "r"((tag | 255) - nz) : "memory");
                }
                __syncwarp();
                if (++i == MBUFS) { i = 0; ph ^= 1; }
            }
            if (lane == 0) mbar_arrive(sbase + SM_PBAR + 96);
            asm volatile("bar.sync 6, 384;\n" ::: "memory");
        }
#pragma unroll
        for (int rh = 0; rh < 2; rh++) {
            const int row = (tid >> 2) + 96 * rh;
            const uint4 (&w)[6] = wor[rh];
            float s = 0.f;
#pragma unroll
            for (int a = 0; a < 6; a++)
                s += ((bf16lo(w[a].x) + bf16hi(w[a].x)) + (bf16lo(w[a].y) + bf16hi(w[a].y))) +
                     ((bf16lo(w[a].z) + bf16hi(w[a].z)) + (bf16lo(w[a].w) + bf16hi(w[a].w)));
            s += __shfl_xor_sync(0xffffffffu, s, 1);
            s += __shfl_xor_sync(0xffffffffu, s, 2);
            s *= (1.f / 192.f);
            const uint32_t sw = (row >> 1) & 3;
            const uint32_t d = sbase + SM_WO + row * 64 + ((c ^ sw) << 4), e = sbase + SM_WO + row * 64 + c * 4;
#pragma unroll
            for (int a = 0; a < 6; a++) {
                const uint32_t h[4] = {pack_f16(bf16lo(w[a].x) - s, bf16hi(w[a].x) - s), pack_f16(bf16lo(w[a].y) - s, bf16hi(w[a].y) - s),
                                       pack_f16(bf16lo(w[a].z) - s, bf16hi(w[a].z) - s), pack_f16(bf16lo(w[a].w) - s, bf16hi(w[a].w) - s)};
                if (a < 2 * PSM) {
                    sts128(d + a * 12288, h[0], h[1], h[2], h[3]);
                } else {
#pragma unroll
                    for (int i = 0; i < 4; i++) sts32(e + a * 12288 + ((i ^ sw) << 4), h[i]);
                }
            }
        }
        fence_async_smem();
        asm volatile("bar.sync 6, 384;\n" ::: "memory");
        if (role == 2 * P.npair && tid == 0) {
            asm volatile("cp.async.bulk.global.shared::cta.bulk_group [%0], [%1], %2;\n"
                         :: "l"(g_wo), "r"(sbase + SM_WO), "n"(SM_STAGE) : "memory");
            asm volatile("cp.async.bulk.commit_group;\n" ::: "memory");
            asm volatile("cp.async.bulk.wait_group 0;\n" ::: "memory");
            asm volatile("fence.proxy.async.global;\n" ::: "memory");
            asm volatile("st.release.gpu.global.u32 [%0], %1;\n" :: "l"(g_guard + 3), "r"(tag | 255) : "memory");
        }
        __syncwarp();
    } else {
        mbar_wait(bars + B_WRAW, 1);
    }
    tag |= 255;
    if (bad) g_guard[1] = tag;
    bad |= seen == tag;
    TR(27, 4 + wg);
    if (wg == 0) ST(5);
    {
        PROJ_SCHEDULE
        uint64_t descW = make_desc(sbase + SM_WO, 12288, 512, 2);
        const uint64_t descA = make_desc(sbase + SM_STAGE + wg * STAGE_BYTES, 16, 1024, 1);
        const uint32_t bar = sbase + SM_PBAR + wg * 8;
        const uint32_t yrel = sbase + SM_STAGE + wg * STAGE_BYTES + (warp * 16 + (lane & 15)) * 128 + (((lane & 7) ^ (lane >> 4)) << 4);
        float acc[96];
#pragma unroll
        for (int i = 0; i < 96; i++) acc[i] = 0.f;
        uint32_t it = 0;
        for (int tile = tile0 + wg * tstep; tile < tend; tile += 3 * tstep, it++) {
            descW += P.z1;
            mbar_wait(bar + (it & 1) * 24, (it >> 1) & 1);
            TR(28, it * 3 + wg);
            ST(6 + wg);
            if (it > 0 || wg > 0) asm volatile("bar.sync %0, 256;\n" :: "r"(8 + wg) : "memory");
            wgmma_fence();
            mma_proj<0, 0>(acc, descA + (uint64_t)((it & 1) * (3 * STAGE_BYTES >> 4)), descW);
            wgmma_commit();
            if (tile + tstep < tend) asm volatile("bar.arrive %0, 256;\n" :: "r"(wg == 2 ? 8 : 9 + wg) : "memory");
            wgmma_wait<0>();
            reg_fence(acc);
            TR(18, it * 3 + wg);
            float a[4];
#pragma unroll
            for (int i = 0; i < 4; i++) a[i] = acc[i] * acc[i];
#pragma unroll
            for (int j = 1; j < 24; j++)
#pragma unroll
                for (int i = 0; i < 4; i++) a[i] = fmaf(acc[4 * j + i], acc[4 * j + i], a[i]);
            float s0 = a[0] + a[1], s1 = a[2] + a[3];
            s0 += __shfl_xor_sync(0xffffffffu, s0, 1);
            s1 += __shfl_xor_sync(0xffffffffu, s1, 1);
            s0 += __shfl_xor_sync(0xffffffffu, s0, 2);
            s1 += __shfl_xor_sync(0xffffffffu, s1, 2);
            if (max(__float_as_uint(s0) - VAR_MIN, __float_as_uint(s1) - VAR_MIN) >= F32_INF - VAR_MIN) {
                const int rem = ((tile < TILES_A) ? NPIX - SEG_B - 64 * tile : SEG_B - 64 * (tile - TILES_A)) - warp * 16 - g;
                if ((__float_as_uint(s0) - VAR_MIN >= F32_INF - VAR_MIN && rem > 0) ||
                    (__float_as_uint(s1) - VAR_MIN >= F32_INF - VAR_MIN && rem > 8)) {
                    bad = true;
                    g_guard[1] = tag;
                }
            }
            const float rs0 = rsqrt_ftz(fmaf(s0, 1.f / 192.f, 1e-5f));
            const float rs1 = rsqrt_ftz(fmaf(s1, 1.f / 192.f, 1e-5f));
            const uint32_t ya = yrel + (it & 1) * 3 * STAGE_BYTES;
            auto direct = [&]() {
                const int p0 = (tile < TILES_A) ? SEG_B + 64 * (tile & PWRAP) : 64 * (tile - TILES_A);
                const int lim = ((tile < TILES_A) ? NPIX : SEG_B) - p0;
                char* const po = reinterpret_cast<char*>(P.out) + (uint32_t)((p0 + warp * 16 + g) * 384 + c * 16);
                const bool v0 = warp * 16 + g < lim, v1 = warp * 16 + g + 8 < lim;
#pragma unroll
                for (int i = 2 * PSM; i < 6; i++) {
                    const int j = 16 * i;
                    stg128_if(v0, po + 64 * i, pack_bf16(acc[j] * rs0, acc[j + 1] * rs0), pack_bf16(acc[j + 4] * rs0, acc[j + 5] * rs0),
                              pack_bf16(acc[j + 8] * rs0, acc[j + 9] * rs0), pack_bf16(acc[j + 12] * rs0, acc[j + 13] * rs0));
                    stg128_if(v1, po + 8 * 384 + 64 * i, pack_bf16(acc[j + 2] * rs1, acc[j + 3] * rs1),
                              pack_bf16(acc[j + 6] * rs1, acc[j + 7] * rs1), pack_bf16(acc[j + 10] * rs1, acc[j + 11] * rs1),
                              pack_bf16(acc[j + 14] * rs1, acc[j + 15] * rs1));
                }
            };
            if (PSM < 3 && PDF) direct();
#pragma unroll
            for (int p = 0; p < 4 * PSM; p++)
                stsm_x4((ya ^ (32 * (p & 3))) + (p >> 2) * 8192,
                        pack_bf16(acc[8 * p] * rs0, acc[8 * p + 1] * rs0), pack_bf16(acc[8 * p + 2] * rs1, acc[8 * p + 3] * rs1),
                        pack_bf16(acc[8 * p + 4] * rs0, acc[8 * p + 5] * rs0), pack_bf16(acc[8 * p + 6] * rs1, acc[8 * p + 7] * rs1));
            __syncwarp();
            if (lane == 0) mbar_arrive(bar + 104 + (it & 1) * 24);
            if (PSM < 3 && !PDF) direct();
            TR(29, it * 3 + wg);
            ST(16 + wg);
        }
        __syncwarp();
        if (lane == 0) mbar_arrive(sbase + SM_PBAR + 56);
    }

    {
        uint32_t any;
        asm volatile("{\n.reg .pred p, q;\nsetp.ne.u32 q, %1, 0;\nbarrier.cta.red.or.pred.aligned p, %2, 128, q;\nselp.u32 %0, 1, 0, p;\n}\n"
                     : "=r"(any) : "r"((uint32_t)bad), "r"(12 + wg) : "memory");
        if (!any) return;
    }
    redo(P, smem + wg * FB_BYTES, tag, 12 + wg);
}

}

typedef CUresult (*PFN_encodeTiled)(CUtensorMap*, CUtensorMapDataType, cuuint32_t, void*, const cuuint64_t*,
                                    const cuuint64_t*, const cuuint32_t*, const cuuint32_t*, CUtensorMapInterleave,
                                    CUtensorMapSwizzle, CUtensorMapL2promotion, CUtensorMapFloatOOBfill);

extern "C" void kernel_launch(void* const* d_in, const int* in_sizes, int n_in, void* d_out, int out_size) {
    swin::Params P;
    P.x           = (const __nv_bfloat16*)d_in[0];
    P.wqkv        = (const __nv_bfloat16*)d_in[1];
    P.wo          = (const __nv_bfloat16*)d_in[2];
    P.logit_scale = (const __nv_bfloat16*)d_in[3];
    P.cpb_w1      = (const __nv_bfloat16*)d_in[4];
    P.cpb_w2      = (const __nv_bfloat16*)d_in[5];
    P.rel_coords  = (const __nv_bfloat16*)d_in[6];
    P.rel_idx     = (const int*)d_in[7];
    P.mask        = (const __nv_bfloat16*)d_in[8];
    P.out         = (__nv_bfloat16*)d_out;
    P.z1 = 0;
    static PFN_encodeTiled encode = nullptr;
    if (!encode) {
        cudaFuncSetAttribute(swin::swin_window_attn_kernel, cudaFuncAttributeMaxDynamicSharedMemorySize, swin::SM_TOTAL);
        cudaDriverEntryPointQueryResult qr;
        cudaGetDriverEntryPoint("cuTensorMapEncodeTiled", (void**)&encode, cudaEnableDefault, &qr);
    }
    CUtensorMap xmap, xmap4, xmap3, omap, wmap, smap, omapb, xmapa, xmapb, smap3, wraw;
    const cuuint32_t estr[4] = {1, 1, 1, 1};
    auto make = [&](CUtensorMap* m, const void* base, int rank, const cuuint64_t* gdim, const cuuint64_t* gstr,
                    const cuuint32_t* box, CUtensorMapSwizzle swz = CU_TENSOR_MAP_SWIZZLE_128B) {
        CUresult r = encode(m, CU_TENSOR_MAP_DATA_TYPE_BFLOAT16, rank, const_cast<void*>(base), gdim, gstr, box, estr,
               CU_TENSOR_MAP_INTERLEAVE_NONE, swz, CU_TENSOR_MAP_L2_PROMOTION_L2_128B,
               CU_TENSOR_MAP_FLOAT_OOB_FILL_NONE);
        (void)r;
    };
    {
        const cuuint64_t gdim[3] = {192, swin::IMG, swin::IMG}, gstr[2] = {384, swin::IMG * 384};
        const cuuint32_t box[3] = {64, 7, 7}, box4[3] = {64, 4, 1}, box3[3] = {64, 3, 1};
        make(&xmap, P.x, 3, gdim, gstr, box);
        make(&xmap4, P.x, 3, gdim, gstr, box4);
        make(&xmap3, P.x, 3, gdim, gstr, box3);
        const cuuint32_t boxa[3] = {64, 7, 3}, boxb[3] = {64, 7, 4};
        make(&xmapa, P.x, 3, gdim, gstr, boxa);
        make(&xmapb, P.x, 3, gdim, gstr, boxb);
    }
    {
        const cuuint64_t gdim[2] = {192, (cuuint64_t)swin::NPIX}, gstr[1] = {384};
        const cuuint32_t box64[2] = {64, 64};
        make(&omap, d_out, 2, gdim, gstr, box64);
        const cuuint64_t gdimb[2] = {192, (cuuint64_t)swin::SEG_B};
        make(&omapb, d_out, 2, gdimb, gstr, box64);
    }
    {
        const cuuint64_t gdim[2] = {576, 192}, gstr[1] = {1152};
        const cuuint32_t box[2] = {16, 192};
        make(&wmap, P.wqkv, 2, gdim, gstr, box, CU_TENSOR_MAP_SWIZZLE_32B);
        const cuuint64_t gdim3[3] = {96, 6, 192}, gstr3[2] = {192, 1152};
        const cuuint32_t box3[3] = {104, 1, 96};
        make(&wraw, P.wqkv, 3, gdim3, gstr3, box3, CU_TENSOR_MAP_SWIZZLE_NONE);
    }
    {
        const cuuint64_t gdim[4] = {96, 2, swin::IMG, swin::IMG}, gstr[3] = {192, 384, swin::IMG * 384};
        const cuuint32_t box4[4] = {104, 1, 7, OONE == 1 ? 7 : 4}, box3[4] = {104, 1, 7, 3};
        make(&smap, d_out, 4, gdim, gstr, box4, CU_TENSOR_MAP_SWIZZLE_NONE);
        make(&smap3, d_out, 4, gdim, gstr, box3, CU_TENSOR_MAP_SWIZZLE_NONE);
    }
    P.npair = NPAIR; P.need = swin::ROW_DONE;
    P.t1 = swin::TILES - NTAIL;
    P.spread = ((132 - 2 * NPAIR) * 65536 + 131) / 132;
    swin::swin_window_attn_kernel<<<132, swin::NTHREADS, swin::SM_TOTAL>>>(P, xmap, xmap4, xmap3, omap, wmap, smap, omapb, xmapa, xmapb, smap3, wraw);
}
```

```cpp
#include <cuda_runtime.h>
#include <cuda.h>
#include <cuda_bf16.h>
#include <stdint.h>
#include <type_traits>

namespace swin {

#define NPAIR 53
#define QFP32 0
#define PF_DIST 3
#define EXP 0
#define QSPLIT 3
#define SSPLIT 0
#define LATEMASK 0
#define CLUSTER 0
#define NOPF 0
#define NTAIL 370
#define PSTORE 1
#define PORDER 1
#define GORD 0
#define GMERGE 0
#define XSPLIT 1
#define EARLYW 1
#define NEARLY 4
#define W1 1
#define W2 2
#define W3 2
#define T_ONEBUF 0
#define T_NOWV 0
#define MPF 3
#define MRND 5
#define PX_L 3
#define PX_S 3
#define PX_W 0
#define PCHUNK 1
#define SPREAD 2
#define PSM 2
#define PDF 0
#define PWRAP -1
#define POLLER 1
#define PUBN 2
#define PUBT 4
#define NSTATIC 92
#define RSLEEP 800
#define AROLL 0
#define WOSPLIT 4
#define PADZ 1
#define MPRE 10
#define MEND 50
#define HOUT 1
#define HX 0
#define HM 0
#define OONE 1
#define VSTR 10256
#define MALIGN 128
#define MBUFS 1
#define FREL 1
#define RPOLL 1
#define NOCC 0
#define WFEN 0
#define ENDX 0
#define EW 1
#define EWT 480
#define GLATE 2
#define MDELAY 0
#define OSW 1
#define XPF 2
#define HOIST 0
#define HINT 0
#define HINT_A ""
#define HINT_B ""
#define REG_G 232
#define REG_A 120
#define REG_H 32
constexpr int IMG      = 511;
constexpr int NWS      = 73;
constexpr int NWINDOWS = NWS * NWS;
constexpr int TOK      = 49;
constexpr int NPIX     = IMG * IMG;
constexpr int NTHREADS = 512;

constexpr int W_ATOM = 6144;
constexpr int SM_WA = 0, SM_WB = 6 * W_ATOM, SM_WV = 12 * W_ATOM;
constexpr int GRP   = TOK * 16;
constexpr int XCH   = TOK * 128;
constexpr int SM_V  = 18 * W_ATOM, V_STRIDE = VSTR, O_STRIDE = 10240, O_PITCH = 208;
constexpr int SM_QK = SM_V + 4 * O_STRIDE, QK_CHUNK = 4 * XCH;
constexpr int SM_MASK = SM_QK + 3 * QK_CHUNK;
constexpr int SM_TAB  = SM_V + 3 * V_STRIDE + 256;
constexpr int SM_DUMP = SM_MASK + 4816;
constexpr int SM_BAR  = SM_DUMP + 320;
constexpr int B_XFULL = 0, B_WRAW = 32, B_XCONS = 40, B_NTILES = 48, B_GDONE = 56, B_DYN = 192, B_ROWS = 384, B_QKRAW = 64, B_QKFREE = 96, B_VFREE = 128, B_ODONE = 160,
              B_VRAW = 224, B_MFULL = 256, B_MSTATE = 264, B_MCONS = 272, B_WFULL = 280, B_STORED = 288, B_PUBD = 304;
constexpr int SM_A_END = SM_BAR + 320;
static_assert(SM_QK % 1024 == 0 && TOK * O_PITCH + 64 - 16 <= O_STRIDE && (28 * O_PITCH + 64) % 128 == 0, "layout");
static_assert(3 * V_STRIDE + 13 * GRP <= 4 * O_STRIDE && V_STRIDE >= O_STRIDE && SM_DUMP % 128 == 80, "layout");
constexpr int SM_WO    = 0;
constexpr int SM_STAGE = 73728;
constexpr int STAGE_BYTES = 24576;
constexpr int SM_MBAR  = SM_STAGE + 6 * STAGE_BYTES, M_BUF = 4992;
constexpr int SM_PBAR  = SM_A_END;
constexpr int SM_TOTAL = SM_PBAR + 152;
static_assert(SM_STAGE + 6 * STAGE_BYTES <= SM_BAR, "smem");
static_assert(SM_TOTAL <= 232448, "smem");
static_assert(SM_BAR % 8 == 0, "barrier alignment");

constexpr int SEG_B   = 3 * IMG;
constexpr int TILES_A = (NPIX - SEG_B + 63) / 64;
constexpr int TILES   = TILES_A + (SEG_B + 63) / 64;
constexpr uint32_t ROW_DONE = NWS * 2;

__device__ uint32_t g_cnt[NWS + 7];
__device__ __align__(128) uint8_t g_wo[SM_STAGE];
__device__ uint32_t g_mz[64 * 128];
__device__ uint32_t g_next[2];
__device__ uint32_t g_done;
__device__ __align__(16) uint32_t g_guard[4];
constexpr uint32_t F32_INF = 0x7F800000u;
constexpr uint32_t SS_MIN  = 0x3B800000u;
constexpr uint32_t VAR_MIN = 0x3D400000u;

#define TR(ev, idx)
#define ST(i)
#define SC(i)
#define CK(k)
constexpr uint64_t EVICT_FIRST = 0x12F0000000000000ull;
constexpr float LOG2E = 1.4426950408889634f;

__device__ __forceinline__ uint32_t smem_u32(const void* p) {
    return (uint32_t)__cvta_generic_to_shared(p);
}
__device__ __forceinline__ uint64_t make_desc(uint32_t saddr, uint32_t lbo, uint32_t sbo, uint32_t swz = 0) {
    return (uint64_t)((saddr & 0x3FFFF) >> 4) | ((uint64_t)(lbo >> 4) << 16) | ((uint64_t)(sbo >> 4) << 32) |
           ((uint64_t)swz << 62);
}
__host__ __device__ constexpr uint64_t make_desc_c(uint32_t saddr, uint32_t lbo, uint32_t sbo, uint32_t swz) {
    return (uint64_t)(saddr >> 4) | ((uint64_t)(lbo >> 4) << 16) | ((uint64_t)(sbo >> 4) << 32) | ((uint64_t)swz << 62);
}
__device__ __forceinline__ void wgmma_fence()  { asm volatile("wgmma.fence.sync.aligned;\n" ::: "memory"); }
__device__ __forceinline__ void wgmma_commit() { asm volatile("wgmma.commit_group.sync.aligned;\n" ::: "memory"); }
template <int N> __device__ __forceinline__ void wgmma_wait() {
    asm volatile("wgmma.wait_group.sync.aligned %0;\n" :: "n"(N) : "memory");
}
__device__ __forceinline__ void fence_async_smem() { asm volatile("fence.proxy.async.shared::cta;\n" ::: "memory"); }
__device__ __forceinline__ void wg_bar(int id) { asm volatile("bar.sync %0, 128;\n" :: "r"(id) : "memory"); }

template <int N> __device__ __forceinline__ void reg_fence(float (&v)[N]) {
#pragma unroll
    for (int i = 0; i < N; i++) asm volatile("" : "+f"(v[i]) :: "memory");
}
template <int N> __device__ __forceinline__ void reg_fence(uint32_t (&v)[N]) {
#pragma unroll
    for (int i = 0; i < N; i++) asm volatile("" : "+r"(v[i]) :: "memory");
}
template <int N, int M> __device__ __forceinline__ void reg_fence(uint32_t (&v)[N][M]) {
#pragma unroll
    for (int i = 0; i < N; i++) reg_fence(v[i]);
}

__device__ __forceinline__ uint32_t pack_bf16(float lo, float hi) {
    uint32_t r;
    asm("cvt.rn.bf16x2.f32 %0, %1, %2;\n" : "=r"(r) : "f"(hi), "f"(lo));
    return r;
}
__device__ __forceinline__ uint32_t pack_f16(float lo, float hi) {
    uint32_t r;
    asm("cvt.rn.f16x2.f32 %0, %1, %2;\n" : "=r"(r) : "f"(hi), "f"(lo));
    return r;
}
__device__ __forceinline__ uint32_t pack_f16_sat(float lo, float hi) {
    uint32_t r;
    asm("cvt.rn.satfinite.f16x2.f32 %0, %1, %2;\n" : "=r"(r) : "f"(hi), "f"(lo));
    return r;
}
__device__ __forceinline__ uint32_t hmul2_f16(uint32_t a, uint32_t b) {
    uint32_t r;
    asm("mul.rn.f16x2 %0, %1, %2;\n" : "=r"(r) : "r"(a), "r"(b));
    return r;
}
__device__ __forceinline__ uint32_t hadd2_f16(uint32_t a, uint32_t b) {
    uint32_t r;
    asm("add.rn.f16x2 %0, %1, %2;\n" : "=r"(r) : "r"(a), "r"(b));
    return r;
}
__device__ __forceinline__ uint32_t hfma2_f16(uint32_t a, uint32_t b, uint32_t c) {
    uint32_t r;
    asm("fma.rn.f16x2 %0, %1, %2, %3;\n" : "=r"(r) : "r"(a), "r"(b), "r"(c));
    return r;
}
__device__ __forceinline__ uint32_t hmax2_f16(uint32_t a, uint32_t b) {
    uint32_t r;
    asm("max.f16x2 %0, %1, %2;\n" : "=r"(r) : "r"(a), "r"(b));
    return r;
}
template <int H> __device__ __forceinline__ uint32_t hsub2_bc(uint32_t a, uint32_t b) {
    uint32_t r;
    if (H == 0) asm("{\n.reg .b16 l, h;\n.reg .b32 t;\nmov.b32 {l, h}, %2;\nmov.b32 t, {l, l};\nsub.rn.f16x2 %0, %1, t;\n}\n" : "=r"(r) : "r"(a), "r"(b));
    else        asm("{\n.reg .b16 l, h;\n.reg .b32 t;\nmov.b32 {l, h}, %2;\nmov.b32 t, {h, h};\nsub.rn.f16x2 %0, %1, t;\n}\n" : "=r"(r) : "r"(a), "r"(b));
    return r;
}
__device__ __forceinline__ uint32_t ex2_f16x2(uint32_t a) {
    uint32_t r;
    asm("ex2.approx.f16x2 %0, %1;\n" : "=r"(r) : "r"(a));
    return r;
}
__device__ __forceinline__ uint32_t ex2_f16lo(uint32_t a) {
    uint32_t r;
    asm("{\n.reg .b16 l, h;\nmov.b32 {l, h}, %1;\nex2.approx.f16 l, l;\nmov.b32 %0, {l, h};\n}\n" : "=r"(r) : "r"(a));
    return r;
}
__device__ __forceinline__ uint32_t lds16(uint32_t addr) {
    uint32_t v;
    asm volatile("ld.shared.u16 %0, [%1];\n" : "=r"(v) : "r"(addr) : "memory");
    return v;
}
__device__ __forceinline__ uint32_t lds16v(uint32_t addr) {
    uint32_t v;
    asm volatile("ld.volatile.shared.u16 %0, [%1];\n" : "=r"(v) : "r"(addr) : "memory");
    return v;
}
__device__ __forceinline__ void sts16(uint32_t addr, uint32_t v) {
    asm volatile("st.volatile.shared.u16 [%0], %1;\n" :: "r"(addr), "r"(v) : "memory");
}
__device__ __forceinline__ float f16lo(uint32_t v) {
    float r;
    asm("{\n.reg .b16 l, h;\nmov.b32 {l, h}, %1;\ncvt.f32.f16 %0, l;\n}\n" : "=f"(r) : "r"(v));
    return r;
}
__device__ __forceinline__ float f16hi(uint32_t v) {
    float r;
    asm("{\n.reg .b16 l, h;\nmov.b32 {l, h}, %1;\ncvt.f32.f16 %0, h;\n}\n" : "=f"(r) : "r"(v));
    return r;
}
__device__ __forceinline__ uint32_t bf2h(uint32_t v) {
    return pack_f16(__uint_as_float(v << 16), __uint_as_float(v & 0xFFFF0000u));
}
__device__ __forceinline__ float bf16lo(uint32_t v) { return __uint_as_float(v << 16); }
__device__ __forceinline__ float bf16hi(uint32_t v) { return __uint_as_float(v & 0xFFFF0000u); }
__device__ __forceinline__ uint32_t hadd2_bf16(uint32_t a, uint32_t b) {
    uint32_t r;
    asm("add.rn.bf16x2 %0, %1, %2;\n" : "=r"(r) : "r"(a), "r"(b));
    return r;
}
__device__ __forceinline__ uint32_t hmul2_bf16(uint32_t a, uint32_t b) {
    uint32_t r;
    asm("mul.rn.bf16x2 %0, %1, %2;\n" : "=r"(r) : "r"(a), "r"(b));
    return r;
}
__device__ __forceinline__ uint32_t hsub2_bf16(uint32_t a, uint32_t b) {
    uint32_t r;
    asm("sub.rn.bf16x2 %0, %1, %2;\n" : "=r"(r) : "r"(a), "r"(b));
    return r;
}
__device__ __forceinline__ uint32_t hfma2_bf16(uint32_t a, uint32_t b, uint32_t c) {
    uint32_t r;
    asm("fma.rn.bf16x2 %0, %1, %2, %3;\n" : "=r"(r) : "r"(a), "r"(b), "r"(c));
    return r;
}
__device__ __forceinline__ uint32_t hmax2_bf16(uint32_t a, uint32_t b) {
    uint32_t r;
    asm("max.bf16x2 %0, %1, %2;\n" : "=r"(r) : "r"(a), "r"(b));
    return r;
}
__device__ __forceinline__ uint32_t ex2_bf16x2(uint32_t a) {
    uint32_t r;
    asm("ex2.approx.ftz.bf16x2 %0, %1;\n" : "=r"(r) : "r"(a));
    return r;
}
__device__ __forceinline__ uint32_t ex2_bf16lo(uint32_t a) {
    uint32_t r;
    asm("{\n.reg .b16 l, h;\nmov.b32 {l, h}, %1;\nex2.approx.ftz.bf16 l, l;\ncvt.u32.u16 %0, l;\n}\n" : "=r"(r) : "r"(a));
    return r;
}
__device__ __forceinline__ uint32_t mbar_test(uint32_t bar, uint32_t parity) {
    uint32_t ok;
    asm volatile("{\n.reg .pred p;\nmbarrier.test_wait.parity.shared::cta.b64 p, [%1], %2;\nselp.u32 %0, 1, 0, p;\n}\n"
                 : "=r"(ok) : "r"(bar), "r"(parity) : "memory");
    return ok;
}
__device__ __forceinline__ uint32_t prmt(uint32_t a, uint32_t b, uint32_t sel) {
    uint32_t r;
    asm("prmt.b32 %0, %1, %2, %3;\n" : "=r"(r) : "r"(a), "r"(b), "r"(sel));
    return r;
}
__device__ __forceinline__ float round_bf16(float x) { return __bfloat162float(__float2bfloat16_rn(x)); }

__device__ __forceinline__ void mbar_init(uint32_t bar, uint32_t count) {
    asm volatile("mbarrier.init.shared::cta.b64 [%0], %1;\n" :: "r"(bar), "r"(count) : "memory");
}
__device__ __forceinline__ void mbar_wait(uint32_t bar, uint32_t parity) {
    asm volatile(
        "{\n"
        ".reg .pred p;\n"
        ".reg .u32 n;\n"
        "mov.u32 n, 0;\n"
        "WAIT_%=:\n"
        "mbarrier.try_wait.parity.shared::cta.b64 p, [%0], %1" HINT_A ";\n"
        "@p bra DONE_%=;\n"
        "add.u32 n, n, 1;\n"
        "setp.lt.u32 p, n, 4194304;\n"
        "@p bra WAIT_%=;\n"
        "exit;\n"
        "DONE_%=:\n"
        "}\n" :: "r"(bar), "r"(parity) : "memory");
}
__device__ __forceinline__ void mbar_wait4(uint32_t b0, uint32_t p0, uint32_t b1, uint32_t p1, uint32_t b2, uint32_t p2,
                                           uint32_t b3, uint32_t p3) {
    asm volatile(
        "{\n"
        ".reg .pred p, q, r, s;\n"
        ".reg .u32 n;\n"
        "mov.u32 n, 0;\n"
        "WAIT_%=:\n"
        "mbarrier.try_wait.parity.shared::cta.b64 p, [%0], %1;\n"
        "mbarrier.try_wait.parity.shared::cta.b64 q, [%2], %3;\n"
        "mbarrier.try_wait.parity.shared::cta.b64 r, [%4], %5;\n"
        "mbarrier.try_wait.parity.shared::cta.b64 s, [%6], %7;\n"
        "and.pred p, p, q;\n"
        "and.pred r, r, s;\n"
        "and.pred p, p, r;\n"
        "@p bra DONE_%=;\n"
        "add.u32 n, n, 1;\n"
        "setp.lt.u32 p, n, 4194304;\n"
        "@p bra WAIT_%=;\n"
        "exit;\n"
        "DONE_%=:\n"
        "}\n" :: "r"(b0), "r"(p0), "r"(b1), "r"(p1), "r"(b2), "r"(p2), "r"(b3), "r"(p3) : "memory");
}
__device__ __forceinline__ void mbar_wait2(uint32_t b0, uint32_t p0, uint32_t b1, uint32_t p1) {
    asm volatile(
        "{\n"
        ".reg .pred p, q;\n"
        ".reg .u32 n;\n"
        "mov.u32 n, 0;\n"
        "WAIT_%=:\n"
        "mbarrier.try_wait.parity.shared::cta.b64 p, [%0], %1;\n"
        "mbarrier.try_wait.parity.shared::cta.b64 q, [%2], %3;\n"
        "and.pred p, p, q;\n"
        "@p bra DONE_%=;\n"
        "add.u32 n, n, 1;\n"
        "setp.lt.u32 p, n, 4194304;\n"
        "@p bra WAIT_%=;\n"
        "exit;\n"
        "DONE_%=:\n"
        "}\n" :: "r"(b0), "r"(p0), "r"(b1), "r"(p1) : "memory");
}
__device__ __forceinline__ void mbar_wait_unless(uint32_t ok, uint32_t bar, uint32_t parity) {
    asm volatile(
        "{\n"
        ".reg .pred p;\n"
        ".reg .u32 n;\n"
        "setp.ne.u32 p, %2, 0;\n"
        "vote.sync.all.pred p, p, 0xffffffff;\n"
        "@p bra DONE_%=;\n"
        "mov.u32 n, 0;\n"
        "WAIT_%=:\n"
        "mbarrier.try_wait.parity.shared::cta.b64 p, [%0], %1" HINT_B ";\n"
        "@p bra DONE_%=;\n"
        "add.u32 n, n, 1;\n"
        "setp.lt.u32 p, n, 4194304;\n"
        "@p bra WAIT_%=;\n"
        "exit;\n"
        "DONE_%=:\n"
        "}\n" :: "r"(bar), "r"(parity), "r"(ok) : "memory");
}
__device__ __forceinline__ void mbar_wait_unless_dep(uint32_t ok, uint32_t bar, uint32_t parity, uint32_t zero, uint32_t& a,
                                                     uint32_t& b, uint32_t& c, uint32_t& d) {
    asm volatile(
        "{\n"
        ".reg .pred p;\n"
        ".reg .u32 n;\n"
        "setp.ne.u32 p, %6, 0;\n"
        "vote.sync.all.pred p, p, 0xffffffff;\n"
        "@p bra DONE_%=;\n"
        "mov.u32 n, 0;\n"
        "WAIT_%=:\n"
        "setp.ne.u32 p, %7, 0;\n"
        "@p ld.shared.v4.b32 {%0, %1, %2, %3}, [%7];\n"
        "mbarrier.try_wait.parity.shared::cta.b64 p, [%4], %5;\n"
        "@p bra DONE_%=;\n"
        "add.u32 n, n, 1;\n"
        "setp.lt.u32 p, n, 4194304;\n"
        "@p bra WAIT_%=;\n"
        "exit;\n"
        "DONE_%=:\n"
        "}\n" : "+r"(a), "+r"(b), "+r"(c), "+r"(d) : "r"(bar), "r"(parity), "r"(ok), "r"(zero) : "memory");
}
__device__ __forceinline__ void mbar_wait2_unless(uint32_t ok, uint32_t b0, uint32_t p0, uint32_t b1, uint32_t p1) {
    asm volatile(
        "{\n"
        ".reg .pred p, q;\n"
        ".reg .u32 n;\n"
        "setp.ne.u32 p, %4, 0;\n"
        "vote.sync.all.pred p, p, 0xffffffff;\n"
        "@p bra DONE_%=;\n"
        "mov.u32 n, 0;\n"
        "WAIT_%=:\n"
        "mbarrier.try_wait.parity.shared::cta.b64 p, [%0], %1" HINT_B ";\n"
        "mbarrier.try_wait.parity.shared::cta.b64 q, [%2], %3" HINT_B ";\n"
        "and.pred p, p, q;\n"
        "@p bra DONE_%=;\n"
        "add.u32 n, n, 1;\n"
        "setp.lt.u32 p, n, 4194304;\n"
        "@p bra WAIT_%=;\n"
        "exit;\n"
        "DONE_%=:\n"
        "}\n" :: "r"(b0), "r"(p0), "r"(b1), "r"(p1), "r"(ok) : "memory");
}
__device__ __forceinline__ void mbar_wait4_unless(uint32_t ok, uint32_t b0, uint32_t p0, uint32_t b1, uint32_t p1, uint32_t b2,
                                                  uint32_t p2, uint32_t b3, uint32_t p3) {
    asm volatile(
        "{\n"
        ".reg .pred p, q, r, s;\n"
        ".reg .u32 n;\n"
        "setp.ne.u32 p, %8, 0;\n"
        "vote.sync.all.pred p, p, 0xffffffff;\n"
        "@p bra DONE_%=;\n"
        "mov.u32 n, 0;\n"
        "WAIT_%=:\n"
        "mbarrier.try_wait.parity.shared::cta.b64 p, [%0], %1;\n"
        "mbarrier.try_wait.parity.shared::cta.b64 q, [%2], %3;\n"
        "mbarrier.try_wait.parity.shared::cta.b64 r, [%4], %5;\n"
        "mbarrier.try_wait.parity.shared::cta.b64 s, [%6], %7;\n"
        "and.pred p, p, q;\n"
        "and.pred r, r, s;\n"
        "and.pred p, p, r;\n"
        "@p bra DONE_%=;\n"
        "add.u32 n, n, 1;\n"
        "setp.lt.u32 p, n, 4194304;\n"
        "@p bra WAIT_%=;\n"
        "exit;\n"
        "DONE_%=:\n"
        "}\n" :: "r"(b0), "r"(p0), "r"(b1), "r"(p1), "r"(b2), "r"(p2), "r"(b3), "r"(p3), "r"(ok) : "memory");
}
__device__ __forceinline__ void sched_fence(uint32_t zero, uint32_t a, uint32_t b, uint32_t c, uint32_t d, uint32_t e = 0,
                                            uint32_t f = 0, uint32_t g = 0, uint32_t h = 0, uint32_t i = 0, uint32_t j = 0,
                                            uint32_t k = 0) {
    asm volatile("{\n.reg .pred p;\n.reg .u32 n;\nsetp.eq.u32 p, %0, 0;\n@p bra.uni DONE_%=;\nmov.u32 n, %0;\nSPIN_%=:\n"
                 "nanosleep.u32 %1;\nnanosleep.u32 %2;\nnanosleep.u32 %3;\nnanosleep.u32 %4;\nnanosleep.u32 %5;\n"
                 "nanosleep.u32 %6;\nnanosleep.u32 %7;\nnanosleep.u32 %8;\nnanosleep.u32 %9;\nnanosleep.u32 %10;\n"
                 "nanosleep.u32 %11;\nsub.u32 n, n, 1;\nsetp.ne.u32 p, n, 0;\n@p bra.uni SPIN_%=;\nDONE_%=:\n}\n"
                 :: "r"(zero), "r"(a), "r"(b), "r"(c), "r"(d), "r"(e), "r"(f), "r"(g), "r"(h), "r"(i), "r"(j), "r"(k) : "memory");
}
__device__ __forceinline__ void sched_fence16(uint32_t zero, const uint32_t (&v)[4][4], uint32_t a = 0, uint32_t b = 0) {
    asm volatile("{\n.reg .pred p;\n.reg .u32 n;\nsetp.eq.u32 p, %0, 0;\n@p bra.uni DONE_%=;\nmov.u32 n, %0;\nSPIN_%=:\n"
                 "nanosleep.u32 %17;\nnanosleep.u32 %18;\n"
                 "st.shared.v4.b32 [n], {%1, %2, %3, %4};\nst.shared.v4.b32 [n + 16], {%5, %6, %7, %8};\n"
                 "st.shared.v4.b32 [n + 32], {%9, %10, %11, %12};\nst.shared.v4.b32 [n + 48], {%13, %14, %15, %16};\n"
                 "sub.u32 n, n, 1;\nsetp.ne.u32 p, n, 0;\n@p bra.uni SPIN_%=;\nDONE_%=:\n}\n"
                 :: "r"(zero), "r"(v[0][0]), "r"(v[0][1]), "r"(v[0][2]), "r"(v[0][3]), "r"(v[1][0]), "r"(v[1][1]), "r"(v[1][2]), "r"(v[1][3]),
                    "r"(v[2][0]), "r"(v[2][1]), "r"(v[2][2]), "r"(v[2][3]), "r"(v[3][0]), "r"(v[3][1]), "r"(v[3][2]), "r"(v[3][3]),
                    "r"(a), "r"(b) : "memory");
}
__device__ __forceinline__ void sched_dep(uint32_t zero, uint32_t& a, uint32_t& b, uint32_t& c, uint32_t& d) {
    asm volatile("{\n.reg .pred p;\n.reg .u32 n;\nsetp.eq.u32 p, %4, 0;\n@p bra.uni DONE_%=;\nmov.u32 n, %4;\nSPIN_%=:\n"
                 "ld.shared.v4.b32 {%0, %1, %2, %3}, [n];\n"
                 "sub.u32 n, n, 1;\nsetp.ne.u32 p, n, 0;\n@p bra.uni SPIN_%=;\nDONE_%=:\n}\n"
                 : "+r"(a), "+r"(b), "+r"(c), "+r"(d) : "r"(zero) : "memory");
}
__device__ __forceinline__ void mbar_arrive(uint32_t bar) {
    asm volatile("mbarrier.arrive.shared::cta.b64 _, [%0];\n" :: "r"(bar) : "memory");
}
__device__ __forceinline__ void mbar_arrive_n(uint32_t bar, uint32_t n) {
    asm volatile("mbarrier.arrive.shared::cta.b64 _, [%0], %1;\n" :: "r"(bar), "r"(n) : "memory");
}
__device__ __forceinline__ void mbar_arrive_expect_tx(uint32_t bar, uint32_t bytes) {
    asm volatile("mbarrier.arrive.expect_tx.shared::cta.b64 _, [%0], %1;\n" :: "r"(bar), "r"(bytes) : "memory");
}
__device__ __forceinline__ void stg128_if(bool p, void* addr, uint32_t x, uint32_t y, uint32_t z, uint32_t w) {
    asm volatile("{\n.reg .pred q;\nsetp.ne.b32 q, %5, 0;\n@q st.global.L1::no_allocate.L2::cache_hint.v4.b32 [%0], {%1, %2, %3, %4}, %6;\n}\n"
                 :: "l"(addr), "r"(x), "r"(y), "r"(z), "r"(w), "r"((uint32_t)p), "l"(EVICT_FIRST) : "memory");
}
__device__ __forceinline__ void stsm_x4(uint32_t addr, uint32_t r0, uint32_t r1, uint32_t r2, uint32_t r3) {
    asm volatile("stmatrix.sync.aligned.m8n8.x4.shared.b16 [%0], {%1, %2, %3, %4};\n"
                 :: "r"(addr), "r"(r0), "r"(r1), "r"(r2), "r"(r3) : "memory");
}
__device__ __forceinline__ void stsm_x4_if(bool p, uint32_t addr, uint32_t r0, uint32_t r1, uint32_t r2, uint32_t r3) {
    asm volatile("{\n.reg .pred q;\nsetp.ne.b32 q, %5, 0;\n@q stmatrix.sync.aligned.m8n8.x4.shared.b16 [%0], {%1, %2, %3, %4};\n}\n"
                 :: "r"(addr), "r"(r0), "r"(r1), "r"(r2), "r"(r3), "r"((uint32_t)p) : "memory");
}
__device__ __forceinline__ void stsm_x2(uint32_t addr, uint32_t r0, uint32_t r1) {
    asm volatile("stmatrix.sync.aligned.m8n8.x2.shared.b16 [%0], {%1, %2};\n" :: "r"(addr), "r"(r0), "r"(r1) : "memory");
}
__device__ __forceinline__ void sts128(uint32_t addr, uint32_t r0, uint32_t r1, uint32_t r2, uint32_t r3) {
    asm volatile("st.shared.v4.b32 [%0], {%1, %2, %3, %4};\n" :: "r"(addr), "r"(r0), "r"(r1), "r"(r2), "r"(r3) : "memory");
}
__device__ __forceinline__ void sts32(uint32_t addr, uint32_t v) {
    asm volatile("st.shared.b32 [%0], %1;\n" :: "r"(addr), "r"(v) : "memory");
}
__device__ __forceinline__ uint32_t lds32(uint32_t addr) {
    uint32_t v;
    asm volatile("ld.shared.b32 %0, [%1];\n" : "=r"(v) : "r"(addr) : "memory");
    return v;
}
__device__ __forceinline__ void lds128(uint32_t (&r)[4], uint32_t addr) {
    asm volatile("ld.shared.v4.b32 {%0, %1, %2, %3}, [%4];\n" : "=r"(r[0]), "=r"(r[1]), "=r"(r[2]), "=r"(r[3]) : "r"(addr) : "memory");
}
__device__ __forceinline__ uint32_t lds32v(uint32_t addr) {
    uint32_t v;
    asm volatile("ld.volatile.shared.b32 %0, [%1];\n" : "=r"(v) : "r"(addr) : "memory");
    return v;
}
__device__ __forceinline__ void ldg_nc_v4(uint32_t (&r)[4], const void* p) {
    asm volatile("ld.global.nc.L1::no_allocate.v4.u32 {%0, %1, %2, %3}, [%4];\n"
                 : "=r"(r[0]), "=r"(r[1]), "=r"(r[2]), "=r"(r[3]) : "l"(p));
}
__device__ __forceinline__ uint32_t ldg_u32(const void* p) {
    uint32_t v;
    asm volatile("ld.global.nc.L1::evict_first.u32 %0, [%1];\n" : "=r"(v) : "l"(p));
    return v;
}
__device__ __forceinline__ void ldg_u64(const void* p, uint32_t& a, uint32_t& b) {
    asm volatile("ld.global.nc.L1::evict_first.v2.u32 {%0, %1}, [%2];\n" : "=r"(a), "=r"(b) : "l"(p));
}
__device__ __forceinline__ void prefetch_l2(const void* p) {
    asm volatile("prefetch.global.L2 [%0];\n" :: "l"(p));
}
__device__ __forceinline__ void cp_async16(uint32_t dst, const void* src) {
    asm volatile("cp.async.cg.shared.global [%0], [%1], 16;\n" :: "r"(dst), "l"(src) : "memory");
}
__device__ __forceinline__ float ex2_ftz(float x) {
    float y;
    asm("ex2.approx.ftz.f32 %0, %1;\n" : "=f"(y) : "f"(x));
    return y;
}
__device__ __forceinline__ float rcp_ftz(float x) {
    float y;
    asm("rcp.approx.ftz.f32 %0, %1;\n" : "=f"(y) : "f"(x));
    return y;
}
__device__ __forceinline__ float rsqrt_ftz(float x) {
    float y;
    asm("rsqrt.approx.ftz.f32 %0, %1;\n" : "=f"(y) : "f"(x));
    return y;
}

__device__ __forceinline__ bool elect_one() {
    uint32_t p;
    asm volatile("{\n.reg .pred q;\nelect.sync _|q, 0xffffffff;\nselp.u32 %0, 1, 0, q;\n}\n" : "=r"(p));
    return p != 0;
}
__device__ __forceinline__ void ldsm_x4(uint32_t (&r)[4], uint32_t addr) {
    asm volatile("ldmatrix.sync.aligned.m8n8.x4.shared.b16 {%0, %1, %2, %3}, [%4];\n"
                 : "=r"(r[0]), "=r"(r[1]), "=r"(r[2]), "=r"(r[3]) : "r"(addr) : "memory");
}
__device__ __forceinline__ void ldsm_x2(uint32_t& r0, uint32_t& r1, uint32_t addr) {
    asm volatile("ldmatrix.sync.aligned.m8n8.x2.shared.b16 {%0, %1}, [%2];\n" : "=r"(r0), "=r"(r1) : "r"(addr) : "memory");
}
__device__ __forceinline__ void tma_2d(uint32_t dst, const CUtensorMap* map, uint32_t bar, int c0, int c1) {
    asm volatile("cp.async.bulk.tensor.2d.shared::cluster.global.mbarrier::complete_tx::bytes [%0], [%1, {%3, %4}], [%2];\n"
                 :: "r"(dst), "l"(reinterpret_cast<uint64_t>(map)), "r"(bar), "r"(c0), "r"(c1) : "memory");
}
__device__ __forceinline__ void tma_3d(uint32_t dst, const CUtensorMap* map, uint32_t bar, int c0, int c1, int c2) {
    asm volatile("cp.async.bulk.tensor.3d.shared::cluster.global.mbarrier::complete_tx::bytes [%0], [%1, {%3, %4, %5}], [%2];\n"
                 :: "r"(dst), "l"(reinterpret_cast<uint64_t>(map)), "r"(bar), "r"(c0), "r"(c1), "r"(c2) : "memory");
}
__device__ __forceinline__ void tma_store_4d(const CUtensorMap* map, uint32_t src, int c0, int c1, int c2, int c3) {
    asm volatile("cp.async.bulk.tensor.4d.global.shared::cta.tile.bulk_group [%0, {%2, %3, %4, %5}], [%1];\n"
                 :: "l"(reinterpret_cast<uint64_t>(map)), "r"(src), "r"(c0), "r"(c1), "r"(c2), "r"(c3) : "memory");
}
__device__ __forceinline__ void mbar_arrive_if(uint32_t bar, uint32_t cnt) {
    asm volatile("{\n.reg .pred q;\nsetp.ne.b32 q, %1, 0;\n@q mbarrier.arrive.shared::cta.b64 _, [%0], %1;\n}\n"
                 :: "r"(bar), "r"(cnt) : "memory");
}

template <int BOFF, int AOFF, int NA>
__device__ __forceinline__ void mma_qk_first(uint32_t (&d)[48], const uint32_t (&a)[NA][4], uint64_t descB) {
    asm volatile(
        "{\n"
        ".reg .pred p0, p1;\n"
        ".reg .b64 ta, ta0, tb, tb0;\n"
        "setp.ne.b32 p0, 0, 0;\n"
        "setp.eq.b32 p1, 0, 0;\n"
        "add.s64 tb0, %64, %65;\n"
        "add.s64 tb, tb0, 0;\n"
        "wgmma.mma_async.sync.aligned.m64n192k16.f16.f16.f16 {%0, %1, %2, %3, %4, %5, %6, %7, %8, %9, %10, %11, %12, %13, %14, %15, %16, %17, %18, %19, %20, %21, %22, %23, %24, %25, %26, %27, %28, %29, %30, %31, %32, %33, %34, %35, %36, %37, %38, %39, %40, %41, %42, %43, %44, %45, %46, %47}, {%48, %49, %50, %51}, tb, p0, 1, 1, 1;\n"
        "add.s64 tb, tb0, 32;\n"
        "wgmma.mma_async.sync.aligned.m64n192k16.f16.f16.f16 {%0, %1, %2, %3, %4, %5, %6, %7, %8, %9, %10, %11, %12, %13, %14, %15, %16, %17, %18, %19, %20, %21, %22, %23, %24, %25, %26, %27, %28, %29, %30, %31, %32, %33, %34, %35, %36, %37, %38, %39, %40, %41, %42, %43, %44, %45, %46, %47}, {%52, %53, %54, %55}, tb, p1, 1, 1, 1;\n"
        "add.s64 tb, tb0, 64;\n"
        "wgmma.mma_async.sync.aligned.m64n192k16.f16.f16.f16 {%0, %1, %2, %3, %4, %5, %6, %7, %8, %9, %10, %11, %12, %13, %14, %15, %16, %17, %18, %19, %20, %21, %22, %23, %24, %25, %26, %27, %28, %29, %30, %31, %32, %33, %34, %35, %36, %37, %38, %39, %40, %41, %42, %43, %44, %45, %46, %47}, {%56, %57, %58, %59}, tb, p1, 1, 1, 1;\n"
        "add.s64 tb, tb0, 96;\n"
        "wgmma.mma_async.sync.aligned.m64n192k16.f16.f16.f16 {%0, %1, %2, %3, %4, %5, %6, %7, %8, %9, %10, %11, %12, %13, %14, %15, %16, %17, %18, %19, %20, %21, %22, %23, %24, %25, %26, %27, %28, %29, %30, %31, %32, %33, %34, %35, %36, %37, %38, %39, %40, %41, %42, %43, %44, %45, %46, %47}, {%60, %61, %62, %63}, tb, p1, 1, 1, 1;\n"
        "}\n"
        : "=r"(d[0]), "=r"(d[1]), "=r"(d[2]), "=r"(d[3]), "=r"(d[4]), "=r"(d[5]), "=r"(d[6]), "=r"(d[7]), "=r"(d[8]), "=r"(d[9]), "=r"(d[10]), "=r"(d[11]), "=r"(d[12]), "=r"(d[13]), "=r"(d[14]), "=r"(d[15]), "=r"(d[16]), "=r"(d[17]), "=r"(d[18]), "=r"(d[19]), "=r"(d[20]), "=r"(d[21]), "=r"(d[22]), "=r"(d[23]), "=r"(d[24]), "=r"(d[25]), "=r"(d[26]), "=r"(d[27]), "=r"(d[28]), "=r"(d[29]), "=r"(d[30]), "=r"(d[31]), "=r"(d[32]), "=r"(d[33]), "=r"(d[34]), "=r"(d[35]), "=r"(d[36]), "=r"(d[37]), "=r"(d[38]), "=r"(d[39]), "=r"(d[40]), "=r"(d[41]), "=r"(d[42]), "=r"(d[43]), "=r"(d[44]), "=r"(d[45]), "=r"(d[46]), "=r"(d[47])
        : "r"(a[AOFF + 0][0]), "r"(a[AOFF + 0][1]), "r"(a[AOFF + 0][2]), "r"(a[AOFF + 0][3]), "r"(a[AOFF + 1][0]), "r"(a[AOFF + 1][1]), "r"(a[AOFF + 1][2]), "r"(a[AOFF + 1][3]), "r"(a[AOFF + 2][0]), "r"(a[AOFF + 2][1]), "r"(a[AOFF + 2][2]), "r"(a[AOFF + 2][3]), "r"(a[AOFF + 3][0]), "r"(a[AOFF + 3][1]), "r"(a[AOFF + 3][2]), "r"(a[AOFF + 3][3]), "l"(descB), "n"(BOFF >> 4));
}

template <int BOFF, int AOFF, int NA>
__device__ __forceinline__ void mma_qk_next(uint32_t (&d)[48], const uint32_t (&a)[NA][4], uint64_t descB) {
    asm volatile(
        "{\n"
        ".reg .pred p0, p1;\n"
        ".reg .b64 ta, ta0, tb, tb0;\n"
        "setp.ne.b32 p0, 0, 0;\n"
        "setp.eq.b32 p1, 0, 0;\n"
        "add.s64 tb0, %64, %65;\n"
        "add.s64 tb, tb0, 0;\n"
        "wgmma.mma_async.sync.aligned.m64n192k16.f16.f16.f16 {%0, %1, %2, %3, %4, %5, %6, %7, %8, %9, %10, %11, %12, %13, %14, %15, %16, %17, %18, %19, %20, %21, %22, %23, %24, %25, %26, %27, %28, %29, %30, %31, %32, %33, %34, %35, %36, %37, %38, %39, %40, %41, %42, %43, %44, %45, %46, %47}, {%48, %49, %50, %51}, tb, p1, 1, 1, 1;\n"
        "add.s64 tb, tb0, 32;\n"
        "wgmma.mma_async.sync.aligned.m64n192k16.f16.f16.f16 {%0, %1, %2, %3, %4, %5, %6, %7, %8, %9, %10, %11, %12, %13, %14, %15, %16, %17, %18, %19, %20, %21, %22, %23, %24, %25, %26, %27, %28, %29, %30, %31, %32, %33, %34, %35, %36, %37, %38, %39, %40, %41, %42, %43, %44, %45, %46, %47}, {%52, %53, %54, %55}, tb, p1, 1, 1, 1;\n"
        "add.s64 tb, tb0, 64;\n"
        "wgmma.mma_async.sync.aligned.m64n192k16.f16.f16.f16 {%0, %1, %2, %3, %4, %5, %6, %7, %8, %9, %10, %11, %12, %13, %14, %15, %16, %17, %18, %19, %20, %21, %22, %23, %24, %25, %26, %27, %28, %29, %30, %31, %32, %33, %34, %35, %36, %37, %38, %39, %40, %41, %42, %43, %44, %45, %46, %47}, {%56, %57, %58, %59}, tb, p1, 1, 1, 1;\n"
        "add.s64 tb, tb0, 96;\n"
        "wgmma.mma_async.sync.aligned.m64n192k16.f16.f16.f16 {%0, %1, %2, %3, %4, %5, %6, %7, %8, %9, %10, %11, %12, %13, %14, %15, %16, %17, %18, %19, %20, %21, %22, %23, %24, %25, %26, %27, %28, %29, %30, %31, %32, %33, %34, %35, %36, %37, %38, %39, %40, %41, %42, %43, %44, %45, %46, %47}, {%60, %61, %62, %63}, tb, p1, 1, 1, 1;\n"
        "}\n"
        : "+r"(d[0]), "+r"(d[1]), "+r"(d[2]), "+r"(d[3]), "+r"(d[4]), "+r"(d[5]), "+r"(d[6]), "+r"(d[7]), "+r"(d[8]), "+r"(d[9]), "+r"(d[10]), "+r"(d[11]), "+r"(d[12]), "+r"(d[13]), "+r"(d[14]), "+r"(d[15]), "+r"(d[16]), "+r"(d[17]), "+r"(d[18]), "+r"(d[19]), "+r"(d[20]), "+r"(d[21]), "+r"(d[22]), "+r"(d[23]), "+r"(d[24]), "+r"(d[25]), "+r"(d[26]), "+r"(d[27]), "+r"(d[28]), "+r"(d[29]), "+r"(d[30]), "+r"(d[31]), "+r"(d[32]), "+r"(d[33]), "+r"(d[34]), "+r"(d[35]), "+r"(d[36]), "+r"(d[37]), "+r"(d[38]), "+r"(d[39]), "+r"(d[40]), "+r"(d[41]), "+r"(d[42]), "+r"(d[43]), "+r"(d[44]), "+r"(d[45]), "+r"(d[46]), "+r"(d[47])
        : "r"(a[AOFF + 0][0]), "r"(a[AOFF + 0][1]), "r"(a[AOFF + 0][2]), "r"(a[AOFF + 0][3]), "r"(a[AOFF + 1][0]), "r"(a[AOFF + 1][1]), "r"(a[AOFF + 1][2]), "r"(a[AOFF + 1][3]), "r"(a[AOFF + 2][0]), "r"(a[AOFF + 2][1]), "r"(a[AOFF + 2][2]), "r"(a[AOFF + 2][3]), "r"(a[AOFF + 3][0]), "r"(a[AOFF + 3][1]), "r"(a[AOFF + 3][2]), "r"(a[AOFF + 3][3]), "l"(descB), "n"(BOFF >> 4));
}

template <int BOFF, int AOFF, int NA>
__device__ __forceinline__ void mma_v_first(uint32_t (&d)[24], const uint32_t (&a)[NA][4], uint64_t descB) {
    asm volatile(
        "{\n"
        ".reg .pred p0, p1;\n"
        ".reg .b64 ta, ta0, tb, tb0;\n"
        "setp.ne.b32 p0, 0, 0;\n"
        "setp.eq.b32 p1, 0, 0;\n"
        "add.s64 tb0, %40, %41;\n"
        "add.s64 tb, tb0, 0;\n"
        "wgmma.mma_async.sync.aligned.m64n96k16.f16.f16.f16 {%0, %1, %2, %3, %4, %5, %6, %7, %8, %9, %10, %11, %12, %13, %14, %15, %16, %17, %18, %19, %20, %21, %22, %23}, {%24, %25, %26, %27}, tb, p0, 1, 1, 1;\n"
        "add.s64 tb, tb0, 32;\n"
        "wgmma.mma_async.sync.aligned.m64n96k16.f16.f16.f16 {%0, %1, %2, %3, %4, %5, %6, %7, %8, %9, %10, %11, %12, %13, %14, %15, %16, %17, %18, %19, %20, %21, %22, %23}, {%28, %29, %30, %31}, tb, p1, 1, 1, 1;\n"
        "add.s64 tb, tb0, 64;\n"
        "wgmma.mma_async.sync.aligned.m64n96k16.f16.f16.f16 {%0, %1, %2, %3, %4, %5, %6, %7, %8, %9, %10, %11, %12, %13, %14, %15, %16, %17, %18, %19, %20, %21, %22, %23}, {%32, %33, %34, %35}, tb, p1, 1, 1, 1;\n"
        "add.s64 tb, tb0, 96;\n"
        "wgmma.mma_async.sync.aligned.m64n96k16.f16.f16.f16 {%0, %1, %2, %3, %4, %5, %6, %7, %8, %9, %10, %11, %12, %13, %14, %15, %16, %17, %18, %19, %20, %21, %22, %23}, {%36, %37, %38, %39}, tb, p1, 1, 1, 1;\n"
        "}\n"
        : "=r"(d[0]), "=r"(d[1]), "=r"(d[2]), "=r"(d[3]), "=r"(d[4]), "=r"(d[5]), "=r"(d[6]), "=r"(d[7]), "=r"(d[8]), "=r"(d[9]), "=r"(d[10]), "=r"(d[11]), "=r"(d[12]), "=r"(d[13]), "=r"(d[14]), "=r"(d[15]), "=r"(d[16]), "=r"(d[17]), "=r"(d[18]), "=r"(d[19]), "=r"(d[20]), "=r"(d[21]), "=r"(d[22]), "=r"(d[23])
        : "r"(a[AOFF + 0][0]), "r"(a[AOFF + 0][1]), "r"(a[AOFF + 0][2]), "r"(a[AOFF + 0][3]), "r"(a[AOFF + 1][0]), "r"(a[AOFF + 1][1]), "r"(a[AOFF + 1][2]), "r"(a[AOFF + 1][3]), "r"(a[AOFF + 2][0]), "r"(a[AOFF + 2][1]), "r"(a[AOFF + 2][2]), "r"(a[AOFF + 2][3]), "r"(a[AOFF + 3][0]), "r"(a[AOFF + 3][1]), "r"(a[AOFF + 3][2]), "r"(a[AOFF + 3][3]), "l"(descB), "n"(BOFF >> 4));
}

template <int BOFF, int AOFF, int NA>
__device__ __forceinline__ void mma_v_next(uint32_t (&d)[24], const uint32_t (&a)[NA][4], uint64_t descB) {
    asm volatile(
        "{\n"
        ".reg .pred p0, p1;\n"
        ".reg .b64 ta, ta0, tb, tb0;\n"
        "setp.ne.b32 p0, 0, 0;\n"
        "setp.eq.b32 p1, 0, 0;\n"
        "add.s64 tb0, %40, %41;\n"
        "add.s64 tb, tb0, 0;\n"
        "wgmma.mma_async.sync.aligned.m64n96k16.f16.f16.f16 {%0, %1, %2, %3, %4, %5, %6, %7, %8, %9, %10, %11, %12, %13, %14, %15, %16, %17, %18, %19, %20, %21, %22, %23}, {%24, %25, %26, %27}, tb, p1, 1, 1, 1;\n"
        "add.s64 tb, tb0, 32;\n"
        "wgmma.mma_async.sync.aligned.m64n96k16.f16.f16.f16 {%0, %1, %2, %3, %4, %5, %6, %7, %8, %9, %10, %11, %12, %13, %14, %15, %16, %17, %18, %19, %20, %21, %22, %23}, {%28, %29, %30, %31}, tb, p1, 1, 1, 1;\n"
        "add.s64 tb, tb0, 64;\n"
        "wgmma.mma_async.sync.aligned.m64n96k16.f16.f16.f16 {%0, %1, %2, %3, %4, %5, %6, %7, %8, %9, %10, %11, %12, %13, %14, %15, %16, %17, %18, %19, %20, %21, %22, %23}, {%32, %33, %34, %35}, tb, p1, 1, 1, 1;\n"
        "add.s64 tb, tb0, 96;\n"
        "wgmma.mma_async.sync.aligned.m64n96k16.f16.f16.f16 {%0, %1, %2, %3, %4, %5, %6, %7, %8, %9, %10, %11, %12, %13, %14, %15, %16, %17, %18, %19, %20, %21, %22, %23}, {%36, %37, %38, %39}, tb, p1, 1, 1, 1;\n"
        "}\n"
        : "+r"(d[0]), "+r"(d[1]), "+r"(d[2]), "+r"(d[3]), "+r"(d[4]), "+r"(d[5]), "+r"(d[6]), "+r"(d[7]), "+r"(d[8]), "+r"(d[9]), "+r"(d[10]), "+r"(d[11]), "+r"(d[12]), "+r"(d[13]), "+r"(d[14]), "+r"(d[15]), "+r"(d[16]), "+r"(d[17]), "+r"(d[18]), "+r"(d[19]), "+r"(d[20]), "+r"(d[21]), "+r"(d[22]), "+r"(d[23])
        : "r"(a[AOFF + 0][0]), "r"(a[AOFF + 0][1]), "r"(a[AOFF + 0][2]), "r"(a[AOFF + 0][3]), "r"(a[AOFF + 1][0]), "r"(a[AOFF + 1][1]), "r"(a[AOFF + 1][2]), "r"(a[AOFF + 1][3]), "r"(a[AOFF + 2][0]), "r"(a[AOFF + 2][1]), "r"(a[AOFF + 2][2]), "r"(a[AOFF + 2][3]), "r"(a[AOFF + 3][0]), "r"(a[AOFF + 3][1]), "r"(a[AOFF + 3][2]), "r"(a[AOFF + 3][3]), "l"(descB), "n"(BOFF >> 4));
}

template <int AOFF, int BOFF>
__device__ __forceinline__ void mma_s0_f32(float (&d)[28], uint64_t descA, uint64_t descB) {
    asm volatile(
        "{\n"
        ".reg .pred p0, p1;\n"
        ".reg .b64 ta, ta0, tb, tb0;\n"
        "setp.ne.b32 p0, 0, 0;\n"
        "setp.eq.b32 p1, 0, 0;\n"
        "add.s64 tb0, %30, %31;\n"
        "add.s64 ta0, %28, %29;\n"
        "add.s64 tb, tb0, 4;\n"
        "add.s64 ta, ta0, 0;\n"
        "wgmma.mma_async.sync.aligned.m64n56k16.f32.f16.f16 {%0, %1, %2, %3, %4, %5, %6, %7, %8, %9, %10, %11, %12, %13, %14, %15, %16, %17, %18, %19, %20, %21, %22, %23, %24, %25, %26, %27}, ta, tb, p1, 1, 1, 0, 0;\n"
        "add.s64 tb, tb0, 1572;\n"
        "add.s64 ta, ta0, 1568;\n"
        "wgmma.mma_async.sync.aligned.m64n56k16.f32.f16.f16 {%0, %1, %2, %3, %4, %5, %6, %7, %8, %9, %10, %11, %12, %13, %14, %15, %16, %17, %18, %19, %20, %21, %22, %23, %24, %25, %26, %27}, ta, tb, p1, 1, 1, 0, 0;\n"
        "add.s64 tb, tb0, 3140;\n"
        "add.s64 ta, ta0, 3136;\n"
        "wgmma.mma_async.sync.aligned.m64n56k16.f32.f16.f16 {%0, %1, %2, %3, %4, %5, %6, %7, %8, %9, %10, %11, %12, %13, %14, %15, %16, %17, %18, %19, %20, %21, %22, %23, %24, %25, %26, %27}, ta, tb, p1, 1, 1, 0, 0;\n"
        "}\n"
        : "+f"(d[0]), "+f"(d[1]), "+f"(d[2]), "+f"(d[3]), "+f"(d[4]), "+f"(d[5]), "+f"(d[6]), "+f"(d[7]), "+f"(d[8]), "+f"(d[9]), "+f"(d[10]), "+f"(d[11]), "+f"(d[12]), "+f"(d[13]), "+f"(d[14]), "+f"(d[15]), "+f"(d[16]), "+f"(d[17]), "+f"(d[18]), "+f"(d[19]), "+f"(d[20]), "+f"(d[21]), "+f"(d[22]), "+f"(d[23]), "+f"(d[24]), "+f"(d[25]), "+f"(d[26]), "+f"(d[27])
        : "l"(descA), "n"(AOFF >> 4), "l"(descB), "n"(BOFF >> 4));
}

template <int AOFF, int BOFF>
__device__ __forceinline__ void mma_s0_f16(uint32_t (&d)[14], uint64_t descA, uint64_t descB) {
    asm volatile(
        "{\n"
        ".reg .pred p0, p1;\n"
        ".reg .b64 ta, ta0, tb, tb0;\n"
        "setp.ne.b32 p0, 0, 0;\n"
        "setp.eq.b32 p1, 0, 0;\n"
        "add.s64 tb0, %16, %17;\n"
        "add.s64 ta0, %14, %15;\n"
        "add.s64 tb, tb0, 4;\n"
        "add.s64 ta, ta0, 0;\n"
        "wgmma.mma_async.sync.aligned.m64n56k16.f16.f16.f16 {%0, %1, %2, %3, %4, %5, %6, %7, %8, %9, %10, %11, %12, %13}, ta, tb, p1, 1, 1, 0, 0;\n"
        "add.s64 tb, tb0, 1572;\n"
        "add.s64 ta, ta0, 1568;\n"
        "wgmma.mma_async.sync.aligned.m64n56k16.f16.f16.f16 {%0, %1, %2, %3, %4, %5, %6, %7, %8, %9, %10, %11, %12, %13}, ta, tb, p1, 1, 1, 0, 0;\n"
        "add.s64 tb, tb0, 3140;\n"
        "add.s64 ta, ta0, 3136;\n"
        "wgmma.mma_async.sync.aligned.m64n56k16.f16.f16.f16 {%0, %1, %2, %3, %4, %5, %6, %7, %8, %9, %10, %11, %12, %13}, ta, tb, p1, 1, 1, 0, 0;\n"
        "}\n"
        : "+r"(d[0]), "+r"(d[1]), "+r"(d[2]), "+r"(d[3]), "+r"(d[4]), "+r"(d[5]), "+r"(d[6]), "+r"(d[7]), "+r"(d[8]), "+r"(d[9]), "+r"(d[10]), "+r"(d[11]), "+r"(d[12]), "+r"(d[13])
        : "l"(descA), "n"(AOFF >> 4), "l"(descB), "n"(BOFF >> 4));
}

template <int AOFF, int BOFF>
__device__ __forceinline__ void mma_s1_f32(float (&d)[28], uint64_t descA, uint64_t descB) {
    asm volatile(
        "{\n"
        ".reg .pred p0, p1;\n"
        ".reg .b64 ta, ta0, tb, tb0;\n"
        "setp.ne.b32 p0, 0, 0;\n"
        "setp.eq.b32 p1, 0, 0;\n"
        "add.s64 tb0, %30, %31;\n"
        "add.s64 ta0, %28, %29;\n"
        "add.s64 tb, tb0, 6;\n"
        "add.s64 ta, ta0, 2;\n"
        "wgmma.mma_async.sync.aligned.m64n56k16.f32.f16.f16 {%0, %1, %2, %3, %4, %5, %6, %7, %8, %9, %10, %11, %12, %13, %14, %15, %16, %17, %18, %19, %20, %21, %22, %23, %24, %25, %26, %27}, ta, tb, p1, 1, 1, 0, 0;\n"
        "add.s64 tb, tb0, 1574;\n"
        "add.s64 ta, ta0, 1570;\n"
        "wgmma.mma_async.sync.aligned.m64n56k16.f32.f16.f16 {%0, %1, %2, %3, %4, %5, %6, %7, %8, %9, %10, %11, %12, %13, %14, %15, %16, %17, %18, %19, %20, %21, %22, %23, %24, %25, %26, %27}, ta, tb, p1, 1, 1, 0, 0;\n"
        "add.s64 tb, tb0, 3142;\n"
        "add.s64 ta, ta0, 3138;\n"
        "wgmma.mma_async.sync.aligned.m64n56k16.f32.f16.f16 {%0, %1, %2, %3, %4, %5, %6, %7, %8, %9, %10, %11, %12, %13, %14, %15, %16, %17, %18, %19, %20, %21, %22, %23, %24, %25, %26, %27}, ta, tb, p1, 1, 1, 0, 0;\n"
        "}\n"
        : "+f"(d[0]), "+f"(d[1]), "+f"(d[2]), "+f"(d[3]), "+f"(d[4]), "+f"(d[5]), "+f"(d[6]), "+f"(d[7]), "+f"(d[8]), "+f"(d[9]), "+f"(d[10]), "+f"(d[11]), "+f"(d[12]), "+f"(d[13]), "+f"(d[14]), "+f"(d[15]), "+f"(d[16]), "+f"(d[17]), "+f"(d[18]), "+f"(d[19]), "+f"(d[20]), "+f"(d[21]), "+f"(d[22]), "+f"(d[23]), "+f"(d[24]), "+f"(d[25]), "+f"(d[26]), "+f"(d[27])
        : "l"(descA), "n"(AOFF >> 4), "l"(descB), "n"(BOFF >> 4));
}

template <int AOFF, int BOFF>
__device__ __forceinline__ void mma_s1_f16(uint32_t (&d)[14], uint64_t descA, uint64_t descB) {
    asm volatile(
        "{\n"
        ".reg .pred p0, p1;\n"
        ".reg .b64 ta, ta0, tb, tb0;\n"
        "setp.ne.b32 p0, 0, 0;\n"
        "setp.eq.b32 p1, 0, 0;\n"
        "add.s64 tb0, %16, %17;\n"
        "add.s64 ta0, %14, %15;\n"
        "add.s64 tb, tb0, 6;\n"
        "add.s64 ta, ta0, 2;\n"
        "wgmma.mma_async.sync.aligned.m64n56k16.f16.f16.f16 {%0, %1, %2, %3, %4, %5, %6, %7, %8, %9, %10, %11, %12, %13}, ta, tb, p1, 1, 1, 0, 0;\n"
        "add.s64 tb, tb0, 1574;\n"
        "add.s64 ta, ta0, 1570;\n"
        "wgmma.mma_async.sync.aligned.m64n56k16.f16.f16.f16 {%0, %1, %2, %3, %4, %5, %6, %7, %8, %9, %10, %11, %12, %13}, ta, tb, p1, 1, 1, 0, 0;\n"
        "add.s64 tb, tb0, 3142;\n"
        "add.s64 ta, ta0, 3138;\n"
        "wgmma.mma_async.sync.aligned.m64n56k16.f16.f16.f16 {%0, %1, %2, %3, %4, %5, %6, %7, %8, %9, %10, %11, %12, %13}, ta, tb, p1, 1, 1, 0, 0;\n"
        "}\n"
        : "+r"(d[0]), "+r"(d[1]), "+r"(d[2]), "+r"(d[3]), "+r"(d[4]), "+r"(d[5]), "+r"(d[6]), "+r"(d[7]), "+r"(d[8]), "+r"(d[9]), "+r"(d[10]), "+r"(d[11]), "+r"(d[12]), "+r"(d[13])
        : "l"(descA), "n"(AOFF >> 4), "l"(descB), "n"(BOFF >> 4));
}

template <int BOFF, int AOFF, int NA>
__device__ __forceinline__ void mma_pv(uint32_t (&d)[14], const uint32_t (&a)[NA][4], uint64_t descB) {
    asm volatile(
        "{\n"
        ".reg .pred p0, p1;\n"
        ".reg .b64 ta, ta0, tb, tb0;\n"
        "setp.ne.b32 p0, 0, 0;\n"
        "setp.eq.b32 p1, 0, 0;\n"
        "add.s64 tb0, %30, %31;\n"
        "add.s64 tb, tb0, 0;\n"
        "wgmma.mma_async.sync.aligned.m64n56k16.f16.f16.f16 {%0, %1, %2, %3, %4, %5, %6, %7, %8, %9, %10, %11, %12, %13}, {%14, %15, %16, %17}, tb, p0, 1, 1, 1;\n"
        "add.s64 tb, tb0, 16;\n"
        "wgmma.mma_async.sync.aligned.m64n56k16.f16.f16.f16 {%0, %1, %2, %3, %4, %5, %6, %7, %8, %9, %10, %11, %12, %13}, {%18, %19, %20, %21}, tb, p1, 1, 1, 1;\n"
        "add.s64 tb, tb0, 32;\n"
        "wgmma.mma_async.sync.aligned.m64n56k16.f16.f16.f16 {%0, %1, %2, %3, %4, %5, %6, %7, %8, %9, %10, %11, %12, %13}, {%22, %23, %24, %25}, tb, p1, 1, 1, 1;\n"
        "add.s64 tb, tb0, 48;\n"
        "wgmma.mma_async.sync.aligned.m64n56k16.f16.f16.f16 {%0, %1, %2, %3, %4, %5, %6, %7, %8, %9, %10, %11, %12, %13}, {%26, %27, %28, %29}, tb, p1, 1, 1, 1;\n"
        "}\n"
        : "=r"(d[0]), "=r"(d[1]), "=r"(d[2]), "=r"(d[3]), "=r"(d[4]), "=r"(d[5]), "=r"(d[6]), "=r"(d[7]), "=r"(d[8]), "=r"(d[9]), "=r"(d[10]), "=r"(d[11]), "=r"(d[12]), "=r"(d[13])
        : "r"(a[AOFF + 0][0]), "r"(a[AOFF + 0][1]), "r"(a[AOFF + 0][2]), "r"(a[AOFF + 0][3]), "r"(a[AOFF + 1][0]), "r"(a[AOFF + 1][1]), "r"(a[AOFF + 1][2]), "r"(a[AOFF + 1][3]), "r"(a[AOFF + 2][0]), "r"(a[AOFF + 2][1]), "r"(a[AOFF + 2][2]), "r"(a[AOFF + 2][3]), "r"(a[AOFF + 3][0]), "r"(a[AOFF + 3][1]), "r"(a[AOFF + 3][2]), "r"(a[AOFF + 3][3]), "l"(descB), "n"(BOFF >> 4));
}

template <int AOFF, int BOFF>
__device__ __forceinline__ void mma_proj(float (&d)[96], uint64_t descA, uint64_t descB) {
    asm volatile(
        "{\n"
        ".reg .pred p0, p1;\n"
        ".reg .b64 ta, ta0, tb, tb0;\n"
        "setp.ne.b32 p0, 0, 0;\n"
        "setp.eq.b32 p1, 0, 0;\n"
        "add.s64 tb0, %98, %99;\n"
        "add.s64 ta0, %96, %97;\n"
        "add.s64 tb, tb0, 0;\n"
        "add.s64 ta, ta0, 0;\n"
        "wgmma.mma_async.sync.aligned.m64n192k16.f32.f16.f16 {%0, %1, %2, %3, %4, %5, %6, %7, %8, %9, %10, %11, %12, %13, %14, %15, %16, %17, %18, %19, %20, %21, %22, %23, %24, %25, %26, %27, %28, %29, %30, %31, %32, %33, %34, %35, %36, %37, %38, %39, %40, %41, %42, %43, %44, %45, %46, %47, %48, %49, %50, %51, %52, %53, %54, %55, %56, %57, %58, %59, %60, %61, %62, %63, %64, %65, %66, %67, %68, %69, %70, %71, %72, %73, %74, %75, %76, %77, %78, %79, %80, %81, %82, %83, %84, %85, %86, %87, %88, %89, %90, %91, %92, %93, %94, %95}, ta, tb, p0, 1, 1, 0, 1;\n"
        "add.s64 tb, tb0, 64;\n"
        "add.s64 ta, ta0, 2;\n"
        "wgmma.mma_async.sync.aligned.m64n192k16.f32.f16.f16 {%0, %1, %2, %3, %4, %5, %6, %7, %8, %9, %10, %11, %12, %13, %14, %15, %16, %17, %18, %19, %20, %21, %22, %23, %24, %25, %26, %27, %28, %29, %30, %31, %32, %33, %34, %35, %36, %37, %38, %39, %40, %41, %42, %43, %44, %45, %46, %47, %48, %49, %50, %51, %52, %53, %54, %55, %56, %57, %58, %59, %60, %61, %62, %63, %64, %65, %66, %67, %68, %69, %70, %71, %72, %73, %74, %75, %76, %77, %78, %79, %80, %81, %82, %83, %84, %85, %86, %87, %88, %89, %90, %91, %92, %93, %94, %95}, ta, tb, p1, 1, 1, 0, 1;\n"
        "add.s64 tb, tb0, 128;\n"
        "add.s64 ta, ta0, 4;\n"
        "wgmma.mma_async.sync.aligned.m64n192k16.f32.f16.f16 {%0, %1, %2, %3, %4, %5, %6, %7, %8, %9, %10, %11, %12, %13, %14, %15, %16, %17, %18, %19, %20, %21, %22, %23, %24, %25, %26, %27, %28, %29, %30, %31, %32, %33, %34, %35, %36, %37, %38, %39, %40, %41, %42, %43, %44, %45, %46, %47, %48, %49, %50, %51, %52, %53, %54, %55, %56, %57, %58, %59, %60, %61, %62, %63, %64, %65, %66, %67, %68, %69, %70, %71, %72, %73, %74, %75, %76, %77, %78, %79, %80, %81, %82, %83, %84, %85, %86, %87, %88, %89, %90, %91, %92, %93, %94, %95}, ta, tb, p1, 1, 1, 0, 1;\n"
        "add.s64 tb, tb0, 192;\n"
        "add.s64 ta, ta0, 6;\n"
        "wgmma.mma_async.sync.aligned.m64n192k16.f32.f16.f16 {%0, %1, %2, %3, %4, %5, %6, %7, %8, %9, %10, %11, %12, %13, %14, %15, %16, %17, %18, %19, %20, %21, %22, %23, %24, %25, %26, %27, %28, %29, %30, %31, %32, %33, %34, %35, %36, %37, %38, %39, %40, %41, %42, %43, %44, %45, %46, %47, %48, %49, %50, %51, %52, %53, %54, %55, %56, %57, %58, %59, %60, %61, %62, %63, %64, %65, %66, %67, %68, %69, %70, %71, %72, %73, %74, %75, %76, %77, %78, %79, %80, %81, %82, %83, %84, %85, %86, %87, %88, %89, %90, %91, %92, %93, %94, %95}, ta, tb, p1, 1, 1, 0, 1;\n"
        "add.s64 tb, tb0, 256;\n"
        "add.s64 ta, ta0, 512;\n"
        "wgmma.mma_async.sync.aligned.m64n192k16.f32.f16.f16 {%0, %1, %2, %3, %4, %5, %6, %7, %8, %9, %10, %11, %12, %13, %14, %15, %16, %17, %18, %19, %20, %21, %22, %23, %24, %25, %26, %27, %28, %29, %30, %31, %32, %33, %34, %35, %36, %37, %38, %39, %40, %41, %42, %43, %44, %45, %46, %47, %48, %49, %50, %51, %52, %53, %54, %55, %56, %57, %58, %59, %60, %61, %62, %63, %64, %65, %66, %67, %68, %69, %70, %71, %72, %73, %74, %75, %76, %77, %78, %79, %80, %81, %82, %83, %84, %85, %86, %87, %88, %89, %90, %91, %92, %93, %94, %95}, ta, tb, p1, 1, 1, 0, 1;\n"
        "add.s64 tb, tb0, 320;\n"
        "add.s64 ta, ta0, 514;\n"
        "wgmma.mma_async.sync.aligned.m64n192k16.f32.f16.f16 {%0, %1, %2, %3, %4, %5, %6, %7, %8, %9, %10, %11, %12, %13, %14, %15, %16, %17, %18, %19, %20, %21, %22, %23, %24, %25, %26, %27, %28, %29, %30, %31, %32, %33, %34, %35, %36, %37, %38, %39, %40, %41, %42, %43, %44, %45, %46, %47, %48, %49, %50, %51, %52, %53, %54, %55, %56, %57, %58, %59, %60, %61, %62, %63, %64, %65, %66, %67, %68, %69, %70, %71, %72, %73, %74, %75, %76, %77, %78, %79, %80, %81, %82, %83, %84, %85, %86, %87, %88, %89, %90, %91, %92, %93, %94, %95}, ta, tb, p1, 1, 1, 0, 1;\n"
        "add.s64 tb, tb0, 384;\n"
        "add.s64 ta, ta0, 516;\n"
        "wgmma.mma_async.sync.aligned.m64n192k16.f32.f16.f16 {%0, %1, %2, %3, %4, %5, %6, %7, %8, %9, %10, %11, %12, %13, %14, %15, %16, %17, %18, %19, %20, %21, %22, %23, %24, %25, %26, %27, %28, %29, %30, %31, %32, %33, %34, %35, %36, %37, %38, %39, %40, %41, %42, %43, %44, %45, %46, %47, %48, %49, %50, %51, %52, %53, %54, %55, %56, %57, %58, %59, %60, %61, %62, %63, %64, %65, %66, %67, %68, %69, %70, %71, %72, %73, %74, %75, %76, %77, %78, %79, %80, %81, %82, %83, %84, %85, %86, %87, %88, %89, %90, %91, %92, %93, %94, %95}, ta, tb, p1, 1, 1, 0, 1;\n"
        "add.s64 tb, tb0, 448;\n"
        "add.s64 ta, ta0, 518;\n"
        "wgmma.mma_async.sync.aligned.m64n192k16.f32.f16.f16 {%0, %1, %2, %3, %4, %5, %6, %7, %8, %9, %10, %11, %12, %13, %14, %15, %16, %17, %18, %19, %20, %21, %22, %23, %24, %25, %26, %27, %28, %29, %30, %31, %32, %33, %34, %35, %36, %37, %38, %39, %40, %41, %42, %43, %44, %45, %46, %47, %48, %49, %50, %51, %52, %53, %54, %55, %56, %57, %58, %59, %60, %61, %62, %63, %64, %65, %66, %67, %68, %69, %70, %71, %72, %73, %74, %75, %76, %77, %78, %79, %80, %81, %82, %83, %84, %85, %86, %87, %88, %89, %90, %91, %92, %93, %94, %95}, ta, tb, p1, 1, 1, 0, 1;\n"
        "add.s64 tb, tb0, 512;\n"
        "add.s64 ta, ta0, 1024;\n"
        "wgmma.mma_async.sync.aligned.m64n192k16.f32.f16.f16 {%0, %1, %2, %3, %4, %5, %6, %7, %8, %9, %10, %11, %12, %13, %14, %15, %16, %17, %18, %19, %20, %21, %22, %23, %24, %25, %26, %27, %28, %29, %30, %31, %32, %33, %34, %35, %36, %37, %38, %39, %40, %41, %42, %43, %44, %45, %46, %47, %48, %49, %50, %51, %52, %53, %54, %55, %56, %57, %58, %59, %60, %61, %62, %63, %64, %65, %66, %67, %68, %69, %70, %71, %72, %73, %74, %75, %76, %77, %78, %79, %80, %81, %82, %83, %84, %85, %86, %87, %88, %89, %90, %91, %92, %93, %94, %95}, ta, tb, p1, 1, 1, 0, 1;\n"
        "add.s64 tb, tb0, 576;\n"
        "add.s64 ta, ta0, 1026;\n"
        "wgmma.mma_async.sync.aligned.m64n192k16.f32.f16.f16 {%0, %1, %2, %3, %4, %5, %6, %7, %8, %9, %10, %11, %12, %13, %14, %15, %16, %17, %18, %19, %20, %21, %22, %23, %24, %25, %26, %27, %28, %29, %30, %31, %32, %33, %34, %35, %36, %37, %38, %39, %40, %41, %42, %43, %44, %45, %46, %47, %48, %49, %50, %51, %52, %53, %54, %55, %56, %57, %58, %59, %60, %61, %62, %63, %64, %65, %66, %67, %68, %69, %70, %71, %72, %73, %74, %75, %76, %77, %78, %79, %80, %81, %82, %83, %84, %85, %86, %87, %88, %89, %90, %91, %92, %93, %94, %95}, ta, tb, p1, 1, 1, 0, 1;\n"
        "add.s64 tb, tb0, 640;\n"
        "add.s64 ta, ta0, 1028;\n"
        "wgmma.mma_async.sync.aligned.m64n192k16.f32.f16.f16 {%0, %1, %2, %3, %4, %5, %6, %7, %8, %9, %10, %11, %12, %13, %14, %15, %16, %17, %18, %19, %20, %21, %22, %23, %24, %25, %26, %27, %28, %29, %30, %31, %32, %33, %34, %35, %36, %37, %38, %39, %40, %41, %42, %43, %44, %45, %46, %47, %48, %49, %50, %51, %52, %53, %54, %55, %56, %57, %58, %59, %60, %61, %62, %63, %64, %65, %66, %67, %68, %69, %70, %71, %72, %73, %74, %75, %76, %77, %78, %79, %80, %81, %82, %83, %84, %85, %86, %87, %88, %89, %90, %91, %92, %93, %94, %95}, ta, tb, p1, 1, 1, 0, 1;\n"
        "add.s64 tb, tb0, 704;\n"
        "add.s64 ta, ta0, 1030;\n"
        "wgmma.mma_async.sync.aligned.m64n192k16.f32.f16.f16 {%0, %1, %2, %3, %4, %5, %6, %7, %8, %9, %10, %11, %12, %13, %14, %15, %16, %17, %18, %19, %20, %21, %22, %23, %24, %25, %26, %27, %28, %29, %30, %31, %32, %33, %34, %35, %36, %37, %38, %39, %40, %41, %42, %43, %44, %45, %46, %47, %48, %49, %50, %51, %52, %53, %54, %55, %56, %57, %58, %59, %60, %61, %62, %63, %64, %65, %66, %67, %68, %69, %70, %71, %72, %73, %74, %75, %76, %77, %78, %79, %80, %81, %82, %83, %84, %85, %86, %87, %88, %89, %90, %91, %92, %93, %94, %95}, ta, tb, p1, 1, 1, 0, 1;\n"
        "}\n"
        : "+f"(d[0]), "+f"(d[1]), "+f"(d[2]), "+f"(d[3]), "+f"(d[4]), "+f"(d[5]), "+f"(d[6]), "+f"(d[7]), "+f"(d[8]), "+f"(d[9]), "+f"(d[10]), "+f"(d[11]), "+f"(d[12]), "+f"(d[13]), "+f"(d[14]), "+f"(d[15]), "+f"(d[16]), "+f"(d[17]), "+f"(d[18]), "+f"(d[19]), "+f"(d[20]), "+f"(d[21]), "+f"(d[22]), "+f"(d[23]), "+f"(d[24]), "+f"(d[25]), "+f"(d[26]), "+f"(d[27]), "+f"(d[28]), "+f"(d[29]), "+f"(d[30]), "+f"(d[31]), "+f"(d[32]), "+f"(d[33]), "+f"(d[34]), "+f"(d[35]), "+f"(d[36]), "+f"(d[37]), "+f"(d[38]), "+f"(d[39]), "+f"(d[40]), "+f"(d[41]), "+f"(d[42]), "+f"(d[43]), "+f"(d[44]), "+f"(d[45]), "+f"(d[46]), "+f"(d[47]), "+f"(d[48]), "+f"(d[49]), "+f"(d[50]), "+f"(d[51]), "+f"(d[52]), "+f"(d[53]), "+f"(d[54]), "+f"(d[55]), "+f"(d[56]), "+f"(d[57]), "+f"(d[58]), "+f"(d[59]), "+f"(d[60]), "+f"(d[61]), "+f"(d[62]), "+f"(d[63]), "+f"(d[64]), "+f"(d[65]), "+f"(d[66]), "+f"(d[67]), "+f"(d[68]), "+f"(d[69]), "+f"(d[70]), "+f"(d[71]), "+f"(d[72]), "+f"(d[73]), "+f"(d[74]), "+f"(d[75]), "+f"(d[76]), "+f"(d[77]), "+f"(d[78]), "+f"(d[79]), "+f"(d[80]), "+f"(d[81]), "+f"(d[82]), "+f"(d[83]), "+f"(d[84]), "+f"(d[85]), "+f"(d[86]), "+f"(d[87]), "+f"(d[88]), "+f"(d[89]), "+f"(d[90]), "+f"(d[91]), "+f"(d[92]), "+f"(d[93]), "+f"(d[94]), "+f"(d[95])
        : "l"(descA), "n"(AOFF >> 4), "l"(descB), "n"(BOFF >> 4));
}

struct Params {
    const __nv_bfloat16* x;
    const __nv_bfloat16* wqkv;
    const __nv_bfloat16* wo;
    const __nv_bfloat16* logit_scale;
    const __nv_bfloat16* cpb_w1;
    const __nv_bfloat16* cpb_w2;
    const __nv_bfloat16* rel_coords;
    const int*           rel_idx;
    const __nv_bfloat16* mask;
    __nv_bfloat16*       out;
    unsigned long long   z1;
    int                  npair;
    uint32_t             need;
    int                  spread;
    int                  t1;
};

constexpr uint32_t POS_END = 0x8000;
__device__ __forceinline__ uint32_t pos_add(uint32_t pos, int n) {
    pos += n;
    return (pos & 127) >= NWS ? pos + (128 - NWS) : pos;
}
__device__ __forceinline__ int role_of(const Params& P, int b) {
    const int n0 = ((b >> 1) * P.spread) >> 16, n1 = (((b >> 1) + 1) * P.spread) >> 16;
    return n1 != n0 ? 2 * P.npair + 2 * n0 + (b & 1) : b - 2 * n0;
}
__device__ __forceinline__ void finish(uint32_t total) {
    __threadfence();
    if (atomicAdd(&g_done, 1u) == total - 1) {
        for (int i = 0; i < NWS; i++) g_cnt[i] = 0;
        g_next[0] = 0; g_next[1] = 0;
        g_done = 0;
    }
}

constexpr int FB_PITCH = 584, FB_X = TOK * FB_PITCH * 2, FB_TAB = FB_X + TOK * 384, FB_BYTES = FB_TAB + 169 * 8 + 8;
static_assert(3 * FB_BYTES <= SM_PBAR && FB_BYTES % 16 == 0 && SM_BAR + B_ROWS == SM_PBAR + 64 && PCHUNK, "smem");
__device__ __forceinline__ void redo(const Params& P, uint8_t* sm, uint32_t tag, int barid) {
    typedef __nv_bfloat16 bf;
    const int t = threadIdx.x & 127, lane = t & 31;
    bf* const qkv = reinterpret_cast<bf*>(sm);
    bf* const xs = reinterpret_cast<bf*>(sm + FB_X);
    bf* const tab = reinterpret_cast<bf*>(sm + FB_TAB);
    volatile int* const next = reinterpret_cast<volatile int*>(sm + FB_TAB + 169 * 8);
#pragma unroll 1
    for (uint32_t n = 0; n < (1u << 22); n++) {
        uint32_t a;
        asm volatile("ld.acquire.gpu.global.u32 %0, [%1];\n" : "=r"(a) : "l"(g_guard) : "memory");
        if (a == tag + 1) break;
        __nanosleep(256);
    }
    asm volatile("fence.proxy.async;\n" ::: "memory");
#pragma unroll 1
    for (int i = t; i < 169 * 4; i += 128) {
        float a = 0.f;
#pragma unroll 1
        for (int u = 0; u < 16; u++) {
            const float h = round_bf16(__bfloat162float(P.rel_coords[(i >> 2) * 2]) * __bfloat162float(P.cpb_w1[u]) +
                                       __bfloat162float(P.rel_coords[(i >> 2) * 2 + 1]) * __bfloat162float(P.cpb_w1[16 + u]));
            a += (h > 0.f ? h : h * 0.f) * __bfloat162float(P.cpb_w2[u * 4 + (i & 3)]);
        }
        tab[i] = __float2bfloat16_rn(16.f * round_bf16(1.f / (1.f + expf(-round_bf16(a)))));
    }
#pragma unroll 1
    for (;;) {
        wg_bar(barid);
        if (t == 0) *next = (int)atomicAdd(g_guard + 2, 1u);
        wg_bar(barid);
        const int win = *next;
        if (win >= NWINDOWS) return;
        const int y0 = 7 * (win / NWS) + 3, x0 = 7 * (win % NWS) + 3;
        auto pixel = [&](int r) { return (size_t)(((y0 + r / 7) % IMG) * IMG + (x0 + r % 7) % IMG) * 192; };
#pragma unroll 1
        for (int i = t; i < TOK * 24; i += 128)
            reinterpret_cast<uint4*>(xs)[i] = reinterpret_cast<const uint4*>(P.x + pixel(i / 24))[i % 24];
#pragma unroll 1
        for (int ph = 0; ph < 2; ph++) {
            const bf* const a = ph ? qkv : xs;
            bf* const d = ph ? xs : qkv;
            const int n = ph ? 192 : 576, pa = ph ? FB_PITCH : 192, pd = ph ? 192 : FB_PITCH;
            wg_bar(barid);
#pragma unroll 1
            for (int col = t; col < n; col += 128) {
                const bf* w = (ph ? P.wo : P.wqkv) + col;
                float acc[TOK];
#pragma unroll
                for (int r = 0; r < TOK; r++) acc[r] = 0.f;
#pragma unroll 1
                for (int k = 0; k < 192; k += 2) {
                    const float w0 = __bfloat162float(w[k * n]), w1 = __bfloat162float(w[(k + 1) * n]);
#pragma unroll
                    for (int r = 0; r < TOK; r++) {
                        const uint32_t v = *reinterpret_cast<const uint32_t*>(a + r * pa + k);
                        acc[r] = fmaf(bf16hi(v), w1, fmaf(bf16lo(v), w0, acc[r]));
                    }
                }
#pragma unroll
                for (int r = 0; r < TOK; r++) d[r * pd + col] = __float2bfloat16_rn(acc[r]);
            }
            wg_bar(barid);
            if (ph) break;
#pragma unroll 1
            for (int i = t; i < TOK * 8; i += 128) {
                bf* const v = qkv + (i % TOK) * FB_PITCH + (i / TOK) * 48;
                float s = 0.f;
#pragma unroll 1
                for (int j = 0; j < 48; j++) s = fmaf(__bfloat162float(v[j]), __bfloat162float(v[j]), s);
                s = round_bf16(1.f / sqrtf(round_bf16(round_bf16(s) + 1e-12f)));
#pragma unroll 1
                for (int j = 0; j < 48; j++) v[j] = __float2bfloat16_rn(__bfloat162float(v[j]) * s);
            }
            wg_bar(barid);
#pragma unroll 1
            for (int i = t; i < TOK * 4; i += 128) {
                const int r = i % TOK, h = i / TOK;
                uint32_t* const q = reinterpret_cast<uint32_t*>(qkv + r * FB_PITCH + h * 48);
                const float tau = round_bf16(expf(round_bf16(fminf(fmaxf(__bfloat162float(P.logit_scale[h]), -100.f), 4.6052f))));
                float v[48], mx = -INFINITY, sum = 0.f;
#pragma unroll
                for (int j = 0; j < 24; j++) { v[2 * j] = bf16lo(q[j]); v[2 * j + 1] = bf16hi(q[j]); }
#pragma unroll 1
                for (int j = 0; j < TOK; j++) {
                    const uint32_t* kk = reinterpret_cast<const uint32_t*>(qkv + j * FB_PITCH + 192 + h * 48);
                    float s = 0.f;
#pragma unroll
                    for (int u = 0; u < 24; u++) s = fmaf(v[2 * u + 1], bf16hi(kk[u]), fmaf(v[2 * u], bf16lo(kk[u]), s));
                    s = round_bf16(round_bf16(s) * tau);
                    s = round_bf16(s + __bfloat162float(tab[min(max(P.rel_idx[r * TOK + j], 0), 168) * 4 + h]));
                    s = round_bf16(s + __bfloat162float(P.mask[(size_t)win * (TOK * TOK) + r * TOK + j]));
                    xs[j * 128 + t] = __float2bfloat16_rn(s);
                    mx = fmaxf(mx, s);
                }
#pragma unroll 1
                for (int j = 0; j < TOK; j++) sum += expf(__bfloat162float(xs[j * 128 + t]) - mx);
#pragma unroll
                for (int j = 0; j < 48; j++) v[j] = 0.f;
#pragma unroll 1
                for (int j = 0; j < TOK; j++) {
                    const uint32_t* vv = reinterpret_cast<const uint32_t*>(qkv + j * FB_PITCH + 384 + h * 48);
                    const float p = round_bf16(expf(__bfloat162float(xs[j * 128 + t]) - mx) / sum);
#pragma unroll
                    for (int u = 0; u < 24; u++) {
                        v[2 * u] = fmaf(p, bf16lo(vv[u]), v[2 * u]);
                        v[2 * u + 1] = fmaf(p, bf16hi(vv[u]), v[2 * u + 1]);
                    }
                }
#pragma unroll
                for (int j = 0; j < 24; j++) q[j] = pack_bf16(v[2 * j], v[2 * j + 1]);
            }
        }
#pragma unroll 1
        for (int r = t >> 5; r < TOK; r += 4) {
            float v[6], m = 0.f, s = 0.f;
#pragma unroll
            for (int j = 0; j < 6; j++) { v[j] = __bfloat162float(xs[r * 192 + j * 32 + lane]); m += v[j]; }
#pragma unroll
            for (int o = 16; o; o >>= 1) m += __shfl_xor_sync(0xffffffffu, m, o);
            m *= 1.f / 192.f;
#pragma unroll
            for (int j = 0; j < 6; j++) s = fmaf(v[j] - m, v[j] - m, s);
#pragma unroll
            for (int o = 16; o; o >>= 1) s += __shfl_xor_sync(0xffffffffu, s, o);
            s = round_bf16(sqrtf(round_bf16(round_bf16(s * (1.f / 192.f)) + 1e-5f)));
            m = round_bf16(m);
#pragma unroll
            for (int j = 0; j < 6; j++) P.out[pixel(r) + j * 32 + lane] = __float2bfloat16_rn(round_bf16(v[j] - m) / s);
        }
    }
}

__global__ void __launch_bounds__(NTHREADS, 1)
swin_window_attn_kernel(const Params P, const __grid_constant__ CUtensorMap xmap, const __grid_constant__ CUtensorMap xmap4,
                        const __grid_constant__ CUtensorMap xmap3,
                        const __grid_constant__ CUtensorMap omap, const __grid_constant__ CUtensorMap wmap,
                        const __grid_constant__ CUtensorMap smap, const __grid_constant__ CUtensorMap omapb,
                        const __grid_constant__ CUtensorMap xmapa, const __grid_constant__ CUtensorMap xmapb,
                        const __grid_constant__ CUtensorMap smap3, const __grid_constant__ CUtensorMap wraw,
                        const __grid_constant__ CUtensorMap smapw) {
    extern __shared__ __align__(1024) uint8_t smem[];
    constexpr uint32_t sbase = 1024;
    if (smem_u32(smem) != sbase) return;
    const int tid = threadIdx.x;
    const int wg = __shfl_sync(0xffffffffu, tid >> 7, 0);
    const int warp = __shfl_sync(0xffffffffu, (tid >> 5) & 3, 0);
    const int lane = tid & 31;
    const int g = lane >> 2, c = lane & 3;

    TR(26, wg);
    if (wg == 0) { ST(0); SC(27); }
    const int role = role_of(P, blockIdx.x);
    const bool attn = role < 2 * P.npair;
    const int pair = role >> 1, half = role & 1;
    const uint32_t bars = sbase + SM_BAR;
    const bool first = wg == 3 && warp == 3;
    if (first) {
        if (lane == 0) {
            mbar_init(bars + B_WRAW, 1);
            mbar_init(bars + B_WFULL, 1);
            mbar_init(bars + B_MFULL, 1);
            for (int b = 0; b < 4; b++) mbar_init(bars + B_XFULL + b * 8, 2);
            asm volatile("fence.mbarrier_init.release.cluster;\n" ::: "memory");
            fence_async_smem();
        }
        __syncwarp();
        asm volatile("bar.arrive 0, 512;\n" ::: "memory");
        if (attn && elect_one()) {
            mbar_arrive_expect_tx(bars + B_WRAW, 12 * W_ATOM);
            TR(26, 30);
            asm volatile("prefetch.tensormap [%0];\n" :: "l"(reinterpret_cast<uint64_t>(&wmap)) : "memory");
            asm volatile("prefetch.tensormap [%0];\n" :: "l"(reinterpret_cast<uint64_t>(XPF ? &wraw : &xmap)) : "memory");
            if (XPF == 1) {
                const uint32_t pos = half ? pos_add(pair, P.npair) : pair;
#pragma unroll
                for (int ch = 0; ch < 3; ch++)
                    asm volatile("cp.async.bulk.prefetch.tensor.3d.L2.global.tile [%0, {%1, %2, %3}];\n"
                                 :: "l"(reinterpret_cast<uint64_t>(&xmap)), "r"(ch * 64), "r"(7 * (pos & 127) + 3), "r"(7 * (pos >> 7) + 3)
                                 : "memory");
            }
            if (XPF == 2) {
                const uint32_t pos = half ? pos_add(pair, P.npair) : pair;
                const char* src = reinterpret_cast<const char*>(P.x) + ((7 * (pos >> 7) + 3) * IMG + 7 * (pos & 127) + 3) * 384;
#pragma unroll
                for (int r = 0; r < 7; r++)
                    asm volatile("cp.async.bulk.prefetch.L2.global [%0], 2688;\n" :: "l"(src + r * IMG * 384) : "memory");
                asm volatile("prefetch.tensormap [%0];\n" :: "l"(reinterpret_cast<uint64_t>(&xmap)) : "memory");
            }
#pragma unroll
            for (int i = 0; i < 2; i++) tma_2d(sbase + i * 6 * W_ATOM, &wraw, bars + B_WRAW, i * 192 + half * 128, 0);
            TR(26, 31);
#pragma unroll
            for (int i = 0; i < 2; i++) tma_2d(sbase + (i * 6 + 4) * W_ATOM, &wmap, bars + B_WRAW, i * 192 + 64 + half * 32, 0);
            TR(26, 33);
            int wh = 0, ww = pair;
#pragma unroll
            for (int j = 0; j < NEARLY; j++) {
                if (ww < NWS - 1) {
                    const uint32_t bar = bars + B_XFULL + (j ? j - 1 : 0) * 8;
                    if (j >= 2) mbar_arrive(bar);
                    mbar_arrive_expect_tx(bar, 3 * XCH);
#pragma unroll
                    for (int ch = 0; ch < 3; ch++)
                        tma_3d(sbase + SM_QK + ((j + 3) & 3) * XCH + ch * QK_CHUNK, &xmap, bar, ch * 64, 7 * ww + 3, 7 * wh + 3);
                }
                ww += P.npair; if (ww >= NWS) { ww -= NWS; wh++; }
                TR(26, 40 + j);
                if (j == 1) {
                    mbar_arrive_expect_tx(bars + B_WFULL, 6 * W_ATOM);
                    tma_2d(sbase + SM_WV, &wraw, bars + B_WFULL, 384 + half * 128, 0);
                    tma_2d(sbase + SM_WV + 4 * W_ATOM, &wmap, bars + B_WFULL, 384 + 64 + half * 32, 0);
                    mbar_arrive_expect_tx(bars + B_MFULL, 4816);
                    asm volatile("cp.async.bulk.shared::cluster.global.mbarrier::complete_tx::bytes [%0], [%1], 4816, [%2];\n"
                                 :: "r"(sbase + SM_MASK), "l"(reinterpret_cast<const char*>(P.mask) + (((uint32_t)pair * 4802u) & ~15u)),
                                    "r"(bars + B_MFULL) : "memory");
                    TR(26, 50);
                }
            }
        }
        __syncwarp();
    }
    const int t0 = min(warp * 16 + g, TOK - 1), t1 = min(warp * 16 + g + 8, TOK - 1);
    int ridx[26];
    uint32_t rc, w2[16];
    uint4 w1[4];
    if (attn && wg == 0) rc = reinterpret_cast<const uint32_t*>(P.logit_scale)[half];
    if (attn && (wg == 1 || wg == 2)) {
        rc = reinterpret_cast<const uint32_t*>(P.rel_coords)[min(tid - 128, 168)];
#pragma unroll
        for (int i = 0; i < 4; i++) w1[i] = reinterpret_cast<const uint4*>(P.cpb_w1)[i];
#pragma unroll
        for (int u = 0; u < 16; u++) w2[u] = reinterpret_cast<const uint32_t*>(P.cpb_w2)[2 * u + half];
#pragma unroll
        for (int rh = 0; rh < 2; rh++) {
            const int* ri = P.rel_idx + (rh ? t1 : t0) * TOK;
#pragma unroll
            for (int j = 0; j < 12; j++) ridx[13 * rh + j] = ri[8 * (j >> 1) + 2 * c + (j & 1)];
            ridx[13 * rh + 12] = ri[48];
        }
    }
    {
        if (tid == 416) {
            const CUtensorMap* maps[4] = {attn ? &smap : &omap, &smap3, &xmapa, &xmapb};
#pragma unroll
            for (int i = 0; i < 4; i++) asm volatile("prefetch.tensormap [%0];\n" :: "l"(reinterpret_cast<uint64_t>(maps[i])) : "memory");
        }
        if (tid == 384) {
            for (int b = 0; b < 4; b++) {
                mbar_init(bars + B_QKRAW + b * 8, 4);
                mbar_init(bars + B_VRAW + b * 8, 4);
                mbar_init(bars + B_VFREE + b * 8, 2);
                mbar_init(bars + B_QKFREE + b * 8, 4);
                mbar_init(bars + B_ODONE + b * 8, 4);
            }
            sts32(bars + B_MSTATE, 0);
            sts32(bars + B_MSTATE + 4, 0x7FFFFFFF);
            sts32(bars + B_NTILES, 0x7FFFFFFF);
            sts128(bars + B_DYN, ~0u, ~0u, ~0u, ~0u);
            sts128(bars + B_DYN + 16, ~0u, ~0u, ~0u, ~0u);
            mbar_init(bars + B_GDONE, 4);
            sts32(bars + B_ROWS, 0xFFFFFFFFu);
            mbar_init(bars + B_MCONS, 4);
            mbar_init(bars + B_XCONS, 4);
            for (int b = 0; b < 4; b++) mbar_init(bars + B_STORED + b * 8, 1);
            for (int b = 0; b < 6; b++) {
                mbar_init(sbase + SM_PBAR + b * 8, 1);
                if (PCHUNK) sts32(sbase + SM_PBAR + 48, 0); else
                mbar_init(sbase + SM_PBAR + 48 + b * 8, PSTORE ? 1 : 4);
                mbar_init(sbase + SM_PBAR + 104 + b * 8, 4);
            }
            mbar_init(sbase + SM_PBAR + 96, attn ? 13 : 12);
            if (MPRE && !attn) for (int b = 0; b < 12 * MBUFS; b++) mbar_init(sbase + SM_MBAR + b * 8, 1);
            mbar_init(sbase + SM_PBAR + 56, 12);
            asm volatile("fence.mbarrier_init.release.cluster;\n" ::: "memory");
        }
        if (wg == 3) {
            static_assert(4 * O_STRIDE == 3 * V_STRIDE + 13 * GRP, "layout");
            if (attn && lane < 16 && warp < 3)
                *reinterpret_cast<uint4*>(smem + SM_V + warp * V_STRIDE + 13 * GRP + lane * 16) = make_uint4(0, 0, 0, 0);
            fence_async_smem();
        }
        if (!first) asm volatile("bar.sync 0, 512;\n" ::: "memory");
        if (wg == 3 && warp == 0) asm volatile("bar.arrive 15, 64;\n" ::: "memory");
        if (first) asm volatile("bar.sync 15, 64;\n" ::: "memory");
        TR(26, 4 + wg);
        TR(26, 13);
    }

    auto raw_w = [&](int rg, int cc) {
        const uint32_t ca = cc - 4 * half, row = rg * 8 + (lane & 7);
        return ca < 8 ? row * 128 + ((ca ^ (lane & 7)) << 4) : 4 * W_ATOM + row * 64 + (((cc ^ (lane >> 1)) & 3) << 4);
    };
    auto permute_a = [&]() {
        uint2 w[9][4];
        uint32_t src[3][2], step[3][2];
        const int rg = ((tid >> 5) - 4) * 3;
#pragma unroll
        for (int i = 0; i < 6; i++) {
            const int cc = (i >> 1) * 2 + (i & 1) * 6;
            src[i >> 1][i & 1] = raw_w(rg, cc + (lane >> 4)) + (lane & 8);
            step[i >> 1][i & 1] = (uint32_t)(cc - 4 * half) < 8 ? 1024 : 512;
        }
        reg_fence(src);
        TR(26, 16 + wg);
        mbar_wait(bars + B_WRAW, 0);
        TR(26, 20 + wg);
#pragma unroll
        for (int i = 0; i < 9; i++)
#pragma unroll
            for (int m = 0; m < 4; m++)
                w[i][m] = *reinterpret_cast<const uint2*>(smem + (m >> 1) * 6 * W_ATOM + src[i % 3][m & 1] + (i / 3) * step[i % 3][m & 1]);
        asm volatile("bar.sync 2, 256;\n" ::: "memory");
        TR(26, 24 + wg);
        const uint32_t d = sbase + (lane >> 3) * W_ATOM + (rg * 8 + (lane & 7)) * 32 + ((lane >> 2) & 1) * 16;
#pragma unroll
        for (int i = 0; i < 9; i++) {
            sts128(d + (i % 3) * 4 * W_ATOM + (i / 3) * 256, bf2h(w[i][0].x), bf2h(w[i][1].x), bf2h(w[i][2].x), bf2h(w[i][3].x));
            sts128((d ^ 16) + (i % 3) * 4 * W_ATOM + (i / 3) * 256, bf2h(w[i][0].y), bf2h(w[i][1].y), bf2h(w[i][2].y), bf2h(w[i][3].y));
        }
    };
    auto permute_w = [&]() {
        uint4 w[3][4];
        uint32_t src[3][2];
#pragma unroll
        for (int it = 0; it < 3; it++) {
            const int o = ((tid >> 5) * 3 + it) * 4 + (lane >> 3);
            src[it][0] = raw_w(o / 6, o % 6);
            src[it][1] = raw_w(o / 6, o % 6 + 6);
        }
        reg_fence(src);
        TR(26, 16 + wg);
        mbar_wait(bars + B_WRAW, 0);
        TR(26, 20 + wg);
#pragma unroll
        for (int it = 0; it < 3; it++) {
#pragma unroll
            for (int m = 0; m < 4; m++)
                w[it][m] = *reinterpret_cast<const uint4*>(smem + (m >> 1) * 6 * W_ATOM + src[it][m & 1]);
        }
        asm volatile("bar.sync 2, 384;\n" ::: "memory");
        TR(26, 24 + wg);
#pragma unroll
        for (int it = 0; it < 3; it++) {
            const int o = ((tid >> 5) * 3 + it) * 4 + (lane >> 3);
            const uint32_t d = sbase + (o % 6) * 2 * W_ATOM + ((o / 6) * 8 + (lane & 7)) * 32 + ((lane >> 2) & 1) * 16;
            sts128(d, bf2h(w[it][0].x), bf2h(w[it][1].x), bf2h(w[it][2].x), bf2h(w[it][3].x));
            sts128(d ^ 16, bf2h(w[it][0].y), bf2h(w[it][1].y), bf2h(w[it][2].y), bf2h(w[it][3].y));
            sts128(d + W_ATOM, bf2h(w[it][0].z), bf2h(w[it][1].z), bf2h(w[it][2].z), bf2h(w[it][3].z));
            sts128((d ^ 16) + W_ATOM, bf2h(w[it][0].w), bf2h(w[it][1].w), bf2h(w[it][2].w), bf2h(w[it][3].w));
        }
    };
    const uint32_t nfinish = gridDim.x + (POLLER ? 0 : 2 * P.npair);
#define PROJ_SCHEDULE                                                                                   \
    int bid = blockIdx.x;                                                                               \
    asm volatile("" : "+r"(bid));                      \
    bid = role_of(P, bid);                                                                              \
    const bool at = bid < 2 * P.npair;                                                                  \
    const int tile0 = at ? P.t1 + bid : bid - 2 * P.npair;                                              \
    const int tstep = at ? 2 * P.npair : (int)gridDim.x - 2 * P.npair;                                  \
    const int tend = at ? TILES : P.t1;
    if (wg == 3) {
        TR(26, 60 + warp);
        asm volatile("setmaxnreg.dec.sync.aligned.u32 %0;\n" :: "n"(REG_H));
        TR(26, 64 + warp);
#define MST_OFF 0
        if (warp == 1 && attn) {
            const uint16_t mlast = reinterpret_cast<const uint16_t*>(P.mask)[NWINDOWS * TOK * TOK - 1];
            const uint32_t ma = sbase + SM_MASK + 16 + lane * 16, mb = sbase + SM_MASK + min(289 + lane, 299) * 16;
            const uint32_t mc = sbase + SM_MASK + (lane & 7) * 2 + (lane & 8) * 600;
            uint32_t ph = 0, win = pair, fp = 0, nzl = 0;
#pragma unroll 1
            for (int k = 0;; k++) {
                mbar_wait(bars + B_MFULL, fp);
                uint32_t acc = lds16(mc);
                if ((lane & 15) - (win & 7) > 8u) acc = 0;
#pragma unroll
                for (int i = 0; i < 10; i += MRND) {
                    uint32_t w[MRND][4];
#pragma unroll
                    for (int j = 0; j < MRND; j++) if (i + j < 10) lds128(w[j], i + j < 9 ? ma + (i + j) * 512 : mb);
#pragma unroll
                    for (int j = 0; j < MRND; j++) if (i + j < 10) acc |= w[j][0] | w[j][1] | w[j][2] | w[j][3];
                    asm volatile("" : "+r"(acc) :: "memory");
                }
                uint32_t nz = __any_sync(0xffffffffu, (acc & 0x7FFF7FFFu) != 0) ? 1 : 0;
                if (lane == 0) asm volatile("st.volatile.shared.b32 [%0], %1;\n" :: "r"(MST_OFF ? sbase + SM_DUMP : bars + B_MSTATE), "r"(32 * k + 32 - 16 * nz + (2 * win & 14) + fp) : "memory");
                fp ^= 1;
                if (k + 1 == MPRE) {
                    uint32_t tag;
                    asm volatile("ld.relaxed.gpu.global.u32 %0, [%1];\n" : "=r"(tag) : "l"(g_guard) : "memory");
#pragma unroll 1
                    for (uint32_t n = 0; n < (1u << 20); n++) {
                        bool ok = true;
                        nzl = 0;
#pragma unroll
                        for (int j = 0; j < 3; j++) {
                            uint32_t f;
                            asm volatile("ld.relaxed.gpu.global.u32 %0, [%1];\n" : "=r"(f) : "l"(g_mz + pair * 128 + 32 * j + lane) : "memory");
                            ok = ok && ((f | 1) == (tag | 255) || 32 * j + lane < MPRE || 32 * j + lane >= MEND);
                            nzl |= (~f & 1) << j;
                        }
                        if (__all_sync(0xffffffffu, ok)) break;
                        nzl = 7;
                        __nanosleep(RSLEEP);
                    }
                }
                if (k + 1 >= MPRE && k + 1 < MEND) {
                    uint32_t kn = MEND;
#pragma unroll
                    for (int j = 0; j < 3; j++) if ((nzl >> j & 1) && 32 * j + lane > k) kn = min(kn, 32 * j + lane);
                    kn = __reduce_min_sync(0xffffffffu, kn);
                    if (kn > k + 1) {
                        if (nz) { mbar_wait(bars + B_MCONS, ph); ph ^= 1; fence_async_smem(); nz = 0; }
                        if (lane == 0) asm volatile("st.volatile.shared.b32 [%0], %1;\n" :: "r"(bars + B_MSTATE), "r"(32 * kn) : "memory");
                        k = kn - 1;
                        win = pair + k * P.npair;
                    }
                }
                win += P.npair;
                if (k + 1 >= NSTATIC) {
                    uint32_t e = 0xFFFF;
#pragma unroll 1
                    for (uint32_t n = 0; n < (1u << 20); n++) {
                        e = lds16v(bars + B_DYN + (k + 1 - NSTATIC) * 2);
                        if (__all_sync(0xffffffffu, e != 0xFFFF)) break;
                        __nanosleep(RSLEEP);
                    }
                    if (__any_sync(0xffffffffu, e >= POS_END)) break;
                    win = e - (e >> 7) * (128 - NWS);
                }
                if (nz && !MST_OFF) { mbar_wait(bars + B_MCONS, ph); ph ^= 1; fence_async_smem(); }
                if (elect_one()) {
                    uint32_t bytes = 4816;
                    if (win == NWINDOWS - 1) {
                        bytes = 4800;
                        asm volatile("st.shared.u16 [%0], %1;\n" :: "r"(sbase + SM_MASK + 4800), "h"(mlast) : "memory");
                    }
                    TR(25, k + 1);
                    mbar_arrive_expect_tx(bars + B_MFULL, bytes);
                    asm volatile("cp.async.bulk.shared::cluster.global.mbarrier::complete_tx::bytes [%0], [%1], %2, [%3];\n"
                                 :: "r"(sbase + SM_MASK),
                                    "l"(reinterpret_cast<const char*>(P.mask) + (((uint32_t)win * 4802u) & ~15u)),
                                    "r"(bytes), "r"(bars + B_MFULL) : "memory");
                    if (MPF && half == (win & 1) && win + MPF * P.npair < NWINDOWS && (!MPRE || k + 1 + MPF < MPRE || k + 1 >= MEND))
                        asm volatile("cp.async.bulk.prefetch.L2.global [%0], %1;\n"
                                     :: "l"(reinterpret_cast<const char*>(P.mask) + (((uint32_t)(win + MPF * P.npair) * 4802u) & ~15u)),
                                        "r"(4800) : "memory");
                }
                __syncwarp();
            }
        }
        if (!elect_one()) return;
        TR(26, 68 + warp);
        if (warp == 0) {
          if (attn) {
            int kmax = 1 << 20, rows = 1 << 30;
            uint32_t cur = pair, pos1 = pos_add(cur, P.npair), pos2 = pos_add(pos1, P.npair);
#pragma unroll 1
            for (int k = -4; k + 4 <= kmax; k++) {
                const int row0 = (k + 4) * TOK;
                const uint32_t dst = sbase + SM_QK + ((k + 3) & 3) * XCH, bar = bars + B_XFULL + ((row0 >> 6) & 3) * 8;
                const bool alone = (row0 & 63) >= 64 - TOK && (row0 & 63) < TOK;
                const int wh = cur >> 7, ww = cur & 127;
                uint32_t claim = NWINDOWS;
                if (k + 7 >= NSTATIC && k + 7 < NSTATIC + 15 && pos2 < POS_END)
                    asm volatile("atom.relaxed.gpu.global.add.u32 %0, [%1], 1;\n" : "=r"(claim) : "l"(g_next + half) : "memory");
                const int x0 = 7 * ww + 3, y0 = 7 * wh + 3;
                const bool done = k < NEARLY - 4 && ww < NWS - 1;
                if (k >= 0) mbar_wait(bars + B_QKFREE + ((k + 3) & 3) * 8, (k >> 2) & 1);
                if (alone && !done) mbar_arrive(bar);
                if (row0 >= rows || ((EXP & 32) && k >= 0)) {
                    mbar_arrive(bar);
                    continue;
                }
                TR(20, k + 4);
                const bool inner = wh < NWS - 1 && ww < NWS - 1;
                if (done) {
                } else if (XSPLIT && inner && (row0 & 63) >= 64 - 21) {
                    const uint32_t bar2 = bars + B_XFULL + (((row0 >> 6) + 1) & 3) * 8;
                    mbar_arrive_expect_tx(bar, 3 * 21 * 128);
#pragma unroll
                    for (int ch = 0; ch < 3; ch++) tma_3d(dst + ch * QK_CHUNK, &xmapa, bar, ch * 64, x0, y0);
                    asm volatile("mbarrier.expect_tx.relaxed.cta.shared::cta.b64 [%0], %1;\n" :: "r"(bar2), "r"(3 * 28 * 128) : "memory");
#pragma unroll
                    for (int ch = 0; ch < 3; ch++) tma_3d(dst + ch * QK_CHUNK + 21 * 128, &xmapb, bar2, ch * 64, x0, y0 + 3);
                } else if (inner) {
                    mbar_arrive_expect_tx(bar, 3 * XCH);
#pragma unroll
                    for (int ch = 0; ch < 3; ch++) tma_3d(dst + ch * QK_CHUNK, &xmap, bar, ch * 64, x0, y0);
                } else if (ww < NWS - 1) {
                    mbar_arrive_expect_tx(bar, 3 * XCH);
#pragma unroll
                    for (int ch = 0; ch < 3; ch++) {
                        tma_3d(dst + ch * QK_CHUNK, &xmapb, bar, ch * 64, x0, y0);
                        tma_3d(dst + ch * QK_CHUNK + 28 * 128, &xmapa, bar, ch * 64, x0, 0);
                    }
                } else {
                    mbar_arrive_expect_tx(bar, 3 * XCH);
                    const int x1 = (ww == NWS - 1) ? 0 : x0 + 4;
#pragma unroll 1
                    for (int i = 0; i < 7; i++) {
                        const int y = (y0 + i >= IMG) ? y0 + i - IMG : y0 + i;
#pragma unroll
                        for (int ch = 0; ch < 3; ch++) {
                            tma_3d(dst + ch * QK_CHUNK + i * 896, &xmap4, bar, ch * 64, x0, y);
                            tma_3d(dst + ch * QK_CHUNK + i * 896 + 512, &xmap3, bar, ch * 64, x1, y);
                        }
                    }
                }
                if (pos1 < POS_END) cur = pos1;
                pos1 = pos2;
                if (k + 7 < NSTATIC) {
                    pos2 = pos_add(pos2, P.npair);
                } else if (pos2 < POS_END) {
                    sts32(bars + B_NTILES + 4, claim);
                    const uint32_t w = lds32v(bars + B_NTILES + 4) + NSTATIC * P.npair;
                    pos2 = w < NWINDOWS ? w + __umulhi(w, 58835169u) * (128 - NWS) : POS_END;
                    sts16(bars + B_DYN + (k + 7 - NSTATIC) * 2, pos2);
                    if (pos2 == POS_END) {
                        rows = (row0 + 3 * TOK + 63) & ~63;
                        kmax = (rows + 63) / TOK;
                        sts32(bars + B_MSTATE + 4, k + 7);
                        sts32(bars + B_NTILES, rows >> 6);
                        if (role < SM_STAGE / 1024)
                            asm volatile("cp.async.bulk.prefetch.L2.global [%0], 1024;\n" :: "l"(g_wo + role * 1024) : "memory");
                    }
                }
                if (!NOPF && half == 0 && pos2 < POS_END) {
#pragma unroll
                    for (int ch = 0; ch < 3; ch++)
                        asm volatile("cp.async.bulk.prefetch.tensor.3d.L2.global.tile [%0, {%1, %2, %3}];\n"
                                     :: "l"(reinterpret_cast<uint64_t>(&xmap)), "r"(ch * 64), "r"(7 * (pos2 & 127) + 3), "r"(7 * (pos2 >> 7) + 3)
                                     : "memory");
                }
            }
            {
#pragma unroll 1
                for (uint32_t n = 0; n < (1u << 22); n++) {
                    uint32_t a, b;
                    asm volatile("ld.relaxed.gpu.global.u32 %0, [%1];\n" : "=r"(b) : "l"(g_guard) : "memory");
                    asm volatile("ld.acquire.gpu.global.u32 %0, [%1];\n" : "=r"(a) : "l"(g_guard + 3) : "memory");
                    if (a == (b | 255)) break;
                }
                asm volatile("fence.proxy.async.global;\n" ::: "memory");
                mbar_arrive_expect_tx(bars + B_WRAW, SM_STAGE);
                mbar_wait(bars + B_GDONE, 0);
#pragma unroll
                for (int i = 0; i < WOSPLIT; i++)
                    asm volatile("cp.async.bulk.shared::cluster.global.mbarrier::complete_tx::bytes [%0], [%1], %2, [%3];\n"
                                 :: "r"(sbase + SM_WO + i * (SM_STAGE / WOSPLIT)), "l"(g_wo + i * (SM_STAGE / WOSPLIT)),
                                    "n"(SM_STAGE / WOSPLIT), "r"(bars + B_WRAW) : "memory");
            }
          }
            mbar_wait(sbase + SM_PBAR + 96, 0);
            ST(15);
            fence_async_smem();
            PROJ_SCHEDULE
            int st = 0, ready = -1, want = -6 * PSM, freed = 0;
            uint32_t ph = 1;
#pragma unroll 1
            for (int t = tile0; t < tend; t += tstep) {
                const int p0 = (t < TILES_A) ? SEG_B + 64 * (t & PWRAP) : 64 * (t - TILES_A);
                const int w1 = (t < TILES_A) ? min((64 * t + 63) / (7 * IMG), NWS - 1) : NWS - 1;
#pragma unroll 1
                for (uint32_t n = 0; n < (1u << 24) && ready < w1; n++) ready = (int)lds32v(bars + B_ROWS);
#pragma unroll
                for (int ch = 0; ch < PSM; ch++) {
                    want++;
#pragma unroll 1
                    for (uint32_t n = 0; n < (1u << 22) && freed < want; n++) freed = (int)lds32v(sbase + SM_PBAR + 48);
                    if (ch == 0) mbar_arrive_expect_tx(sbase + SM_PBAR + st * 8, STAGE_BYTES);
                    tma_2d(sbase + SM_STAGE + st * STAGE_BYTES + ch * 8192, &omap, sbase + SM_PBAR + st * 8, ch * 64, p0);
                    if (ch == 0) {
#pragma unroll
                        for (int c2 = PSM; c2 < 3; c2++)
                            tma_2d(sbase + SM_STAGE + st * STAGE_BYTES + c2 * 8192, &omap, sbase + SM_PBAR + st * 8, c2 * 64, p0);
                    }
                }
                if (++st == 6) st = 0;
            }
            if (!POLLER) finish(nfinish);
        } else if (warp == 2 && (POLLER || attn)) {
            CK(0);
            uint32_t rows = 0, cur = attn ? pair : POS_END;
#pragma unroll 1
            for (int k = 0; cur < POS_END; k++) {
                const uint32_t wh = cur >> 7;
                mbar_wait(bars + B_STORED + (k & 1) * 8, (k >> 1) & 1);
                mbar_arrive(bars + B_PUBD + (k & 1) * 8);
                rows = rows * 128 + wh + 1;
                cur = k + 1 < NSTATIC ? pos_add(cur, P.npair) : lds16v(bars + B_DYN + (k + 1 - NSTATIC) * 2);
                if (rows >= (1u << (7 * PUBN - 7)) || k < 2 || cur >= (NWS - PUBT) * 128) {
                    asm volatile("fence.release.gpu;\n" ::: "memory");
#pragma unroll 1
                    for (; rows; rows >>= 7)
                        asm volatile("red.relaxed.gpu.global.add.u32 [%0], 1;\n" :: "l"(g_cnt + ((rows & 127) - 1)) : "memory");
                }
                TR(24, k);
                CK(k + 1);
                if (k == 30) { ST(9); SC(29); }
                if (k == 60) { ST(10); SC(30); }
                if (k == 90) { ST(11); SC(31); }
            }
            ST(14);
            const int r1 = attn ? NWS - 1 : min((64 * P.t1 - 1) / (7 * IMG), NWS - 1);
#pragma unroll 1
            for (int r = attn ? min(64 * P.t1 / (7 * IMG), NWS - 1) : 0; r <= r1; r++) {
#pragma unroll 1
                for (uint32_t n = 0; n < (1u << 22); n++) {
                    uint32_t a;
                    asm volatile("ld.relaxed.gpu.global.u32 %0, [%1];\n" : "=r"(a) : "l"(g_cnt + r) : "memory");
                    if (a >= P.need) break;
                    __nanosleep(64);
                }
                asm volatile("fence.acquire.gpu;\n" ::: "memory");
                asm volatile("fence.proxy.async.global;\n" ::: "memory");
                asm volatile("st.volatile.shared.b32 [%0], %1;\n" :: "r"(bars + B_ROWS), "r"(r) : "memory");
                if (r >= 66) ST(20 + r - 66);
            }
            finish(nfinish);
        } else if (warp == 3 && attn) {
            for (int t = 0; t < 3; t++) mbar_arrive_n(bars + B_VFREE + t * 8, 2);
            uint32_t cur = pair;
#pragma unroll 1
            for (int k = 0; cur < POS_END; k++) {
                const int wh = cur >> 7, ww = cur & 127;
                const uint32_t src = sbase + SM_V + (k & 3) * O_STRIDE;
                const int x0 = 7 * ww + 3, y0 = 7 * wh + 3;
                mbar_wait(bars + B_ODONE + (k & 3) * 8, (k >> 2) & 1);
                if (!(WFEN & 2)) fence_async_smem();
                TR(22, k);
                if (ww == NWS - 1) {
#pragma unroll 1
                    for (int i = 0; i < 7; i++)
                        tma_store_4d(&smapw, src + ((7 * i + 4) & ~1) * 192, 0, 3 * half, ~i & 1, y0 + i >= IMG ? y0 + i - IMG : y0 + i);
                    asm volatile("cp.async.bulk.commit_group;\n" ::: "memory");
                    asm volatile("cp.async.bulk.wait_group 0;\n" ::: "memory");
                }
                tma_store_4d(&smap, src, 0, 3 * half, x0, y0);
                if (wh == NWS - 1) tma_store_4d(&smap3, src + 28 * 192, 0, 3 * half, x0, 0);
                asm volatile("cp.async.bulk.commit_group;\n" ::: "memory");
                asm volatile("cp.async.bulk.wait_group.read 0;\n" ::: "memory");
                {
                    const int row0 = (k + 4) * TOK;
                    mbar_arrive_n(bars + B_VFREE + ((row0 >> 6) & 3) * 8, ((row0 & 63) >= 64 - TOK && (row0 & 63) < TOK) ? 2 : 1);
                }
                TR(23, k);
                cur = k + 1 < NSTATIC ? pos_add(cur, P.npair) : lds16v(bars + B_DYN + (k + 1 - NSTATIC) * 2);
                asm volatile("cp.async.bulk.wait_group 0;\n" ::: "memory");
                asm volatile("fence.proxy.async.global;\n" ::: "memory");
                mbar_wait(bars + B_PUBD + (k & 1) * 8, ((k >> 1) + 1) & 1);
                mbar_arrive(bars + B_STORED + (k & 1) * 8);
            }
            mbar_arrive(sbase + SM_PBAR + 96);
        }
        if (PSTORE && warp == 1) {
            PROJ_SCHEDULE
            int st = 0, prev = -1, done = 0;
            uint32_t ph = 0;
            if (bid == gridDim.x - 1) { g_guard[2] = 0; __threadfence(); }
#pragma unroll 1
            for (int t = tile0; t < tend; t += tstep) {
                const int p0 = (t < TILES_A) ? SEG_B + 64 * (t & PWRAP) : 64 * (t - TILES_A);
                mbar_wait(sbase + SM_PBAR + 104 + st * 8, ph);
                if (!(WFEN & 1)) fence_async_smem();
                if (!at) TR(22, (t - tile0) / tstep);
                if (!at && done == 40 * PSM) ST(9);
                if (!at && done == 90 * PSM) ST(10);
                if (!at && done == 130 * PSM) ST(11);
                if (!at && done == 140 * PSM) ST(12);
#pragma unroll
                for (int ch = 0; ch < PSM; ch++) {
                    asm volatile("cp.async.bulk.tensor.2d.global.shared::cta.tile.bulk_group.L2::cache_hint [%0, {%2, %3}], [%1], %4;\n"
                                 :: "l"(reinterpret_cast<uint64_t>(t < TILES_A ? &omap : &omapb)),
                                    "r"(sbase + SM_STAGE + st * STAGE_BYTES + ch * 8192), "r"(ch * 64), "r"(p0), "l"(EVICT_FIRST) : "memory");
                    asm volatile("cp.async.bulk.commit_group;\n" ::: "memory");
                    asm volatile("cp.async.bulk.wait_group.read %0;\n" :: "n"(PCHUNK) : "memory");
                    asm volatile("st.volatile.shared.b32 [%0], %1;\n" :: "r"(sbase + SM_PBAR + 48), "r"(max(done + ch + 1 - PCHUNK, 0)) : "memory");
                }
                done += PSM;
                if (!mbar_test(sbase + SM_PBAR + 104 + (st == 5 ? 0 : st + 1) * 8, st == 5 ? ph ^ 1 : ph)) {
                    if (PCHUNK > 1) {
                        asm volatile("cp.async.bulk.wait_group.read 1;\n" ::: "memory");
                        asm volatile("st.volatile.shared.b32 [%0], %1;\n" :: "r"(sbase + SM_PBAR + 48), "r"(done - 1) : "memory");
                    }
                    asm volatile("cp.async.bulk.wait_group.read 0;\n" ::: "memory");
                    asm volatile("st.volatile.shared.b32 [%0], %1;\n" :: "r"(sbase + SM_PBAR + 48), "r"(done) : "memory");
                }
                prev = st;
                if (++st == 6) { st = 0; ph ^= 1; }
            }
            mbar_wait(sbase + SM_PBAR + 56, 0);
            asm volatile("fence.release.gpu;\n" ::: "memory");
            asm volatile("cp.async.bulk.wait_group 0;\n" ::: "memory");
            asm volatile("red.relaxed.gpu.global.add.u32 [%0], %1;\n" :: "l"(g_guard), "r"(bid == 0 ? 257 - gridDim.x : 1) : "memory");
            TR(30, 0);
            ST(13);
        }
        return;
    }
    bool bad = false;
    if (!attn) {
        asm volatile("setmaxnreg.inc.sync.aligned.u32 160;\n");
        uint32_t lo = 0x7F807F80u, hi = 0;
#pragma unroll 1
        for (int i = (role - 2 * P.npair) * 384 + tid; i < 192 * 96; i += (gridDim.x - 2 * P.npair) * 384) {
            const bool o = i >= 192 * 72;
            const uint4 w = o ? reinterpret_cast<const uint4*>(P.wo)[i - 192 * 72] : reinterpret_cast<const uint4*>(P.wqkv)[i];
            const uint32_t m = __vmaxu2(__vmaxu2(w.x & 0x7FFF7FFFu, w.y & 0x7FFF7FFFu), __vmaxu2(w.z & 0x7FFF7FFFu, w.w & 0x7FFF7FFFu));
            lo = __vminu2(lo, m);
            hi = __vmaxu2(hi, m + (o ? 0x02000200u : 0u));
        }
        bad = __vminu2(lo, 0x38803880u) != 0x38803880u || __vmaxu2(hi, 0x42004200u) != 0x42004200u;
    } else if (wg == 0) {
        float qs = 1.f;
        if (c < 2) qs = round_bf16(expf(round_bf16(fminf(fmaxf(c ? bf16hi(rc) : bf16lo(rc), -100.f), 4.6052f)))) * LOG2E;
        asm volatile("" : "+f"(qs) :: "memory");
        if (GLATE == 1) permute_w();
        TR(26, 28);
        asm volatile("setmaxnreg.inc.sync.aligned.u32 %0;\n" :: "n"(REG_G));
        TR(26, 29);
        uint32_t xa[8][4];
        uint32_t qk[2][48], vv[24];
        uint32_t rho = warp * 16 + (lane & 15), rq = warp * 16 + g;
        uint32_t rx = rho + 3 * TOK - (rho >= TOK ? 4 * TOK : 0);
        uint32_t hi = lane >> 4, lane0 = lane == 0, c2 = 2 * c;
        asm volatile("" : "+r"(hi), "+r"(lane0), "+r"(c2));
        auto row_addr = [&](uint32_t (&ax)[4], uint32_t r) {
            ax[0] = sbase + SM_QK + r * 128 + (((r & 7) ^ hi) << 4);
#pragma unroll
            for (int i = 1; i < 4; i++) ax[i] = ax[0] ^ (32 * i);
        };
#define XADDR(ax, s) ((ax)[((s) & 3) ^ (((s) >> 1) & 2)] + ((s) >> 2) * QK_CHUNK)
        uint64_t descW = make_desc(sbase, W_ATOM, 256, 3);
        const uint32_t zero = (uint32_t)P.z1;
        const uint32_t vbase = sbase + SM_V + (lane >> 4) * GRP;
        uint32_t ones = 0x3C003C00u | zero, ones2 = ones | (zero >> 1);
        asm volatile("" : "+r"(ones), "+r"(ones2));
        const uint32_t mh[2] = {0xFFFF0000u, 0xFFFF0000u}, ml[2] = {0x10000u, 0x10000u};
        uint32_t raw[48], xb[4][4];
        auto cvt = [&](auto& dst, int d0, const uint32_t (&raw)[48], int s0) {
#pragma unroll
            for (int s = 0; s < 4; s++) {
#pragma unroll
                for (int i = 0; i < 4; i++)
                    dst[d0 + s][i] = pack_f16(__uint_as_float(raw[4 * (s0 + s) + i] * ml[i & 1]), __uint_as_float(raw[4 * (s0 + s) + i] & mh[i & 1]));
                reg_fence(dst[d0 + s]);
            }
        };
        uint32_t ax[4];
        auto load_x = [&](int s0) {
#pragma unroll
            for (int s = s0; s < s0 + 4; s++) ldsm_x4(reinterpret_cast<uint32_t (&)[4]>(raw[4 * s]), XADDR(ax, s));
        };
        auto next_x = [&]() {
            row_addr(ax, rx);
            rx += 64;
            if (rx >= 4 * TOK) rx -= 4 * TOK;
        };
        if (!GLATE) permute_w();
        TR(26, 10);
        mbar_wait(bars + B_XFULL, 0);
        next_x();
        load_x(0); load_x(4); load_x(8);
        cvt(xa, 0, raw, 0); cvt(xa, 4, raw, 4); cvt(xb, 0, raw, 8);
        __syncwarp();
        mbar_arrive_if(bars + B_QKFREE + 24, lane0);
        TR(26, 8);
        asm volatile("bar.sync 7, 384;\n" ::: "memory");
        fence_async_smem();
        TR(26, 9);
        wgmma_fence();
        mma_qk_first<SM_WA, 0>(qk[0], xa, descW);
        mma_qk_next<SM_WA + 2048, 4>(qk[0], xa, descW);
        mma_qk_next<SM_WA + 4096, 0>(qk[0], xb, descW);
        wgmma_commit();
        TR(26, 11);
        asm volatile("bar.sync 11, 384;\n" ::: "memory");
        fence_async_smem();
        TR(26, 12);
        wgmma_fence();
        mma_v_first<SM_WV, 0>(vv, xa, descW);
        mma_v_next<SM_WV + 2048, 4>(vv, xa, descW);
        wgmma_commit();
        wgmma_wait<0>();
        ST(1); SC(28);
        uint32_t xok = 0, range = 0;
        int ntiles;
        auto body = [&](auto U_, int t) {
            constexpr int U = decltype(U_)::value;
            uint32_t (&cur)[48] = qk[U];
            uint32_t (&nxt)[48] = qk[U ^ 1];
            descW += P.z1;
            const uint32_t bt = bars + (t & 3) * 8, pt = (t >> 2) & 1;
            TR(1, t);
            wgmma_fence();
            mma_v_next<SM_WV + 4096, 0>(vv, xb, descW);
            wgmma_commit();
            next_x();
            mbar_wait_unless(xok, bars + ((t + 1) & 3) * 8 + B_XFULL, ((t + 1) >> 2) & 1);
            TR(2, t);
            load_x(0);
            load_x(4);
            uint32_t av = vbase + rho * 16 + ((rho * 1338) >> 16) * (V_STRIDE - GRP);
            uint32_t aq[2];
            aq[0] = sbase + SM_QK + rq * 128 + (((rq & 7) ^ c2) << 4);
            aq[1] = aq[0] + 1024;
            if (rq >= 4 * TOK - 8) aq[1] = (aq[1] - QK_CHUNK) ^ 64;
            rho += 64;
            if (rho >= 4 * TOK) rho -= 4 * TOK;
            rq += 64;
            if (rq >= 4 * TOK) rq -= 4 * TOK;
            asm volatile("" : "+r"(av), "+r"(aq[0]), "+r"(aq[1]), "+r"(rho), "+r"(rq));
            cvt(xa, 0, raw, 0);
            wgmma_fence();
            mma_qk_first<SM_WA, 0>(nxt, xa, descW);
            wgmma_commit();
            load_x(8);
            __syncwarp();
            mbar_arrive_if(bars + B_XCONS, lane0);
            const uint32_t vok = mbar_test(bt + B_VFREE, pt);
            ntiles = lds32v(bars + B_NTILES);
            cvt(xa, 4, raw, 4);
            TR(5, t);
            wgmma_fence();
            mma_qk_next<SM_WA + 2048, 4>(nxt, xa, descW);
            wgmma_commit();
            wgmma_wait<2>();
            reg_fence(cur);
            reg_fence(vv);
            TR(6, t);
            mbar_wait_unless(vok, bt + B_VFREE, pt);
            if (U == 0 && t == 2) asm volatile("bar.sync 3, 384;\n" ::: "memory");
#pragma unroll
            for (int p = 0; p < 6; p++)
                stsm_x4(av + (p < 3 ? 2 * p : 2 * p + 1) * GRP, vv[4 * p], vv[4 * p + 1], vv[4 * p + 2], vv[4 * p + 3]);
            stsm_x2(av + 6 * GRP, ones, ones2);
            __syncwarp();
            mbar_arrive_if(bt + B_VRAW, lane0);
            const uint32_t cok = mbar_test(bars + B_XCONS, U);
            TR(4, t);
            cvt(xb, 0, raw, 8);
            uint32_t ss[4];
#pragma unroll
            for (int i = 0; i < 4; i++) ss[i] = hmul2_f16(cur[i], cur[i]);
#pragma unroll
            for (int i = 4; i < ((EXP & 16) ? 4 : 48); i++) ss[i & 3] = hfma2_f16(cur[i], cur[i], ss[i & 3]);
            ss[0] = hadd2_f16(ss[0], ss[2]);
            ss[1] = hadd2_f16(ss[1], ss[3]);
            const float s0 = f16lo(ss[0]) + f16hi(ss[0]) + 1e-12f, s1 = f16lo(ss[1]) + f16hi(ss[1]) + 1e-12f;
            range = __viaddmax_u32(__float_as_uint(s0), 0u - SS_MIN, __viaddmax_u32(__float_as_uint(s1), 0u - SS_MIN, range));
            const float f0 = rsqrt_ftz(s0) * qs, f1 = rsqrt_ftz(s1) * qs;
            uint32_t f2[2] = {pack_f16_sat(f0, f0), pack_f16_sat(f1, f1)};
            reg_fence(f2);
            sched_fence16(zero, xb, f2[0], f2[1]);
            wgmma_fence();
            mma_v_first<SM_WV, 0>(vv, xa, descW);
            wgmma_commit();
            mbar_wait_unless_dep(cok, bars + B_XCONS, U, zero, f2[0], f2[1], aq[0], aq[1]);
            TR(7, t);
#pragma unroll
            for (int u = 0; u < 6; u++)
#pragma unroll
                for (int r = 0; r < 2; r++)
                    sts128((aq[r] ^ ((u & 1) * 16 + (u & 2) * 32)) + (u >> 1) * QK_CHUNK,
                           hmul2_f16(cur[8 * u + r], f2[r]), hmul2_f16(cur[8 * u + 2 + r], f2[r]),
                           hmul2_f16(cur[8 * u + 4 + r], f2[r]), hmul2_f16(cur[8 * u + 6 + r], f2[r]));
            __syncwarp();
            mbar_arrive_if(bt + B_QKRAW, lane0);
            TR(3, t);
            wgmma_fence();
            mma_v_next<SM_WV + 2048, 4>(vv, xa, descW);
            wgmma_commit();
            xok = mbar_test(bars + ((t + 2) & 3) * 8 + B_XFULL, ((t + 2) >> 2) & 1);
            mma_qk_next<SM_WA + 4096, 0>(nxt, xb, descW);
            wgmma_commit();
            TR(0, t + 1);
            wgmma_wait<GORD == 4 ? 2 : 1>();
        };
        for (int t = 0;; t += 2) {
            body(std::integral_constant<int, 0>(), t);
            if (__any_sync(0xffffffffu, t + 1 >= ntiles)) { wgmma_wait<0>(); reg_fence(qk[1]); break; }
            body(std::integral_constant<int, 1>(), t + 1);
            if (__any_sync(0xffffffffu, t + 2 >= ntiles)) { wgmma_wait<0>(); reg_fence(qk[0]); break; }
        }
        reg_fence(vv);
        bad = range >= F32_INF - SS_MIN;
        __syncwarp();
        mbar_arrive_if(bars + B_GDONE, lane0);
        asm volatile("setmaxnreg.dec.sync.aligned.u32 160;\n");
    } else {
        if (REG_A > 128) asm volatile("setmaxnreg.inc.sync.aligned.u32 %0;\n" :: "n"(REG_A));
        if (REG_A < 128) asm volatile("setmaxnreg.dec.sync.aligned.u32 %0;\n" :: "n"(REG_A));
        {
            const float c0 = bf16lo(rc), c1 = bf16hi(rc);
            float a0 = 0.f, a1 = 0.f;
#pragma unroll
            for (int u = 0; u < 16; u++) {
                const uint32_t p = reinterpret_cast<const uint32_t*>(w1)[u >> 1], q = reinterpret_cast<const uint32_t*>(w1)[8 + (u >> 1)];
                float h = round_bf16(c0 * ((u & 1) ? bf16hi(p) : bf16lo(p)) + c1 * ((u & 1) ? bf16hi(q) : bf16lo(q)));
                h = fmaxf(h, 0.f);
                a0 += h * bf16lo(w2[u]);
                a1 += h * bf16hi(w2[u]);
            }
            const float s0 = round_bf16(__fdividef(1.f, 1.f + expf(-round_bf16(a0))));
            const float s1 = round_bf16(__fdividef(1.f, 1.f + expf(-round_bf16(a1))));
            if (tid - 128 < 169) sts32(sbase + SM_TAB + (tid - 128) * 4, pack_f16(16.f * LOG2E * s0, 16.f * LOG2E * s1));
        }
        if (GLATE == 2) permute_a(); else permute_w();
        asm volatile("bar.arrive 7, 384;\n" ::: "memory");
        TR(26, 72 + wg);
        {
            uint4 w[9];
            const int rg = ((tid >> 5) - 4) * 3;
            mbar_wait(bars + B_WFULL, 0);
#pragma unroll
            for (int i = 0; i < 9; i++) w[i] = *reinterpret_cast<const uint4*>(smem + SM_WV + raw_w(rg + i / 3, (i % 3) * 4 + (lane >> 3)));
            asm volatile("bar.sync 1, 256;\n" ::: "memory");
            const uint32_t d = sbase + SM_WV + (lane >> 4) * W_ATOM + (rg * 8 + (lane & 7)) * 32 + (((lane >> 2) ^ (lane >> 3)) & 1) * 16;
#pragma unroll
            for (int i = 0; i < 9; i++)
                sts128(d + (i % 3) * 2 * W_ATOM + (i / 3) * 256, bf2h(w[i].x), bf2h(w[i].y), bf2h(w[i].z), bf2h(w[i].w));
            asm volatile("bar.arrive 11, 384;\n" ::: "memory");
            TR(26, 76 + wg);
        }
        uint32_t bias[28];
        {
            const uint32_t* tab = reinterpret_cast<const uint32_t*>(smem + SM_TAB);
#pragma unroll
            for (int rh = 0; rh < 2; rh++) {
#pragma unroll
                for (int j = 0; j < 6; j++) {
                    const uint32_t lo = tab[min(max(ridx[13 * rh + 2 * j], 0), 168)];
                    const uint32_t hi = tab[min(max(ridx[13 * rh + 2 * j + 1], 0), 168)];
                    bias[2 * j + rh]      = prmt(lo, hi, 0x5410);
                    bias[14 + 2 * j + rh] = prmt(lo, hi, 0x7632);
                }
                const uint32_t l = (c == 0) ? tab[min(max(ridx[13 * rh + 12], 0), 168)] : 0xFC00FC00u;
                bias[12 + rh] = (l & 0xFFFFu) | 0xFC000000u;
                bias[26 + rh] = (l >> 16) | 0xFC000000u;
            }
        }
#pragma unroll
        for (int i = 0; i < 28; i++)
            if (warp * 16 + g + (i & 1) * 8 >= TOK && i % 14 < 12) bias[i] = 0xFC00FC00u;
        reg_fence(bias);
        asm volatile("bar.arrive 3, 384;\n" ::: "memory");
        uint32_t os[3];
#pragma unroll
        for (int p = 0; p < 3; p++) {
            const int orow = warp * 16 + (lane & 7);
            uint32_t a = orow * 192 + p * 64;
            a += (((lane >> 3) ^ (a >> 7)) & 3) << 4;
            os[p] = sbase + SM_V + (wg - 1) * O_STRIDE + (orow < TOK ? a : 74 * 128 + (a & 127));
        }
        reg_fence(os);
        const int orow = warp * 16 + (lane & 7);
        const bool ov = orow < TOK;
        const uint32_t orel = sbase + (ov ? SM_V + orow * O_PITCH + (OONE == 2 && orow >= 28 ? 64 : 0) : SM_DUMP + ((lane + (OONE == 2 ? 7 : 3)) & 7) * 16) + (lane >> 3) * 16;
        const uint32_t oup = (OONE == 2 && warp == 1) ? (lane & 4) * 16 : 0;
        const uint32_t omul = ov ? O_STRIDE : 0;
        const uint64_t descK0 = make_desc(sbase + SM_QK, 16, 1024, 1);
        const uint64_t descV0 = make_desc(sbase + SM_V, 128, GRP, 0);
        const uint32_t mrel = sbase + SM_MASK + t0 * 98 + c * 4;
        const uint32_t mrow = (warp < 3) ? 784 : 0;
        const uint32_t pmask = (c == 0) ? 0xFFFFu : 0u;

        uint32_t mstate = 0;
        int nwin;
        const uint32_t barw = bars + (wg - 1) * 8;
        const uint64_t descKw = descK0 + (uint64_t)((wg - 1) * (XCH >> 4)), descVw = descV0 + (uint64_t)((wg - 1) * (V_STRIDE >> 4));
        uint32_t oa = orel + (wg - 1) * omul;
        const uint32_t oflip = oa ^ (oa + 2 * omul);
        uint32_t qok = 0;
        const uint32_t zero = (uint32_t)P.z1;
        auto window = [&](auto IT_, int k) {
            constexpr int IT = decltype(IT_)::value;
            const uint32_t bar = barw + 16 * IT;
            const int tl = (k * TOK + TOK - 1) >> 6, tn = ((k + 2) * TOK + TOK - 1) >> 6;
            const uint32_t bt = bars + (tl & 3) * 8, pt = (tl >> 2) & 1;
            TR(8, k);
            uint32_t sc0[14], sc1[14];
#pragma unroll
            for (int i = 0; i < 14; i++) { sc0[i] = bias[i]; sc1[i] = bias[14 + i]; }
            if (mstate < 32 * k + 32) {
#pragma unroll 1
                for (uint32_t n = 0; n < (1u << 22) && mstate < 32 * k + 16; n++) mstate = lds32v(bars + B_MSTATE);
                if (mstate < 32 * k + 32) {
                    mbar_wait(bars + B_MFULL, mstate & 1);
                    const uint32_t ma = mrel + (mstate & 14);
#pragma unroll
                    for (int i = 0; i < 14; i++) {
                        const uint32_t lo = lds16(ma + (i & 1) * mrow + (i >> 1) * 16);
                        const uint32_t hi = i < 12 ? lds16(ma + (i & 1) * mrow + (i >> 1) * 16 + 2) : 0u;
                        const uint32_t mk = pack_f16(__uint_as_float(lo << 16), __uint_as_float(hi << 16));
                        sc0[i] = hfma2_f16(mk, 0x3DC53DC5u, sc0[i]);
                        sc1[i] = hfma2_f16(mk, 0x3DC53DC5u, sc1[i]);
                    }
                    __syncwarp();
                    if (lane == 0) mbar_arrive(bars + B_MCONS);
                }
            }
            reg_fence(sc0);
            reg_fence(sc1);
            TR(10, k);
            mbar_wait_unless(qok, bt + B_QKRAW, pt);
            fence_async_smem();
            TR(11, k);
            wgmma_fence();
#if !(EXP & 128)
            mma_s0_f16<2 * IT * XCH, 2 * IT * XCH>(sc0, descKw, descKw);
            mma_s1_f16<2 * IT * XCH, 2 * IT * XCH>(sc1, descKw, descKw);
#endif
            wgmma_commit();
            const uint32_t vok = mbar_test(bt + B_VRAW, pt);
            uint32_t m[2];
            auto rowmax = [&](const uint32_t (&S)[14], int h) {
                uint32_t a[2];
#pragma unroll
                for (int o = 0; o < 2; o++)
                    a[o] = hmax2_f16(hmax2_f16(hmax2_f16(hmax2_f16(S[o], S[2 + o]), S[4 + o]), hmax2_f16(hmax2_f16(S[6 + o], S[8 + o]), S[10 + o])), S[12 + o]);
                m[h] = hmax2_f16(prmt(a[0], a[1], 0x5410), prmt(a[0], a[1], 0x7632));
            };
            wgmma_wait<0>();
            reg_fence(sc0);
            reg_fence(sc1);
            if (lane == 0) mbar_arrive(bar + B_QKFREE);
            TR(12, k);
            rowmax(sc0, 0);
            rowmax(sc1, 1);
#pragma unroll
            for (int i = 0; i < 2; i++) m[i] = hmax2_f16(m[i], __shfl_xor_sync(0xffffffffu, m[i], 1));
#pragma unroll
            for (int i = 0; i < 2; i++) m[i] = hmax2_f16(m[i], __shfl_xor_sync(0xffffffffu, m[i], 2));
            auto probs = [&](const uint32_t (&S)[14], uint32_t mm, uint32_t (&pa)[4][4]) {
#pragma unroll
                for (int j = 0; j < 6; j++) {
                    pa[j >> 1][(j & 1) * 2]     = ex2_f16x2(hsub2_bc<0>(S[2 * j], mm));
                    pa[j >> 1][(j & 1) * 2 + 1] = ex2_f16x2(hsub2_bc<1>(S[2 * j + 1], mm));
                }
                pa[3][0] = ex2_f16lo(hsub2_bc<0>(S[12], mm)) & pmask;
                pa[3][1] = ex2_f16lo(hsub2_bc<1>(S[13], mm)) & pmask;
                pa[3][2] = 0u; pa[3][3] = 0u;
                reg_fence(pa);
            };
            uint32_t pa0[4][4], pa1[4][4];
            uint32_t o0[14], o1[14];
            TR(13, k);
            mbar_wait_unless(vok, bt + B_VRAW, pt);
            fence_async_smem();
            TR(14, k);
            probs(sc0, m[0], pa0);
            wgmma_fence();
            mma_pv<2 * IT * V_STRIDE, 0>(o0, pa0, descVw);
            wgmma_commit();
            probs(sc1, m[1], pa1);
            wgmma_fence();
            mma_pv<2 * IT * V_STRIDE + 6 * GRP, 0>(o1, pa1, descVw);
            wgmma_commit();
            uint32_t w[24];
            wgmma_wait<1>();
            reg_fence(o0);
            {
                const float il0 = rcp_ftz(f16lo(o0[12])), il1 = rcp_ftz(f16lo(o0[13]));
                const uint32_t l0 = pack_f16(il0, il0), l1 = pack_f16(il1, il1);
#pragma unroll
                for (int j = 0; j < 12; j++) w[j] = hmul2_f16(o0[j], (j & 1) ? l1 : l0);
            }
            wgmma_wait<0>();
            reg_fence(o1);
            TR(15, k);
            asm volatile("{\n.reg .pred p;\nsetp.eq.u32 p, %0, 1;\n@p bar.sync 4, 128;\n@!p bar.sync 5, 128;\n}\n"
                         :: "r"(wg) : "memory");
            qok = mbar_test(bars + (tn & 3) * 8 + B_QKRAW, (tn >> 2) & 1);
            asm volatile("ld.volatile.shared.v2.b32 {%0, %1}, [%2];\n" : "=r"(mstate), "=r"(nwin) : "r"(bars + B_MSTATE) : "memory");
            {
                const float il2 = rcp_ftz(f16lo(o1[0])), il3 = rcp_ftz(f16lo(o1[1]));
                const uint32_t l2 = pack_f16(il2, il2), l3 = pack_f16(il3, il3);
#pragma unroll
                for (int j = 0; j < 12; j++) w[12 + j] = hmul2_f16(o1[j + 2], (j & 1) ? l3 : l2);
#pragma unroll
                for (int p = 0; p < 3; p++) stsm_x4(os[p] + 2 * IT * O_STRIDE, w[8 * p], w[8 * p + 2], w[8 * p + 4], w[8 * p + 6]);
#pragma unroll
                for (int p = 0; p < 3; p++) stsm_x4_if(warp < 3, os[p] + 2 * IT * O_STRIDE + 8 * 192, w[8 * p + 1], w[8 * p + 3], w[8 * p + 5], w[8 * p + 7]);
            }
            if (WFEN & 2) fence_async_smem();
            __syncwarp();
            if (lane == 0) mbar_arrive(bar + B_ODONE);
            TR(16, k);
        };
        for (int k = wg - 1;; k += 4) {
            window(std::integral_constant<int, 0>(), k);
            if (__any_sync(0xffffffffu, k + 2 >= nwin)) break;
            window(std::integral_constant<int, 1>(), k + 2);
            if (__any_sync(0xffffffffu, k + 4 >= nwin)) break;
        }
        (void)zero;
        asm volatile("setmaxnreg.inc.sync.aligned.u32 160;\n");
    }

    TR(27, wg);
    ST(2 + wg);
    uint32_t tag, seen;
    asm volatile("ld.relaxed.gpu.global.v2.u32 {%0, %1}, [%2];\n" : "=r"(tag), "=r"(seen) : "l"(g_guard) : "memory");
    if (attn || !MPRE) {
        __syncwarp();
        if (lane == 0) mbar_arrive(sbase + SM_PBAR + 96);
    }
    if (!attn) {
        uint4 wor[2][6];
#pragma unroll
        for (int i = 0; i < 12; i++)
            ldg_nc_v4(reinterpret_cast<uint32_t (&)[4]>(wor[i / 6][i % 6]), P.wo + ((tid >> 2) + i / 6 * 96) * 192 + 32 * (i % 6) + 8 * c);
        {
            const uint32_t wstep = (gridDim.x - 2 * P.npair) * 12, wend = MEND * P.npair;
            const uint32_t mbuf = sbase + (tid >> 5) * MBUFS * M_BUF, mbar = sbase + SM_MBAR + (tid >> 5) * MBUFS * 8;
            uint32_t w = MPRE * P.npair + (role - 2 * P.npair) * 12 + (tid >> 5);
            auto load = [&](uint32_t w, uint32_t i) {
                if (w < wend) {
                    const uint32_t o = (w * 4802u) & ~(MALIGN - 1), n = MALIGN == 16 ? 4816 : ((w * 4802u & ~15u) + 4816 - o + MALIGN - 1) & ~(MALIGN - 1);
                    mbar_arrive_expect_tx(mbar + i * 8, n);
                    asm volatile("cp.async.bulk.shared::cluster.global.mbarrier::complete_tx::bytes [%0], [%1], %3, [%2];\n"
                                 :: "r"(mbuf + i * M_BUF), "l"(reinterpret_cast<const char*>(P.mask) + o),
                                    "r"(mbar + i * 8), "r"(n) : "memory");
                }
            };
            if (elect_one()) {
                if (MDELAY) __nanosleep(MDELAY);
#pragma unroll 1
                for (int i = 0; i < MBUFS; i++) load(w + i * wstep, i);
            }
            __syncwarp();
            uint32_t i = 0, ph = 0;
#pragma unroll 1
            for (; w < wend; w += wstep) {
                const uint32_t b = mbuf + i * M_BUF + ((w * 4802u) & (MALIGN - 16));
                mbar_wait(mbar + i * 8, ph);
                uint32_t acc = lds16(b + (lane & 7) * 2 + (lane & 8) * 600);
                if ((lane & 15) - (w & 7) > 8u) acc = 0;
                uint32_t v[10][4];
#pragma unroll
                for (int j = 0; j < 10; j++) lds128(v[j], b + 16 * (j < 9 ? 1 + lane + 32 * j : min(289 + lane, 299)));
#pragma unroll
                for (int j = 0; j < 10; j++) acc |= v[j][0] | v[j][1] | v[j][2] | v[j][3];
                const uint32_t nz = __any_sync(0xffffffffu, (acc & 0x7FFF7FFFu) != 0) ? 1 : 0;
                if (elect_one()) {
                    load(w + MBUFS * wstep, i);
                    const uint32_t k = w / (uint32_t)P.npair;
                    asm volatile("st.relaxed.gpu.global.u32 [%0], %1;\n" :: "l"(g_mz + (w - k * P.npair) * 128 + k), "r"((tag | 255) - nz) : "memory");
                }
                __syncwarp();
                if (++i == MBUFS) { i = 0; ph ^= 1; }
            }
            if (lane == 0) mbar_arrive(sbase + SM_PBAR + 96);
            asm volatile("bar.sync 6, 384;\n" ::: "memory");
        }
#pragma unroll
        for (int rh = 0; rh < 2; rh++) {
            const int row = (tid >> 2) + 96 * rh;
            const uint4 (&w)[6] = wor[rh];
            float s = 0.f;
#pragma unroll
            for (int a = 0; a < 6; a++)
                s += ((bf16lo(w[a].x) + bf16hi(w[a].x)) + (bf16lo(w[a].y) + bf16hi(w[a].y))) +
                     ((bf16lo(w[a].z) + bf16hi(w[a].z)) + (bf16lo(w[a].w) + bf16hi(w[a].w)));
            s += __shfl_xor_sync(0xffffffffu, s, 1);
            s += __shfl_xor_sync(0xffffffffu, s, 2);
            s *= (1.f / 192.f);
            const uint32_t sw = (row >> 1) & 3;
            const uint32_t d = sbase + SM_WO + row * 64 + ((c ^ sw) << 4), e = sbase + SM_WO + row * 64 + c * 4;
#pragma unroll
            for (int a = 0; a < 6; a++) {
                const uint32_t h[4] = {pack_f16(bf16lo(w[a].x) - s, bf16hi(w[a].x) - s), pack_f16(bf16lo(w[a].y) - s, bf16hi(w[a].y) - s),
                                       pack_f16(bf16lo(w[a].z) - s, bf16hi(w[a].z) - s), pack_f16(bf16lo(w[a].w) - s, bf16hi(w[a].w) - s)};
                if (a < 2 * PSM) {
                    sts128(d + a * 12288, h[0], h[1], h[2], h[3]);
                } else {
#pragma unroll
                    for (int i = 0; i < 4; i++) sts32(e + a * 12288 + ((i ^ sw) << 4), h[i]);
                }
            }
        }
        fence_async_smem();
        asm volatile("bar.sync 6, 384;\n" ::: "memory");
        if (role == 2 * P.npair && tid == 0) {
            asm volatile("cp.async.bulk.global.shared::cta.bulk_group [%0], [%1], %2;\n"
                         :: "l"(g_wo), "r"(sbase + SM_WO), "n"(SM_STAGE) : "memory");
            asm volatile("cp.async.bulk.commit_group;\n" ::: "memory");
            asm volatile("cp.async.bulk.wait_group 0;\n" ::: "memory");
            asm volatile("fence.proxy.async.global;\n" ::: "memory");
            asm volatile("st.release.gpu.global.u32 [%0], %1;\n" :: "l"(g_guard + 3), "r"(tag | 255) : "memory");
        }
        __syncwarp();
    } else {
        mbar_wait(bars + B_WRAW, 1);
    }
    tag |= 255;
    if (bad) g_guard[1] = tag;
    bad |= seen == tag;
    TR(27, 4 + wg);
    if (wg == 0) ST(5);
    {
        PROJ_SCHEDULE
        uint64_t descW = make_desc(sbase + SM_WO, 12288, 512, 2);
        const uint64_t descA = make_desc(sbase + SM_STAGE + wg * STAGE_BYTES, 16, 1024, 1);
        const uint32_t bar = sbase + SM_PBAR + wg * 8;
        const uint32_t yrel = sbase + SM_STAGE + wg * STAGE_BYTES + (warp * 16 + (lane & 15)) * 128 + (((lane & 7) ^ (lane >> 4)) << 4);
        float acc[96];
#pragma unroll
        for (int i = 0; i < 96; i++) acc[i] = 0.f;
        uint32_t it = 0;
        for (int tile = tile0 + wg * tstep; tile < tend; tile += 3 * tstep, it++) {
            descW += P.z1;
            mbar_wait(bar + (it & 1) * 24, (it >> 1) & 1);
            TR(28, it * 3 + wg);
            ST(6 + wg);
            if (it > 0 || wg > 0) asm volatile("bar.sync %0, 256;\n" :: "r"(8 + wg) : "memory");
            wgmma_fence();
            mma_proj<0, 0>(acc, descA + (uint64_t)((it & 1) * (3 * STAGE_BYTES >> 4)), descW);
            wgmma_commit();
            if (tile + tstep < tend) asm volatile("bar.arrive %0, 256;\n" :: "r"(wg == 2 ? 8 : 9 + wg) : "memory");
            wgmma_wait<0>();
            reg_fence(acc);
            TR(18, it * 3 + wg);
            float a[4];
#pragma unroll
            for (int i = 0; i < 4; i++) a[i] = acc[i] * acc[i];
#pragma unroll
            for (int j = 1; j < 24; j++)
#pragma unroll
                for (int i = 0; i < 4; i++) a[i] = fmaf(acc[4 * j + i], acc[4 * j + i], a[i]);
            float s0 = a[0] + a[1], s1 = a[2] + a[3];
            s0 += __shfl_xor_sync(0xffffffffu, s0, 1);
            s1 += __shfl_xor_sync(0xffffffffu, s1, 1);
            s0 += __shfl_xor_sync(0xffffffffu, s0, 2);
            s1 += __shfl_xor_sync(0xffffffffu, s1, 2);
            if (max(__float_as_uint(s0) - VAR_MIN, __float_as_uint(s1) - VAR_MIN) >= F32_INF - VAR_MIN) {
                const int rem = ((tile < TILES_A) ? NPIX - SEG_B - 64 * tile : SEG_B - 64 * (tile - TILES_A)) - warp * 16 - g;
                if ((__float_as_uint(s0) - VAR_MIN >= F32_INF - VAR_MIN && rem > 0) ||
                    (__float_as_uint(s1) - VAR_MIN >= F32_INF - VAR_MIN && rem > 8)) {
                    bad = true;
                    g_guard[1] = tag;
                }
            }
            const float rs0 = rsqrt_ftz(fmaf(s0, 1.f / 192.f, 1e-5f));
            const float rs1 = rsqrt_ftz(fmaf(s1, 1.f / 192.f, 1e-5f));
            const uint32_t ya = yrel + (it & 1) * 3 * STAGE_BYTES;
            auto direct = [&]() {
                const int p0 = (tile < TILES_A) ? SEG_B + 64 * (tile & PWRAP) : 64 * (tile - TILES_A);
                const int lim = ((tile < TILES_A) ? NPIX : SEG_B) - p0;
                char* const po = reinterpret_cast<char*>(P.out) + (uint32_t)((p0 + warp * 16 + g) * 384 + c * 16);
                const bool v0 = warp * 16 + g < lim, v1 = warp * 16 + g + 8 < lim;
#pragma unroll
                for (int i = 2 * PSM; i < 6; i++) {
                    const int j = 16 * i;
                    stg128_if(v0, po + 64 * i, pack_bf16(acc[j] * rs0, acc[j + 1] * rs0), pack_bf16(acc[j + 4] * rs0, acc[j + 5] * rs0),
                              pack_bf16(acc[j + 8] * rs0, acc[j + 9] * rs0), pack_bf16(acc[j + 12] * rs0, acc[j + 13] * rs0));
                    stg128_if(v1, po + 8 * 384 + 64 * i, pack_bf16(acc[j + 2] * rs1, acc[j + 3] * rs1),
                              pack_bf16(acc[j + 6] * rs1, acc[j + 7] * rs1), pack_bf16(acc[j + 10] * rs1, acc[j + 11] * rs1),
                              pack_bf16(acc[j + 14] * rs1, acc[j + 15] * rs1));
                }
            };
            if (PSM < 3 && PDF) direct();
#pragma unroll
            for (int p = 0; p < 4 * PSM; p++)
                stsm_x4((ya ^ (32 * (p & 3))) + (p >> 2) * 8192,
                        pack_bf16(acc[8 * p] * rs0, acc[8 * p + 1] * rs0), pack_bf16(acc[8 * p + 2] * rs1, acc[8 * p + 3] * rs1),
                        pack_bf16(acc[8 * p + 4] * rs0, acc[8 * p + 5] * rs0), pack_bf16(acc[8 * p + 6] * rs1, acc[8 * p + 7] * rs1));
            if (WFEN & 1) fence_async_smem();
            __syncwarp();
            if (lane == 0) mbar_arrive(bar + 104 + (it & 1) * 24);
            if (PSM < 3 && !PDF) direct();
            TR(29, it * 3 + wg);
            ST(16 + wg);
        }
        __syncwarp();
        if (lane == 0) mbar_arrive(sbase + SM_PBAR + 56);
    }

    {
        uint32_t any;
        asm volatile("{\n.reg .pred p, q;\nsetp.ne.u32 q, %1, 0;\nbarrier.cta.red.or.pred.aligned p, %2, 128, q;\nselp.u32 %0, 1, 0, p;\n}\n"
                     : "=r"(any) : "r"((uint32_t)bad), "r"(12 + wg) : "memory");
        if (!any) return;
    }
    redo(P, smem + wg * FB_BYTES, tag, 12 + wg);
}

}

typedef CUresult (*PFN_encodeTiled)(CUtensorMap*, CUtensorMapDataType, cuuint32_t, void*, const cuuint64_t*,
                                    const cuuint64_t*, const cuuint32_t*, const cuuint32_t*, CUtensorMapInterleave,
                                    CUtensorMapSwizzle, CUtensorMapL2promotion, CUtensorMapFloatOOBfill);

extern "C" void kernel_launch(void* const* d_in, const int* in_sizes, int n_in, void* d_out, int out_size) {
    swin::Params P;
    P.x           = (const __nv_bfloat16*)d_in[0];
    P.wqkv        = (const __nv_bfloat16*)d_in[1];
    P.wo          = (const __nv_bfloat16*)d_in[2];
    P.logit_scale = (const __nv_bfloat16*)d_in[3];
    P.cpb_w1      = (const __nv_bfloat16*)d_in[4];
    P.cpb_w2      = (const __nv_bfloat16*)d_in[5];
    P.rel_coords  = (const __nv_bfloat16*)d_in[6];
    P.rel_idx     = (const int*)d_in[7];
    P.mask        = (const __nv_bfloat16*)d_in[8];
    P.out         = (__nv_bfloat16*)d_out;
    P.z1 = 0;
    static PFN_encodeTiled encode = nullptr;
    if (!encode) {
        cudaFuncSetAttribute(swin::swin_window_attn_kernel, cudaFuncAttributeMaxDynamicSharedMemorySize, swin::SM_TOTAL);
        cudaDriverEntryPointQueryResult qr;
        cudaGetDriverEntryPoint("cuTensorMapEncodeTiled", (void**)&encode, cudaEnableDefault, &qr);
    }
    CUtensorMap xmap, xmap4, xmap3, omap, wmap, smap, omapb, xmapa, xmapb, smap3, wraw, smapw;
    const cuuint32_t estr[4] = {1, 1, 1, 1};
    auto make = [&](CUtensorMap* m, const void* base, int rank, const cuuint64_t* gdim, const cuuint64_t* gstr,
                    const cuuint32_t* box, CUtensorMapSwizzle swz = CU_TENSOR_MAP_SWIZZLE_128B) {
        CUresult r = encode(m, CU_TENSOR_MAP_DATA_TYPE_BFLOAT16, rank, const_cast<void*>(base), gdim, gstr, box, estr,
               CU_TENSOR_MAP_INTERLEAVE_NONE, swz, CU_TENSOR_MAP_L2_PROMOTION_L2_128B,
               CU_TENSOR_MAP_FLOAT_OOB_FILL_NONE);
        (void)r;
    };
    {
        const cuuint64_t gdim[3] = {192, swin::IMG, swin::IMG}, gstr[2] = {384, swin::IMG * 384};
        const cuuint32_t box[3] = {64, 7, 7}, box4[3] = {64, 4, 1}, box3[3] = {64, 3, 1};
        make(&xmap, P.x, 3, gdim, gstr, box);
        make(&xmap4, P.x, 3, gdim, gstr, box4);
        make(&xmap3, P.x, 3, gdim, gstr, box3);
        const cuuint32_t boxa[3] = {64, 7, 3}, boxb[3] = {64, 7, 4};
        make(&xmapa, P.x, 3, gdim, gstr, boxa);
        make(&xmapb, P.x, 3, gdim, gstr, boxb);
    }
    {
        const cuuint64_t gdim[2] = {192, (cuuint64_t)swin::NPIX}, gstr[1] = {384};
        const cuuint32_t box64[2] = {64, 64};
        make(&omap, d_out, 2, gdim, gstr, box64);
        const cuuint64_t gdimb[2] = {192, (cuuint64_t)swin::SEG_B};
        make(&omapb, d_out, 2, gdimb, gstr, box64);
    }
    {
        const cuuint64_t gdim[2] = {576, 192}, gstr[1] = {1152};
        const cuuint32_t box[2] = {32, 192}, box2[2] = {64, 192};
        make(&wmap, P.wqkv, 2, gdim, gstr, box, CU_TENSOR_MAP_SWIZZLE_64B);
        make(&wraw, P.wqkv, 2, gdim, gstr, box2);
    }
    {
        const cuuint64_t gdim[4] = {32, 6, swin::IMG, swin::IMG}, gstr[3] = {64, 384, swin::IMG * 384};
        const cuuint32_t box7[4] = {32, 3, 7, 7}, box3[4] = {32, 3, 7, 3}, boxw[4] = {32, 3, 4, 1};
        make(&smap, d_out, 4, gdim, gstr, box7, CU_TENSOR_MAP_SWIZZLE_64B);
        make(&smap3, d_out, 4, gdim, gstr, box3, CU_TENSOR_MAP_SWIZZLE_64B);
        const cuuint64_t gdimw[4] = {32, 6, 4, swin::IMG};
        make(&smapw, (char*)d_out - 384, 4, gdimw, gstr, boxw, CU_TENSOR_MAP_SWIZZLE_64B);
    }
    P.npair = NPAIR; P.need = swin::ROW_DONE;
    P.t1 = swin::TILES - NTAIL;
    P.spread = ((132 - 2 * NPAIR) * 65536 + 131) / 132;
    swin::swin_window_attn_kernel<<<132, swin::NTHREADS, swin::SM_TOTAL>>>(P, xmap, xmap4, xmap3, omap, wmap, smap, omapb, xmapa, xmapb, smap3, wraw, smapw);
}
```

```cpp
#include <cuda_runtime.h>
#include <cuda.h>
#include <cuda_bf16.h>
#include <stdint.h>
#include <type_traits>

namespace swin {

#define NPAIR 53
#define QFP32 0
#define PF_DIST 3
#define EXP 0
#define QSPLIT 3
#define SSPLIT 0
#define LATEMASK 0
#define CLUSTER 0
#define NOPF 0
#define NTAIL 200
#define PSTORE 1
#define PORDER 1
#define GORD 0
#define GMERGE 0
#define XSPLIT 1
#define EARLYW 1
#define NEARLY 4
#define W1 1
#define W2 2
#define W3 2
#define T_ONEBUF 0
#define T_NOWV 0
#define MPF 3
#define MRND 5
#define PX_L 3
#define PX_S 3
#define PX_W 0
#define PCHUNK 1
#define SPREAD 2
#define PSM 2
#define PDF 0
#define PWRAP -1
#define POLLER 1
#define PUBN 2
#define PUBT 4
#define NSTATIC 92
#define RSLEEP 800
#define AROLL 0
#define WOSPLIT 4
#define PADZ 1
#define MPRE 14
#define MEND 92
#define HOUT 1
#define HX 0
#define HM 2
#define OONE 1
#define VSTR 10256
#define MALIGN 128
#define MBUFS 2
#define FREL 1
#define RPOLL 1
#define NOCC 0
#define WFEN 0
#define ENDX 0
#define EW 1
#define EWT 480
#define GLATE 2
#define MDELAY 0
#define OSW 1
#define XPF 2
#define NOLD 0
#define OPF 1
#define WPOLL 1
#define EDELAY 200
#define PH 1
#define MBG 0
#define BGB 2
#define BGS 0
#define MLIM (MBG ? MBG : MEND)
#define PFALT 0
#define PV3 0
#define OMASK 0
#define WMASK 0
#define HOIST 0
#define HINT 0
#define HINT_A ""
#define HINT_B ""
#define REG_G 232
#define REG_A 120
#define REG_H 32
constexpr int IMG      = 511;
constexpr int NWS      = 73;
constexpr int NWINDOWS = NWS * NWS;
constexpr int TOK      = 49;
constexpr int NPIX     = IMG * IMG;
constexpr int NTHREADS = 512;

constexpr int W_ATOM = 6144;
constexpr int SM_WA = 0, SM_WB = 6 * W_ATOM, SM_WV = 12 * W_ATOM;
constexpr int GRP   = TOK * 16;
constexpr int XCH   = TOK * 128;
constexpr int SM_V  = 18 * W_ATOM, V_STRIDE = VSTR, O_STRIDE = 10240, O_PITCH = 208;
constexpr int SM_QK = SM_V + 4 * O_STRIDE, QK_CHUNK = 4 * XCH;
constexpr int SM_MASK = SM_QK + 3 * QK_CHUNK;
constexpr int SM_TAB  = SM_V + 3 * V_STRIDE + 256;
constexpr int SM_DUMP = SM_MASK + 4816;
constexpr int SM_BAR  = SM_DUMP + 320;
constexpr int B_XFULL = 0, B_WRAW = 32, B_XCONS = 40, B_NTILES = 48, B_GDONE = 56, B_DYN = 192, B_ROWS = 384, B_QKRAW = 64, B_QKFREE = 96, B_VFREE = 128, B_ODONE = 160,
              B_VRAW = 224, B_MFULL = 256, B_MSTATE = 264, B_MCONS = 272, B_WFULL = 280, B_STORED = 288, B_PUBD = 304;
constexpr int SM_A_END = SM_BAR + 320;
static_assert(SM_QK % 1024 == 0 && TOK * O_PITCH + 64 - 16 <= O_STRIDE && (28 * O_PITCH + 64) % 128 == 0, "layout");
static_assert(3 * V_STRIDE + 13 * GRP <= 4 * O_STRIDE && V_STRIDE >= O_STRIDE && SM_DUMP % 128 == 80, "layout");
constexpr int SM_WO    = 0;
constexpr int SM_STAGE = 73728;
constexpr int STAGE_BYTES = 24576;
constexpr int SM_MBAR  = SM_STAGE + 6 * STAGE_BYTES, M_BUF = 4992;
constexpr int SM_PBAR  = SM_A_END;
constexpr int SM_TOTAL = SM_PBAR + 152;
static_assert(SM_STAGE + 6 * STAGE_BYTES <= SM_BAR && SM_MBAR + 256 + BGB * M_BUF <= SM_BAR && (!MBG || MBUFS <= 2), "smem");
static_assert(SM_TOTAL <= 232448, "smem");
static_assert(SM_BAR % 8 == 0, "barrier alignment");

constexpr int SEG_B   = 3 * IMG;
constexpr int TILES_A = (NPIX - SEG_B + 63) / 64;
constexpr int TILES   = TILES_A + (SEG_B + 63) / 64;
constexpr uint32_t ROW_DONE = NWS * 2;

__device__ uint32_t g_cnt[NWS + 7];
__device__ __align__(128) uint8_t g_wo[SM_STAGE];
__device__ uint32_t g_mz[64 * 128];
__device__ uint32_t g_next[2];
__device__ uint32_t g_done;
__device__ __align__(16) uint32_t g_guard[4];
constexpr uint32_t F32_INF = 0x7F800000u;
constexpr uint32_t SS_MIN  = 0x3B800000u;
constexpr uint32_t VAR_MIN = 0x3D400000u;

#define TR(ev, idx)
#define ST(i)
#define SC(i)
#define CK(k)
constexpr uint64_t EVICT_FIRST = 0x12F0000000000000ull;
constexpr float LOG2E = 1.4426950408889634f;

__device__ __forceinline__ uint32_t smem_u32(const void* p) {
    return (uint32_t)__cvta_generic_to_shared(p);
}
__device__ __forceinline__ uint64_t make_desc(uint32_t saddr, uint32_t lbo, uint32_t sbo, uint32_t swz = 0) {
    return (uint64_t)((saddr & 0x3FFFF) >> 4) | ((uint64_t)(lbo >> 4) << 16) | ((uint64_t)(sbo >> 4) << 32) |
           ((uint64_t)swz << 62);
}
__host__ __device__ constexpr uint64_t make_desc_c(uint32_t saddr, uint32_t lbo, uint32_t sbo, uint32_t swz) {
    return (uint64_t)(saddr >> 4) | ((uint64_t)(lbo >> 4) << 16) | ((uint64_t)(sbo >> 4) << 32) | ((uint64_t)swz << 62);
}
__device__ __forceinline__ void wgmma_fence()  { asm volatile("wgmma.fence.sync.aligned;\n" ::: "memory"); }
__device__ __forceinline__ void wgmma_commit() { asm volatile("wgmma.commit_group.sync.aligned;\n" ::: "memory"); }
template <int N> __device__ __forceinline__ void wgmma_wait() {
    asm volatile("wgmma.wait_group.sync.aligned %0;\n" :: "n"(N) : "memory");
}
__device__ __forceinline__ void fence_async_smem() { asm volatile("fence.proxy.async.shared::cta;\n" ::: "memory"); }
__device__ __forceinline__ void wg_bar(int id) { asm volatile("bar.sync %0, 128;\n" :: "r"(id) : "memory"); }

template <int N> __device__ __forceinline__ void reg_fence(float (&v)[N]) {
#pragma unroll
    for (int i = 0; i < N; i++) asm volatile("" : "+f"(v[i]) :: "memory");
}
template <int N> __device__ __forceinline__ void reg_fence(uint32_t (&v)[N]) {
#pragma unroll
    for (int i = 0; i < N; i++) asm volatile("" : "+r"(v[i]) :: "memory");
}
template <int N, int M> __device__ __forceinline__ void reg_fence(uint32_t (&v)[N][M]) {
#pragma unroll
    for (int i = 0; i < N; i++) reg_fence(v[i]);
}

__device__ __forceinline__ uint32_t pack_bf16(float lo, float hi) {
    uint32_t r;
    asm("cvt.rn.bf16x2.f32 %0, %1, %2;\n" : "=r"(r) : "f"(hi), "f"(lo));
    return r;
}
__device__ __forceinline__ uint32_t pack_f16(float lo, float hi) {
    uint32_t r;
    asm("cvt.rn.f16x2.f32 %0, %1, %2;\n" : "=r"(r) : "f"(hi), "f"(lo));
    return r;
}
__device__ __forceinline__ uint32_t pack_f16_sat(float lo, float hi) {
    uint32_t r;
    asm("cvt.rn.satfinite.f16x2.f32 %0, %1, %2;\n" : "=r"(r) : "f"(hi), "f"(lo));
    return r;
}
__device__ __forceinline__ uint32_t hmul2_f16(uint32_t a, uint32_t b) {
    uint32_t r;
    asm("mul.rn.f16x2 %0, %1, %2;\n" : "=r"(r) : "r"(a), "r"(b));
    return r;
}
__device__ __forceinline__ uint32_t hadd2_f16(uint32_t a, uint32_t b) {
    uint32_t r;
    asm("add.rn.f16x2 %0, %1, %2;\n" : "=r"(r) : "r"(a), "r"(b));
    return r;
}
__device__ __forceinline__ uint32_t hfma2_f16(uint32_t a, uint32_t b, uint32_t c) {
    uint32_t r;
    asm("fma.rn.f16x2 %0, %1, %2, %3;\n" : "=r"(r) : "r"(a), "r"(b), "r"(c));
    return r;
}
__device__ __forceinline__ uint32_t hmax2_f16(uint32_t a, uint32_t b) {
    uint32_t r;
    asm("max.f16x2 %0, %1, %2;\n" : "=r"(r) : "r"(a), "r"(b));
    return r;
}
template <int H> __device__ __forceinline__ uint32_t hsub2_bc(uint32_t a, uint32_t b) {
    uint32_t r;
    if (H == 0) asm("{\n.reg .b16 l, h;\n.reg .b32 t;\nmov.b32 {l, h}, %2;\nmov.b32 t, {l, l};\nsub.rn.f16x2 %0, %1, t;\n}\n" : "=r"(r) : "r"(a), "r"(b));
    else        asm("{\n.reg .b16 l, h;\n.reg .b32 t;\nmov.b32 {l, h}, %2;\nmov.b32 t, {h, h};\nsub.rn.f16x2 %0, %1, t;\n}\n" : "=r"(r) : "r"(a), "r"(b));
    return r;
}
template <int H> __device__ __forceinline__ uint32_t hmul2_bc(uint32_t a, uint32_t b) {
    uint32_t r;
    if (H == 0) asm("{\n.reg .b16 l, h;\n.reg .b32 t;\nmov.b32 {l, h}, %2;\nmov.b32 t, {l, l};\nmul.rn.f16x2 %0, %1, t;\n}\n" : "=r"(r) : "r"(a), "r"(b));
    else        asm("{\n.reg .b16 l, h;\n.reg .b32 t;\nmov.b32 {l, h}, %2;\nmov.b32 t, {h, h};\nmul.rn.f16x2 %0, %1, t;\n}\n" : "=r"(r) : "r"(a), "r"(b));
    return r;
}
__device__ __forceinline__ uint32_t hsub2_f16(uint32_t a, uint32_t b) {
    uint32_t r;
    asm("sub.rn.f16x2 %0, %1, %2;\n" : "=r"(r) : "r"(a), "r"(b));
    return r;
}
__device__ __forceinline__ uint32_t ex2_f16x2(uint32_t a) {
    uint32_t r;
    asm("ex2.approx.f16x2 %0, %1;\n" : "=r"(r) : "r"(a));
    return r;
}
__device__ __forceinline__ uint32_t ex2_f16lo(uint32_t a) {
    uint32_t r;
    asm("{\n.reg .b16 l, h;\nmov.b32 {l, h}, %1;\nex2.approx.f16 l, l;\nmov.b32 %0, {l, h};\n}\n" : "=r"(r) : "r"(a));
    return r;
}
__device__ __forceinline__ uint32_t lds16(uint32_t addr) {
    uint32_t v;
    asm volatile("ld.shared.u16 %0, [%1];\n" : "=r"(v) : "r"(addr) : "memory");
    return v;
}
__device__ __forceinline__ uint32_t lds16v(uint32_t addr) {
    uint32_t v;
    asm volatile("ld.volatile.shared.u16 %0, [%1];\n" : "=r"(v) : "r"(addr) : "memory");
    return v;
}
__device__ __forceinline__ void sts16(uint32_t addr, uint32_t v) {
    asm volatile("st.volatile.shared.u16 [%0], %1;\n" :: "r"(addr), "r"(v) : "memory");
}
__device__ __forceinline__ float f16lo(uint32_t v) {
    float r;
    asm("{\n.reg .b16 l, h;\nmov.b32 {l, h}, %1;\ncvt.f32.f16 %0, l;\n}\n" : "=f"(r) : "r"(v));
    return r;
}
__device__ __forceinline__ float f16hi(uint32_t v) {
    float r;
    asm("{\n.reg .b16 l, h;\nmov.b32 {l, h}, %1;\ncvt.f32.f16 %0, h;\n}\n" : "=f"(r) : "r"(v));
    return r;
}
__device__ __forceinline__ uint32_t bf2h(uint32_t v) {
    return pack_f16(__uint_as_float(v << 16), __uint_as_float(v & 0xFFFF0000u));
}
__device__ __forceinline__ float bf16lo(uint32_t v) { return __uint_as_float(v << 16); }
__device__ __forceinline__ float bf16hi(uint32_t v) { return __uint_as_float(v & 0xFFFF0000u); }
__device__ __forceinline__ uint32_t hadd2_bf16(uint32_t a, uint32_t b) {
    uint32_t r;
    asm("add.rn.bf16x2 %0, %1, %2;\n" : "=r"(r) : "r"(a), "r"(b));
    return r;
}
__device__ __forceinline__ uint32_t hmul2_bf16(uint32_t a, uint32_t b) {
    uint32_t r;
    asm("mul.rn.bf16x2 %0, %1, %2;\n" : "=r"(r) : "r"(a), "r"(b));
    return r;
}
__device__ __forceinline__ uint32_t hsub2_bf16(uint32_t a, uint32_t b) {
    uint32_t r;
    asm("sub.rn.bf16x2 %0, %1, %2;\n" : "=r"(r) : "r"(a), "r"(b));
    return r;
}
__device__ __forceinline__ uint32_t hfma2_bf16(uint32_t a, uint32_t b, uint32_t c) {
    uint32_t r;
    asm("fma.rn.bf16x2 %0, %1, %2, %3;\n" : "=r"(r) : "r"(a), "r"(b), "r"(c));
    return r;
}
__device__ __forceinline__ uint32_t hmax2_bf16(uint32_t a, uint32_t b) {
    uint32_t r;
    asm("max.bf16x2 %0, %1, %2;\n" : "=r"(r) : "r"(a), "r"(b));
    return r;
}
__device__ __forceinline__ uint32_t ex2_bf16x2(uint32_t a) {
    uint32_t r;
    asm("ex2.approx.ftz.bf16x2 %0, %1;\n" : "=r"(r) : "r"(a));
    return r;
}
__device__ __forceinline__ uint32_t ex2_bf16lo(uint32_t a) {
    uint32_t r;
    asm("{\n.reg .b16 l, h;\nmov.b32 {l, h}, %1;\nex2.approx.ftz.bf16 l, l;\ncvt.u32.u16 %0, l;\n}\n" : "=r"(r) : "r"(a));
    return r;
}
__device__ __forceinline__ uint32_t mbar_test(uint32_t bar, uint32_t parity) {
    uint32_t ok;
    asm volatile("{\n.reg .pred p;\nmbarrier.test_wait.parity.shared::cta.b64 p, [%1], %2;\nselp.u32 %0, 1, 0, p;\n}\n"
                 : "=r"(ok) : "r"(bar), "r"(parity) : "memory");
    return ok;
}
__device__ __forceinline__ uint32_t prmt(uint32_t a, uint32_t b, uint32_t sel) {
    uint32_t r;
    asm("prmt.b32 %0, %1, %2, %3;\n" : "=r"(r) : "r"(a), "r"(b), "r"(sel));
    return r;
}
__device__ __forceinline__ float round_bf16(float x) { return __bfloat162float(__float2bfloat16_rn(x)); }

__device__ __forceinline__ void mbar_init(uint32_t bar, uint32_t count) {
    asm volatile("mbarrier.init.shared::cta.b64 [%0], %1;\n" :: "r"(bar), "r"(count) : "memory");
}
__device__ __forceinline__ void mbar_wait(uint32_t bar, uint32_t parity) {
    asm volatile(
        "{\n"
        ".reg .pred p;\n"
        ".reg .u32 n;\n"
        "mov.u32 n, 0;\n"
        "WAIT_%=:\n"
        "mbarrier.try_wait.parity.shared::cta.b64 p, [%0], %1" HINT_A ";\n"
        "@p bra DONE_%=;\n"
        "add.u32 n, n, 1;\n"
        "setp.lt.u32 p, n, 4194304;\n"
        "@p bra WAIT_%=;\n"
        "exit;\n"
        "DONE_%=:\n"
        "}\n" :: "r"(bar), "r"(parity) : "memory");
}
__device__ __forceinline__ void mbar_wait4(uint32_t b0, uint32_t p0, uint32_t b1, uint32_t p1, uint32_t b2, uint32_t p2,
                                           uint32_t b3, uint32_t p3) {
    asm volatile(
        "{\n"
        ".reg .pred p, q, r, s;\n"
        ".reg .u32 n;\n"
        "mov.u32 n, 0;\n"
        "WAIT_%=:\n"
        "mbarrier.try_wait.parity.shared::cta.b64 p, [%0], %1;\n"
        "mbarrier.try_wait.parity.shared::cta.b64 q, [%2], %3;\n"
        "mbarrier.try_wait.parity.shared::cta.b64 r, [%4], %5;\n"
        "mbarrier.try_wait.parity.shared::cta.b64 s, [%6], %7;\n"
        "and.pred p, p, q;\n"
        "and.pred r, r, s;\n"
        "and.pred p, p, r;\n"
        "@p bra DONE_%=;\n"
        "add.u32 n, n, 1;\n"
        "setp.lt.u32 p, n, 4194304;\n"
        "@p bra WAIT_%=;\n"
        "exit;\n"
        "DONE_%=:\n"
        "}\n" :: "r"(b0), "r"(p0), "r"(b1), "r"(p1), "r"(b2), "r"(p2), "r"(b3), "r"(p3) : "memory");
}
__device__ __forceinline__ void mbar_wait2(uint32_t b0, uint32_t p0, uint32_t b1, uint32_t p1) {
    asm volatile(
        "{\n"
        ".reg .pred p, q;\n"
        ".reg .u32 n;\n"
        "mov.u32 n, 0;\n"
        "WAIT_%=:\n"
        "mbarrier.try_wait.parity.shared::cta.b64 p, [%0], %1;\n"
        "mbarrier.try_wait.parity.shared::cta.b64 q, [%2], %3;\n"
        "and.pred p, p, q;\n"
        "@p bra DONE_%=;\n"
        "add.u32 n, n, 1;\n"
        "setp.lt.u32 p, n, 4194304;\n"
        "@p bra WAIT_%=;\n"
        "exit;\n"
        "DONE_%=:\n"
        "}\n" :: "r"(b0), "r"(p0), "r"(b1), "r"(p1) : "memory");
}
__device__ __forceinline__ void mbar_wait_unless(uint32_t ok, uint32_t bar, uint32_t parity) {
    asm volatile(
        "{\n"
        ".reg .pred p;\n"
        ".reg .u32 n;\n"
        "setp.ne.u32 p, %2, 0;\n"
        "vote.sync.all.pred p, p, 0xffffffff;\n"
        "@p bra DONE_%=;\n"
        "mov.u32 n, 0;\n"
        "WAIT_%=:\n"
        "mbarrier.try_wait.parity.shared::cta.b64 p, [%0], %1" HINT_B ";\n"
        "@p bra DONE_%=;\n"
        "add.u32 n, n, 1;\n"
        "setp.lt.u32 p, n, 4194304;\n"
        "@p bra WAIT_%=;\n"
        "exit;\n"
        "DONE_%=:\n"
        "}\n" :: "r"(bar), "r"(parity), "r"(ok) : "memory");
}
__device__ __forceinline__ void mbar_wait_unless_dep(uint32_t ok, uint32_t bar, uint32_t parity, uint32_t zero, uint32_t& a,
                                                     uint32_t& b, uint32_t& c, uint32_t& d) {
    asm volatile(
        "{\n"
        ".reg .pred p;\n"
        ".reg .u32 n;\n"
        "setp.ne.u32 p, %6, 0;\n"
        "vote.sync.all.pred p, p, 0xffffffff;\n"
        "@p bra DONE_%=;\n"
        "mov.u32 n, 0;\n"
        "WAIT_%=:\n"
        "setp.ne.u32 p, %7, 0;\n"
        "@p ld.shared.v4.b32 {%0, %1, %2, %3}, [%7];\n"
        "mbarrier.try_wait.parity.shared::cta.b64 p, [%4], %5;\n"
        "@p bra DONE_%=;\n"
        "add.u32 n, n, 1;\n"
        "setp.lt.u32 p, n, 4194304;\n"
        "@p bra WAIT_%=;\n"
        "exit;\n"
        "DONE_%=:\n"
        "}\n" : "+r"(a), "+r"(b), "+r"(c), "+r"(d) : "r"(bar), "r"(parity), "r"(ok), "r"(zero) : "memory");
}
__device__ __forceinline__ void mbar_wait2_unless(uint32_t ok, uint32_t b0, uint32_t p0, uint32_t b1, uint32_t p1) {
    asm volatile(
        "{\n"
        ".reg .pred p, q;\n"
        ".reg .u32 n;\n"
        "setp.ne.u32 p, %4, 0;\n"
        "vote.sync.all.pred p, p, 0xffffffff;\n"
        "@p bra DONE_%=;\n"
        "mov.u32 n, 0;\n"
        "WAIT_%=:\n"
        "mbarrier.try_wait.parity.shared::cta.b64 p, [%0], %1" HINT_B ";\n"
        "mbarrier.try_wait.parity.shared::cta.b64 q, [%2], %3" HINT_B ";\n"
        "and.pred p, p, q;\n"
        "@p bra DONE_%=;\n"
        "add.u32 n, n, 1;\n"
        "setp.lt.u32 p, n, 4194304;\n"
        "@p bra WAIT_%=;\n"
        "exit;\n"
        "DONE_%=:\n"
        "}\n" :: "r"(b0), "r"(p0), "r"(b1), "r"(p1), "r"(ok) : "memory");
}
__device__ __forceinline__ void mbar_wait4_unless(uint32_t ok, uint32_t b0, uint32_t p0, uint32_t b1, uint32_t p1, uint32_t b2,
                                                  uint32_t p2, uint32_t b3, uint32_t p3) {
    asm volatile(
        "{\n"
        ".reg .pred p, q, r, s;\n"
        ".reg .u32 n;\n"
        "setp.ne.u32 p, %8, 0;\n"
        "vote.sync.all.pred p, p, 0xffffffff;\n"
        "@p bra DONE_%=;\n"
        "mov.u32 n, 0;\n"
        "WAIT_%=:\n"
        "mbarrier.try_wait.parity.shared::cta.b64 p, [%0], %1;\n"
        "mbarrier.try_wait.parity.shared::cta.b64 q, [%2], %3;\n"
        "mbarrier.try_wait.parity.shared::cta.b64 r, [%4], %5;\n"
        "mbarrier.try_wait.parity.shared::cta.b64 s, [%6], %7;\n"
        "and.pred p, p, q;\n"
        "and.pred r, r, s;\n"
        "and.pred p, p, r;\n"
        "@p bra DONE_%=;\n"
        "add.u32 n, n, 1;\n"
        "setp.lt.u32 p, n, 4194304;\n"
        "@p bra WAIT_%=;\n"
        "exit;\n"
        "DONE_%=:\n"
        "}\n" :: "r"(b0), "r"(p0), "r"(b1), "r"(p1), "r"(b2), "r"(p2), "r"(b3), "r"(p3), "r"(ok) : "memory");
}
__device__ __forceinline__ void sched_fence(uint32_t zero, uint32_t a, uint32_t b, uint32_t c, uint32_t d, uint32_t e = 0,
                                            uint32_t f = 0, uint32_t g = 0, uint32_t h = 0, uint32_t i = 0, uint32_t j = 0,
                                            uint32_t k = 0) {
    asm volatile("{\n.reg .pred p;\n.reg .u32 n;\nsetp.eq.u32 p, %0, 0;\n@p bra.uni DONE_%=;\nmov.u32 n, %0;\nSPIN_%=:\n"
                 "nanosleep.u32 %1;\nnanosleep.u32 %2;\nnanosleep.u32 %3;\nnanosleep.u32 %4;\nnanosleep.u32 %5;\n"
                 "nanosleep.u32 %6;\nnanosleep.u32 %7;\nnanosleep.u32 %8;\nnanosleep.u32 %9;\nnanosleep.u32 %10;\n"
                 "nanosleep.u32 %11;\nsub.u32 n, n, 1;\nsetp.ne.u32 p, n, 0;\n@p bra.uni SPIN_%=;\nDONE_%=:\n}\n"
                 :: "r"(zero), "r"(a), "r"(b), "r"(c), "r"(d), "r"(e), "r"(f), "r"(g), "r"(h), "r"(i), "r"(j), "r"(k) : "memory");
}
__device__ __forceinline__ void sched_fence16(uint32_t zero, const uint32_t (&v)[4][4], uint32_t a = 0, uint32_t b = 0) {
    asm volatile("{\n.reg .pred p;\n.reg .u32 n;\nsetp.eq.u32 p, %0, 0;\n@p bra.uni DONE_%=;\nmov.u32 n, %0;\nSPIN_%=:\n"
                 "nanosleep.u32 %17;\nnanosleep.u32 %18;\n"
                 "st.shared.v4.b32 [n], {%1, %2, %3, %4};\nst.shared.v4.b32 [n + 16], {%5, %6, %7, %8};\n"
                 "st.shared.v4.b32 [n + 32], {%9, %10, %11, %12};\nst.shared.v4.b32 [n + 48], {%13, %14, %15, %16};\n"
                 "sub.u32 n, n, 1;\nsetp.ne.u32 p, n, 0;\n@p bra.uni SPIN_%=;\nDONE_%=:\n}\n"
                 :: "r"(zero), "r"(v[0][0]), "r"(v[0][1]), "r"(v[0][2]), "r"(v[0][3]), "r"(v[1][0]), "r"(v[1][1]), "r"(v[1][2]), "r"(v[1][3]),
                    "r"(v[2][0]), "r"(v[2][1]), "r"(v[2][2]), "r"(v[2][3]), "r"(v[3][0]), "r"(v[3][1]), "r"(v[3][2]), "r"(v[3][3]),
                    "r"(a), "r"(b) : "memory");
}
__device__ __forceinline__ void sched_dep(uint32_t zero, uint32_t& a, uint32_t& b, uint32_t& c, uint32_t& d) {
    asm volatile("{\n.reg .pred p;\n.reg .u32 n;\nsetp.eq.u32 p, %4, 0;\n@p bra.uni DONE_%=;\nmov.u32 n, %4;\nSPIN_%=:\n"
                 "ld.shared.v4.b32 {%0, %1, %2, %3}, [n];\n"
                 "sub.u32 n, n, 1;\nsetp.ne.u32 p, n, 0;\n@p bra.uni SPIN_%=;\nDONE_%=:\n}\n"
                 : "+r"(a), "+r"(b), "+r"(c), "+r"(d) : "r"(zero) : "memory");
}
__device__ __forceinline__ void mbar_arrive(uint32_t bar) {
    asm volatile("mbarrier.arrive.shared::cta.b64 _, [%0];\n" :: "r"(bar) : "memory");
}
__device__ __forceinline__ void mbar_arrive_n(uint32_t bar, uint32_t n) {
    asm volatile("mbarrier.arrive.shared::cta.b64 _, [%0], %1;\n" :: "r"(bar), "r"(n) : "memory");
}
__device__ __forceinline__ void mbar_arrive_expect_tx(uint32_t bar, uint32_t bytes) {
    asm volatile("mbarrier.arrive.expect_tx.shared::cta.b64 _, [%0], %1;\n" :: "r"(bar), "r"(bytes) : "memory");
}
__device__ __forceinline__ void stg128_if(bool p, void* addr, uint32_t x, uint32_t y, uint32_t z, uint32_t w) {
    asm volatile("{\n.reg .pred q;\nsetp.ne.b32 q, %5, 0;\n@q st.global.L1::no_allocate.L2::cache_hint.v4.b32 [%0], {%1, %2, %3, %4}, %6;\n}\n"
                 :: "l"(addr), "r"(x), "r"(y), "r"(z), "r"(w), "r"((uint32_t)p), "l"(EVICT_FIRST) : "memory");
}
__device__ __forceinline__ void stsm_x4(uint32_t addr, uint32_t r0, uint32_t r1, uint32_t r2, uint32_t r3) {
    asm volatile("stmatrix.sync.aligned.m8n8.x4.shared.b16 [%0], {%1, %2, %3, %4};\n"
                 :: "r"(addr), "r"(r0), "r"(r1), "r"(r2), "r"(r3) : "memory");
}
__device__ __forceinline__ void stsm_x4_if(bool p, uint32_t addr, uint32_t r0, uint32_t r1, uint32_t r2, uint32_t r3) {
    asm volatile("{\n.reg .pred q;\nsetp.ne.b32 q, %5, 0;\n@q stmatrix.sync.aligned.m8n8.x4.shared.b16 [%0], {%1, %2, %3, %4};\n}\n"
                 :: "r"(addr), "r"(r0), "r"(r1), "r"(r2), "r"(r3), "r"((uint32_t)p) : "memory");
}
__device__ __forceinline__ void stsm_x2(uint32_t addr, uint32_t r0, uint32_t r1) {
    asm volatile("stmatrix.sync.aligned.m8n8.x2.shared.b16 [%0], {%1, %2};\n" :: "r"(addr), "r"(r0), "r"(r1) : "memory");
}
__device__ __forceinline__ void sts128(uint32_t addr, uint32_t r0, uint32_t r1, uint32_t r2, uint32_t r3) {
    asm volatile("st.shared.v4.b32 [%0], {%1, %2, %3, %4};\n" :: "r"(addr), "r"(r0), "r"(r1), "r"(r2), "r"(r3) : "memory");
}
__device__ __forceinline__ void sts32(uint32_t addr, uint32_t v) {
    asm volatile("st.shared.b32 [%0], %1;\n" :: "r"(addr), "r"(v) : "memory");
}
__device__ __forceinline__ uint32_t lds32(uint32_t addr) {
    uint32_t v;
    asm volatile("ld.shared.b32 %0, [%1];\n" : "=r"(v) : "r"(addr) : "memory");
    return v;
}
__device__ __forceinline__ void lds128(uint32_t (&r)[4], uint32_t addr) {
    asm volatile("ld.shared.v4.b32 {%0, %1, %2, %3}, [%4];\n" : "=r"(r[0]), "=r"(r[1]), "=r"(r[2]), "=r"(r[3]) : "r"(addr) : "memory");
}
__device__ __forceinline__ uint32_t lds32v(uint32_t addr) {
    uint32_t v;
    asm volatile("ld.volatile.shared.b32 %0, [%1];\n" : "=r"(v) : "r"(addr) : "memory");
    return v;
}
__device__ __forceinline__ void ldg_nc_v4(uint32_t (&r)[4], const void* p) {
    asm volatile("ld.global.nc.L1::no_allocate.v4.u32 {%0, %1, %2, %3}, [%4];\n"
                 : "=r"(r[0]), "=r"(r[1]), "=r"(r[2]), "=r"(r[3]) : "l"(p));
}
__device__ __forceinline__ uint32_t ldg_u32(const void* p) {
    uint32_t v;
    asm volatile("ld.global.nc.L1::evict_first.u32 %0, [%1];\n" : "=r"(v) : "l"(p));
    return v;
}
__device__ __forceinline__ void ldg_u64(const void* p, uint32_t& a, uint32_t& b) {
    asm volatile("ld.global.nc.L1::evict_first.v2.u32 {%0, %1}, [%2];\n" : "=r"(a), "=r"(b) : "l"(p));
}
__device__ __forceinline__ void prefetch_l2(const void* p) {
    asm volatile("prefetch.global.L2 [%0];\n" :: "l"(p));
}
__device__ __forceinline__ void cp_async16(uint32_t dst, const void* src) {
    asm volatile("cp.async.cg.shared.global [%0], [%1], 16;\n" :: "r"(dst), "l"(src) : "memory");
}
__device__ __forceinline__ float ex2_ftz(float x) {
    float y;
    asm("ex2.approx.ftz.f32 %0, %1;\n" : "=f"(y) : "f"(x));
    return y;
}
__device__ __forceinline__ float rcp_ftz(float x) {
    float y;
    asm("rcp.approx.ftz.f32 %0, %1;\n" : "=f"(y) : "f"(x));
    return y;
}
__device__ __forceinline__ float rsqrt_ftz(float x) {
    float y;
    asm("rsqrt.approx.ftz.f32 %0, %1;\n" : "=f"(y) : "f"(x));
    return y;
}

__device__ __forceinline__ bool elect_one() {
    uint32_t p;
    asm volatile("{\n.reg .pred q;\nelect.sync _|q, 0xffffffff;\nselp.u32 %0, 1, 0, q;\n}\n" : "=r"(p));
    return p != 0;
}
__device__ __forceinline__ void ldsm_x4(uint32_t (&r)[4], uint32_t addr) {
    asm volatile("ldmatrix.sync.aligned.m8n8.x4.shared.b16 {%0, %1, %2, %3}, [%4];\n"
                 : "=r"(r[0]), "=r"(r[1]), "=r"(r[2]), "=r"(r[3]) : "r"(addr) : "memory");
}
__device__ __forceinline__ void ldsm_x2(uint32_t& r0, uint32_t& r1, uint32_t addr) {
    asm volatile("ldmatrix.sync.aligned.m8n8.x2.shared.b16 {%0, %1}, [%2];\n" : "=r"(r0), "=r"(r1) : "r"(addr) : "memory");
}
__device__ __forceinline__ void tma_2d(uint32_t dst, const CUtensorMap* map, uint32_t bar, int c0, int c1) {
    asm volatile("cp.async.bulk.tensor.2d.shared::cluster.global.mbarrier::complete_tx::bytes [%0], [%1, {%3, %4}], [%2];\n"
                 :: "r"(dst), "l"(reinterpret_cast<uint64_t>(map)), "r"(bar), "r"(c0), "r"(c1) : "memory");
}
__device__ __forceinline__ void tma_3d(uint32_t dst, const CUtensorMap* map, uint32_t bar, int c0, int c1, int c2) {
    asm volatile("cp.async.bulk.tensor.3d.shared::cluster.global.mbarrier::complete_tx::bytes [%0], [%1, {%3, %4, %5}], [%2];\n"
                 :: "r"(dst), "l"(reinterpret_cast<uint64_t>(map)), "r"(bar), "r"(c0), "r"(c1), "r"(c2) : "memory");
}
__device__ __forceinline__ void tma_store_4d(const CUtensorMap* map, uint32_t src, int c0, int c1, int c2, int c3) {
    asm volatile("cp.async.bulk.tensor.4d.global.shared::cta.tile.bulk_group [%0, {%2, %3, %4, %5}], [%1];\n"
                 :: "l"(reinterpret_cast<uint64_t>(map)), "r"(src), "r"(c0), "r"(c1), "r"(c2), "r"(c3) : "memory");
}
__device__ __forceinline__ void mbar_arrive_if(uint32_t bar, uint32_t cnt) {
    asm volatile("{\n.reg .pred q;\nsetp.ne.b32 q, %1, 0;\n@q mbarrier.arrive.shared::cta.b64 _, [%0], %1;\n}\n"
                 :: "r"(bar), "r"(cnt) : "memory");
}

template <int BOFF, int AOFF, int NA>
__device__ __forceinline__ void mma_qk_first(uint32_t (&d)[48], const uint32_t (&a)[NA][4], uint64_t descB) {
    asm volatile(
        "{\n"
        ".reg .pred p0, p1;\n"
        ".reg .b64 ta, ta0, tb, tb0;\n"
        "setp.ne.b32 p0, 0, 0;\n"
        "setp.eq.b32 p1, 0, 0;\n"
        "add.s64 tb0, %64, %65;\n"
        "add.s64 tb, tb0, 0;\n"
        "wgmma.mma_async.sync.aligned.m64n192k16.f16.f16.f16 {%0, %1, %2, %3, %4, %5, %6, %7, %8, %9, %10, %11, %12, %13, %14, %15, %16, %17, %18, %19, %20, %21, %22, %23, %24, %25, %26, %27, %28, %29, %30, %31, %32, %33, %34, %35, %36, %37, %38, %39, %40, %41, %42, %43, %44, %45, %46, %47}, {%48, %49, %50, %51}, tb, p0, 1, 1, 1;\n"
        "add.s64 tb, tb0, 32;\n"
        "wgmma.mma_async.sync.aligned.m64n192k16.f16.f16.f16 {%0, %1, %2, %3, %4, %5, %6, %7, %8, %9, %10, %11, %12, %13, %14, %15, %16, %17, %18, %19, %20, %21, %22, %23, %24, %25, %26, %27, %28, %29, %30, %31, %32, %33, %34, %35, %36, %37, %38, %39, %40, %41, %42, %43, %44, %45, %46, %47}, {%52, %53, %54, %55}, tb, p1, 1, 1, 1;\n"
        "add.s64 tb, tb0, 64;\n"
        "wgmma.mma_async.sync.aligned.m64n192k16.f16.f16.f16 {%0, %1, %2, %3, %4, %5, %6, %7, %8, %9, %10, %11, %12, %13, %14, %15, %16, %17, %18, %19, %20, %21, %22, %23, %24, %25, %26, %27, %28, %29, %30, %31, %32, %33, %34, %35, %36, %37, %38, %39, %40, %41, %42, %43, %44, %45, %46, %47}, {%56, %57, %58, %59}, tb, p1, 1, 1, 1;\n"
        "add.s64 tb, tb0, 96;\n"
        "wgmma.mma_async.sync.aligned.m64n192k16.f16.f16.f16 {%0, %1, %2, %3, %4, %5, %6, %7, %8, %9, %10, %11, %12, %13, %14, %15, %16, %17, %18, %19, %20, %21, %22, %23, %24, %25, %26, %27, %28, %29, %30, %31, %32, %33, %34, %35, %36, %37, %38, %39, %40, %41, %42, %43, %44, %45, %46, %47}, {%60, %61, %62, %63}, tb, p1, 1, 1, 1;\n"
        "}\n"
        : "=r"(d[0]), "=r"(d[1]), "=r"(d[2]), "=r"(d[3]), "=r"(d[4]), "=r"(d[5]), "=r"(d[6]), "=r"(d[7]), "=r"(d[8]), "=r"(d[9]), "=r"(d[10]), "=r"(d[11]), "=r"(d[12]), "=r"(d[13]), "=r"(d[14]), "=r"(d[15]), "=r"(d[16]), "=r"(d[17]), "=r"(d[18]), "=r"(d[19]), "=r"(d[20]), "=r"(d[21]), "=r"(d[22]), "=r"(d[23]), "=r"(d[24]), "=r"(d[25]), "=r"(d[26]), "=r"(d[27]), "=r"(d[28]), "=r"(d[29]), "=r"(d[30]), "=r"(d[31]), "=r"(d[32]), "=r"(d[33]), "=r"(d[34]), "=r"(d[35]), "=r"(d[36]), "=r"(d[37]), "=r"(d[38]), "=r"(d[39]), "=r"(d[40]), "=r"(d[41]), "=r"(d[42]), "=r"(d[43]), "=r"(d[44]), "=r"(d[45]), "=r"(d[46]), "=r"(d[47])
        : "r"(a[AOFF + 0][0]), "r"(a[AOFF + 0][1]), "r"(a[AOFF + 0][2]), "r"(a[AOFF + 0][3]), "r"(a[AOFF + 1][0]), "r"(a[AOFF + 1][1]), "r"(a[AOFF + 1][2]), "r"(a[AOFF + 1][3]), "r"(a[AOFF + 2][0]), "r"(a[AOFF + 2][1]), "r"(a[AOFF + 2][2]), "r"(a[AOFF + 2][3]), "r"(a[AOFF + 3][0]), "r"(a[AOFF + 3][1]), "r"(a[AOFF + 3][2]), "r"(a[AOFF + 3][3]), "l"(descB), "n"(BOFF >> 4));
}

template <int BOFF, int AOFF, int NA>
__device__ __forceinline__ void mma_qk_next(uint32_t (&d)[48], const uint32_t (&a)[NA][4], uint64_t descB) {
    asm volatile(
        "{\n"
        ".reg .pred p0, p1;\n"
        ".reg .b64 ta, ta0, tb, tb0;\n"
        "setp.ne.b32 p0, 0, 0;\n"
        "setp.eq.b32 p1, 0, 0;\n"
        "add.s64 tb0, %64, %65;\n"
        "add.s64 tb, tb0, 0;\n"
        "wgmma.mma_async.sync.aligned.m64n192k16.f16.f16.f16 {%0, %1, %2, %3, %4, %5, %6, %7, %8, %9, %10, %11, %12, %13, %14, %15, %16, %17, %18, %19, %20, %21, %22, %23, %24, %25, %26, %27, %28, %29, %30, %31, %32, %33, %34, %35, %36, %37, %38, %39, %40, %41, %42, %43, %44, %45, %46, %47}, {%48, %49, %50, %51}, tb, p1, 1, 1, 1;\n"
        "add.s64 tb, tb0, 32;\n"
        "wgmma.mma_async.sync.aligned.m64n192k16.f16.f16.f16 {%0, %1, %2, %3, %4, %5, %6, %7, %8, %9, %10, %11, %12, %13, %14, %15, %16, %17, %18, %19, %20, %21, %22, %23, %24, %25, %26, %27, %28, %29, %30, %31, %32, %33, %34, %35, %36, %37, %38, %39, %40, %41, %42, %43, %44, %45, %46, %47}, {%52, %53, %54, %55}, tb, p1, 1, 1, 1;\n"
        "add.s64 tb, tb0, 64;\n"
        "wgmma.mma_async.sync.aligned.m64n192k16.f16.f16.f16 {%0, %1, %2, %3, %4, %5, %6, %7, %8, %9, %10, %11, %12, %13, %14, %15, %16, %17, %18, %19, %20, %21, %22, %23, %24, %25, %26, %27, %28, %29, %30, %31, %32, %33, %34, %35, %36, %37, %38, %39, %40, %41, %42, %43, %44, %45, %46, %47}, {%56, %57, %58, %59}, tb, p1, 1, 1, 1;\n"
        "add.s64 tb, tb0, 96;\n"
        "wgmma.mma_async.sync.aligned.m64n192k16.f16.f16.f16 {%0, %1, %2, %3, %4, %5, %6, %7, %8, %9, %10, %11, %12, %13, %14, %15, %16, %17, %18, %19, %20, %21, %22, %23, %24, %25, %26, %27, %28, %29, %30, %31, %32, %33, %34, %35, %36, %37, %38, %39, %40, %41, %42, %43, %44, %45, %46, %47}, {%60, %61, %62, %63}, tb, p1, 1, 1, 1;\n"
        "}\n"
        : "+r"(d[0]), "+r"(d[1]), "+r"(d[2]), "+r"(d[3]), "+r"(d[4]), "+r"(d[5]), "+r"(d[6]), "+r"(d[7]), "+r"(d[8]), "+r"(d[9]), "+r"(d[10]), "+r"(d[11]), "+r"(d[12]), "+r"(d[13]), "+r"(d[14]), "+r"(d[15]), "+r"(d[16]), "+r"(d[17]), "+r"(d[18]), "+r"(d[19]), "+r"(d[20]), "+r"(d[21]), "+r"(d[22]), "+r"(d[23]), "+r"(d[24]), "+r"(d[25]), "+r"(d[26]), "+r"(d[27]), "+r"(d[28]), "+r"(d[29]), "+r"(d[30]), "+r"(d[31]), "+r"(d[32]), "+r"(d[33]), "+r"(d[34]), "+r"(d[35]), "+r"(d[36]), "+r"(d[37]), "+r"(d[38]), "+r"(d[39]), "+r"(d[40]), "+r"(d[41]), "+r"(d[42]), "+r"(d[43]), "+r"(d[44]), "+r"(d[45]), "+r"(d[46]), "+r"(d[47])
        : "r"(a[AOFF + 0][0]), "r"(a[AOFF + 0][1]), "r"(a[AOFF + 0][2]), "r"(a[AOFF + 0][3]), "r"(a[AOFF + 1][0]), "r"(a[AOFF + 1][1]), "r"(a[AOFF + 1][2]), "r"(a[AOFF + 1][3]), "r"(a[AOFF + 2][0]), "r"(a[AOFF + 2][1]), "r"(a[AOFF + 2][2]), "r"(a[AOFF + 2][3]), "r"(a[AOFF + 3][0]), "r"(a[AOFF + 3][1]), "r"(a[AOFF + 3][2]), "r"(a[AOFF + 3][3]), "l"(descB), "n"(BOFF >> 4));
}

template <int BOFF, int AOFF, int NA>
__device__ __forceinline__ void mma_v_first(uint32_t (&d)[24], const uint32_t (&a)[NA][4], uint64_t descB) {
    asm volatile(
        "{\n"
        ".reg .pred p0, p1;\n"
        ".reg .b64 ta, ta0, tb, tb0;\n"
        "setp.ne.b32 p0, 0, 0;\n"
        "setp.eq.b32 p1, 0, 0;\n"
        "add.s64 tb0, %40, %41;\n"
        "add.s64 tb, tb0, 0;\n"
        "wgmma.mma_async.sync.aligned.m64n96k16.f16.f16.f16 {%0, %1, %2, %3, %4, %5, %6, %7, %8, %9, %10, %11, %12, %13, %14, %15, %16, %17, %18, %19, %20, %21, %22, %23}, {%24, %25, %26, %27}, tb, p0, 1, 1, 1;\n"
        "add.s64 tb, tb0, 32;\n"
        "wgmma.mma_async.sync.aligned.m64n96k16.f16.f16.f16 {%0, %1, %2, %3, %4, %5, %6, %7, %8, %9, %10, %11, %12, %13, %14, %15, %16, %17, %18, %19, %20, %21, %22, %23}, {%28, %29, %30, %31}, tb, p1, 1, 1, 1;\n"
        "add.s64 tb, tb0, 64;\n"
        "wgmma.mma_async.sync.aligned.m64n96k16.f16.f16.f16 {%0, %1, %2, %3, %4, %5, %6, %7, %8, %9, %10, %11, %12, %13, %14, %15, %16, %17, %18, %19, %20, %21, %22, %23}, {%32, %33, %34, %35}, tb, p1, 1, 1, 1;\n"
        "add.s64 tb, tb0, 96;\n"
        "wgmma.mma_async.sync.aligned.m64n96k16.f16.f16.f16 {%0, %1, %2, %3, %4, %5, %6, %7, %8, %9, %10, %11, %12, %13, %14, %15, %16, %17, %18, %19, %20, %21, %22, %23}, {%36, %37, %38, %39}, tb, p1, 1, 1, 1;\n"
        "}\n"
        : "=r"(d[0]), "=r"(d[1]), "=r"(d[2]), "=r"(d[3]), "=r"(d[4]), "=r"(d[5]), "=r"(d[6]), "=r"(d[7]), "=r"(d[8]), "=r"(d[9]), "=r"(d[10]), "=r"(d[11]), "=r"(d[12]), "=r"(d[13]), "=r"(d[14]), "=r"(d[15]), "=r"(d[16]), "=r"(d[17]), "=r"(d[18]), "=r"(d[19]), "=r"(d[20]), "=r"(d[21]), "=r"(d[22]), "=r"(d[23])
        : "r"(a[AOFF + 0][0]), "r"(a[AOFF + 0][1]), "r"(a[AOFF + 0][2]), "r"(a[AOFF + 0][3]), "r"(a[AOFF + 1][0]), "r"(a[AOFF + 1][1]), "r"(a[AOFF + 1][2]), "r"(a[AOFF + 1][3]), "r"(a[AOFF + 2][0]), "r"(a[AOFF + 2][1]), "r"(a[AOFF + 2][2]), "r"(a[AOFF + 2][3]), "r"(a[AOFF + 3][0]), "r"(a[AOFF + 3][1]), "r"(a[AOFF + 3][2]), "r"(a[AOFF + 3][3]), "l"(descB), "n"(BOFF >> 4));
}

template <int BOFF, int AOFF, int NA>
__device__ __forceinline__ void mma_v_next(uint32_t (&d)[24], const uint32_t (&a)[NA][4], uint64_t descB) {
    asm volatile(
        "{\n"
        ".reg .pred p0, p1;\n"
        ".reg .b64 ta, ta0, tb, tb0;\n"
        "setp.ne.b32 p0, 0, 0;\n"
        "setp.eq.b32 p1, 0, 0;\n"
        "add.s64 tb0, %40, %41;\n"
        "add.s64 tb, tb0, 0;\n"
        "wgmma.mma_async.sync.aligned.m64n96k16.f16.f16.f16 {%0, %1, %2, %3, %4, %5, %6, %7, %8, %9, %10, %11, %12, %13, %14, %15, %16, %17, %18, %19, %20, %21, %22, %23}, {%24, %25, %26, %27}, tb, p1, 1, 1, 1;\n"
        "add.s64 tb, tb0, 32;\n"
        "wgmma.mma_async.sync.aligned.m64n96k16.f16.f16.f16 {%0, %1, %2, %3, %4, %5, %6, %7, %8, %9, %10, %11, %12, %13, %14, %15, %16, %17, %18, %19, %20, %21, %22, %23}, {%28, %29, %30, %31}, tb, p1, 1, 1, 1;\n"
        "add.s64 tb, tb0, 64;\n"
        "wgmma.mma_async.sync.aligned.m64n96k16.f16.f16.f16 {%0, %1, %2, %3, %4, %5, %6, %7, %8, %9, %10, %11, %12, %13, %14, %15, %16, %17, %18, %19, %20, %21, %22, %23}, {%32, %33, %34, %35}, tb, p1, 1, 1, 1;\n"
        "add.s64 tb, tb0, 96;\n"
        "wgmma.mma_async.sync.aligned.m64n96k16.f16.f16.f16 {%0, %1, %2, %3, %4, %5, %6, %7, %8, %9, %10, %11, %12, %13, %14, %15, %16, %17, %18, %19, %20, %21, %22, %23}, {%36, %37, %38, %39}, tb, p1, 1, 1, 1;\n"
        "}\n"
        : "+r"(d[0]), "+r"(d[1]), "+r"(d[2]), "+r"(d[3]), "+r"(d[4]), "+r"(d[5]), "+r"(d[6]), "+r"(d[7]), "+r"(d[8]), "+r"(d[9]), "+r"(d[10]), "+r"(d[11]), "+r"(d[12]), "+r"(d[13]), "+r"(d[14]), "+r"(d[15]), "+r"(d[16]), "+r"(d[17]), "+r"(d[18]), "+r"(d[19]), "+r"(d[20]), "+r"(d[21]), "+r"(d[22]), "+r"(d[23])
        : "r"(a[AOFF + 0][0]), "r"(a[AOFF + 0][1]), "r"(a[AOFF + 0][2]), "r"(a[AOFF + 0][3]), "r"(a[AOFF + 1][0]), "r"(a[AOFF + 1][1]), "r"(a[AOFF + 1][2]), "r"(a[AOFF + 1][3]), "r"(a[AOFF + 2][0]), "r"(a[AOFF + 2][1]), "r"(a[AOFF + 2][2]), "r"(a[AOFF + 2][3]), "r"(a[AOFF + 3][0]), "r"(a[AOFF + 3][1]), "r"(a[AOFF + 3][2]), "r"(a[AOFF + 3][3]), "l"(descB), "n"(BOFF >> 4));
}

template <int AOFF, int BOFF>
__device__ __forceinline__ void mma_s0_f32(float (&d)[28], uint64_t descA, uint64_t descB) {
    asm volatile(
        "{\n"
        ".reg .pred p0, p1;\n"
        ".reg .b64 ta, ta0, tb, tb0;\n"
        "setp.ne.b32 p0, 0, 0;\n"
        "setp.eq.b32 p1, 0, 0;\n"
        "add.s64 tb0, %30, %31;\n"
        "add.s64 ta0, %28, %29;\n"
        "add.s64 tb, tb0, 4;\n"
        "add.s64 ta, ta0, 0;\n"
        "wgmma.mma_async.sync.aligned.m64n56k16.f32.f16.f16 {%0, %1, %2, %3, %4, %5, %6, %7, %8, %9, %10, %11, %12, %13, %14, %15, %16, %17, %18, %19, %20, %21, %22, %23, %24, %25, %26, %27}, ta, tb, p1, 1, 1, 0, 0;\n"
        "add.s64 tb, tb0, 1572;\n"
        "add.s64 ta, ta0, 1568;\n"
        "wgmma.mma_async.sync.aligned.m64n56k16.f32.f16.f16 {%0, %1, %2, %3, %4, %5, %6, %7, %8, %9, %10, %11, %12, %13, %14, %15, %16, %17, %18, %19, %20, %21, %22, %23, %24, %25, %26, %27}, ta, tb, p1, 1, 1, 0, 0;\n"
        "add.s64 tb, tb0, 3140;\n"
        "add.s64 ta, ta0, 3136;\n"
        "wgmma.mma_async.sync.aligned.m64n56k16.f32.f16.f16 {%0, %1, %2, %3, %4, %5, %6, %7, %8, %9, %10, %11, %12, %13, %14, %15, %16, %17, %18, %19, %20, %21, %22, %23, %24, %25, %26, %27}, ta, tb, p1, 1, 1, 0, 0;\n"
        "}\n"
        : "+f"(d[0]), "+f"(d[1]), "+f"(d[2]), "+f"(d[3]), "+f"(d[4]), "+f"(d[5]), "+f"(d[6]), "+f"(d[7]), "+f"(d[8]), "+f"(d[9]), "+f"(d[10]), "+f"(d[11]), "+f"(d[12]), "+f"(d[13]), "+f"(d[14]), "+f"(d[15]), "+f"(d[16]), "+f"(d[17]), "+f"(d[18]), "+f"(d[19]), "+f"(d[20]), "+f"(d[21]), "+f"(d[22]), "+f"(d[23]), "+f"(d[24]), "+f"(d[25]), "+f"(d[26]), "+f"(d[27])
        : "l"(descA), "n"(AOFF >> 4), "l"(descB), "n"(BOFF >> 4));
}

template <int AOFF, int BOFF>
__device__ __forceinline__ void mma_s0_f16(uint32_t (&d)[14], uint64_t descA, uint64_t descB) {
    asm volatile(
        "{\n"
        ".reg .pred p0, p1;\n"
        ".reg .b64 ta, ta0, tb, tb0;\n"
        "setp.ne.b32 p0, 0, 0;\n"
        "setp.eq.b32 p1, 0, 0;\n"
        "add.s64 tb0, %16, %17;\n"
        "add.s64 ta0, %14, %15;\n"
        "add.s64 tb, tb0, 4;\n"
        "add.s64 ta, ta0, 0;\n"
        "wgmma.mma_async.sync.aligned.m64n56k16.f16.f16.f16 {%0, %1, %2, %3, %4, %5, %6, %7, %8, %9, %10, %11, %12, %13}, ta, tb, p1, 1, 1, 0, 0;\n"
        "add.s64 tb, tb0, 1572;\n"
        "add.s64 ta, ta0, 1568;\n"
        "wgmma.mma_async.sync.aligned.m64n56k16.f16.f16.f16 {%0, %1, %2, %3, %4, %5, %6, %7, %8, %9, %10, %11, %12, %13}, ta, tb, p1, 1, 1, 0, 0;\n"
        "add.s64 tb, tb0, 3140;\n"
        "add.s64 ta, ta0, 3136;\n"
        "wgmma.mma_async.sync.aligned.m64n56k16.f16.f16.f16 {%0, %1, %2, %3, %4, %5, %6, %7, %8, %9, %10, %11, %12, %13}, ta, tb, p1, 1, 1, 0, 0;\n"
        "}\n"
        : "+r"(d[0]), "+r"(d[1]), "+r"(d[2]), "+r"(d[3]), "+r"(d[4]), "+r"(d[5]), "+r"(d[6]), "+r"(d[7]), "+r"(d[8]), "+r"(d[9]), "+r"(d[10]), "+r"(d[11]), "+r"(d[12]), "+r"(d[13])
        : "l"(descA), "n"(AOFF >> 4), "l"(descB), "n"(BOFF >> 4));
}

template <int AOFF, int BOFF>
__device__ __forceinline__ void mma_s1_f32(float (&d)[28], uint64_t descA, uint64_t descB) {
    asm volatile(
        "{\n"
        ".reg .pred p0, p1;\n"
        ".reg .b64 ta, ta0, tb, tb0;\n"
        "setp.ne.b32 p0, 0, 0;\n"
        "setp.eq.b32 p1, 0, 0;\n"
        "add.s64 tb0, %30, %31;\n"
        "add.s64 ta0, %28, %29;\n"
        "add.s64 tb, tb0, 6;\n"
        "add.s64 ta, ta0, 2;\n"
        "wgmma.mma_async.sync.aligned.m64n56k16.f32.f16.f16 {%0, %1, %2, %3, %4, %5, %6, %7, %8, %9, %10, %11, %12, %13, %14, %15, %16, %17, %18, %19, %20, %21, %22, %23, %24, %25, %26, %27}, ta, tb, p1, 1, 1, 0, 0;\n"
        "add.s64 tb, tb0, 1574;\n"
        "add.s64 ta, ta0, 1570;\n"
        "wgmma.mma_async.sync.aligned.m64n56k16.f32.f16.f16 {%0, %1, %2, %3, %4, %5, %6, %7, %8, %9, %10, %11, %12, %13, %14, %15, %16, %17, %18, %19, %20, %21, %22, %23, %24, %25, %26, %27}, ta, tb, p1, 1, 1, 0, 0;\n"
        "add.s64 tb, tb0, 3142;\n"
        "add.s64 ta, ta0, 3138;\n"
        "wgmma.mma_async.sync.aligned.m64n56k16.f32.f16.f16 {%0, %1, %2, %3, %4, %5, %6, %7, %8, %9, %10, %11, %12, %13, %14, %15, %16, %17, %18, %19, %20, %21, %22, %23, %24, %25, %26, %27}, ta, tb, p1, 1, 1, 0, 0;\n"
        "}\n"
        : "+f"(d[0]), "+f"(d[1]), "+f"(d[2]), "+f"(d[3]), "+f"(d[4]), "+f"(d[5]), "+f"(d[6]), "+f"(d[7]), "+f"(d[8]), "+f"(d[9]), "+f"(d[10]), "+f"(d[11]), "+f"(d[12]), "+f"(d[13]), "+f"(d[14]), "+f"(d[15]), "+f"(d[16]), "+f"(d[17]), "+f"(d[18]), "+f"(d[19]), "+f"(d[20]), "+f"(d[21]), "+f"(d[22]), "+f"(d[23]), "+f"(d[24]), "+f"(d[25]), "+f"(d[26]), "+f"(d[27])
        : "l"(descA), "n"(AOFF >> 4), "l"(descB), "n"(BOFF >> 4));
}

template <int AOFF, int BOFF>
__device__ __forceinline__ void mma_s1_f16(uint32_t (&d)[14], uint64_t descA, uint64_t descB) {
    asm volatile(
        "{\n"
        ".reg .pred p0, p1;\n"
        ".reg .b64 ta, ta0, tb, tb0;\n"
        "setp.ne.b32 p0, 0, 0;\n"
        "setp.eq.b32 p1, 0, 0;\n"
        "add.s64 tb0, %16, %17;\n"
        "add.s64 ta0, %14, %15;\n"
        "add.s64 tb, tb0, 6;\n"
        "add.s64 ta, ta0, 2;\n"
        "wgmma.mma_async.sync.aligned.m64n56k16.f16.f16.f16 {%0, %1, %2, %3, %4, %5, %6, %7, %8, %9, %10, %11, %12, %13}, ta, tb, p1, 1, 1, 0, 0;\n"
        "add.s64 tb, tb0, 1574;\n"
        "add.s64 ta, ta0, 1570;\n"
        "wgmma.mma_async.sync.aligned.m64n56k16.f16.f16.f16 {%0, %1, %2, %3, %4, %5, %6, %7, %8, %9, %10, %11, %12, %13}, ta, tb, p1, 1, 1, 0, 0;\n"
        "add.s64 tb, tb0, 3142;\n"
        "add.s64 ta, ta0, 3138;\n"
        "wgmma.mma_async.sync.aligned.m64n56k16.f16.f16.f16 {%0, %1, %2, %3, %4, %5, %6, %7, %8, %9, %10, %11, %12, %13}, ta, tb, p1, 1, 1, 0, 0;\n"
        "}\n"
        : "+r"(d[0]), "+r"(d[1]), "+r"(d[2]), "+r"(d[3]), "+r"(d[4]), "+r"(d[5]), "+r"(d[6]), "+r"(d[7]), "+r"(d[8]), "+r"(d[9]), "+r"(d[10]), "+r"(d[11]), "+r"(d[12]), "+r"(d[13])
        : "l"(descA), "n"(AOFF >> 4), "l"(descB), "n"(BOFF >> 4));
}

template <int BOFF, int AOFF, int NA>
__device__ __forceinline__ void mma_pv(uint32_t (&d)[14], const uint32_t (&a)[NA][4], uint64_t descB) {
    asm volatile(
        "{\n"
        ".reg .pred p0, p1;\n"
        ".reg .b64 ta, ta0, tb, tb0;\n"
        "setp.ne.b32 p0, 0, 0;\n"
        "setp.eq.b32 p1, 0, 0;\n"
        "add.s64 tb0, %30, %31;\n"
        "add.s64 tb, tb0, 0;\n"
        "wgmma.mma_async.sync.aligned.m64n56k16.f16.f16.f16 {%0, %1, %2, %3, %4, %5, %6, %7, %8, %9, %10, %11, %12, %13}, {%14, %15, %16, %17}, tb, p0, 1, 1, 1;\n"
        "add.s64 tb, tb0, 16;\n"
        "wgmma.mma_async.sync.aligned.m64n56k16.f16.f16.f16 {%0, %1, %2, %3, %4, %5, %6, %7, %8, %9, %10, %11, %12, %13}, {%18, %19, %20, %21}, tb, p1, 1, 1, 1;\n"
        "add.s64 tb, tb0, 32;\n"
        "wgmma.mma_async.sync.aligned.m64n56k16.f16.f16.f16 {%0, %1, %2, %3, %4, %5, %6, %7, %8, %9, %10, %11, %12, %13}, {%22, %23, %24, %25}, tb, p1, 1, 1, 1;\n"
        "add.s64 tb, tb0, 48;\n"
        "wgmma.mma_async.sync.aligned.m64n56k16.f16.f16.f16 {%0, %1, %2, %3, %4, %5, %6, %7, %8, %9, %10, %11, %12, %13}, {%26, %27, %28, %29}, tb, p1, 1, 1, 1;\n"
        "}\n"
        : "=r"(d[0]), "=r"(d[1]), "=r"(d[2]), "=r"(d[3]), "=r"(d[4]), "=r"(d[5]), "=r"(d[6]), "=r"(d[7]), "=r"(d[8]), "=r"(d[9]), "=r"(d[10]), "=r"(d[11]), "=r"(d[12]), "=r"(d[13])
        : "r"(a[AOFF + 0][0]), "r"(a[AOFF + 0][1]), "r"(a[AOFF + 0][2]), "r"(a[AOFF + 0][3]), "r"(a[AOFF + 1][0]), "r"(a[AOFF + 1][1]), "r"(a[AOFF + 1][2]), "r"(a[AOFF + 1][3]), "r"(a[AOFF + 2][0]), "r"(a[AOFF + 2][1]), "r"(a[AOFF + 2][2]), "r"(a[AOFF + 2][3]), "r"(a[AOFF + 3][0]), "r"(a[AOFF + 3][1]), "r"(a[AOFF + 3][2]), "r"(a[AOFF + 3][3]), "l"(descB), "n"(BOFF >> 4));
}

template <int BOFF, int AOFF, int NA>
__device__ __forceinline__ void mma_pv3(uint32_t (&d)[14], const uint32_t (&a)[NA][4], uint64_t descB) {
    asm volatile(
        "{\n"
        ".reg .pred p0, p1;\n"
        ".reg .b64 ta, ta0, tb, tb0;\n"
        "setp.ne.b32 p0, 0, 0;\n"
        "setp.eq.b32 p1, 0, 0;\n"
        "add.s64 tb0, %26, %27;\n"
        "add.s64 tb, tb0, 0;\n"
        "wgmma.mma_async.sync.aligned.m64n56k16.f16.f16.f16 {%0, %1, %2, %3, %4, %5, %6, %7, %8, %9, %10, %11, %12, %13}, {%14, %15, %16, %17}, tb, p1, 1, 1, 1;\n"
        "add.s64 tb, tb0, 16;\n"
        "wgmma.mma_async.sync.aligned.m64n56k16.f16.f16.f16 {%0, %1, %2, %3, %4, %5, %6, %7, %8, %9, %10, %11, %12, %13}, {%18, %19, %20, %21}, tb, p1, 1, 1, 1;\n"
        "add.s64 tb, tb0, 32;\n"
        "wgmma.mma_async.sync.aligned.m64n56k16.f16.f16.f16 {%0, %1, %2, %3, %4, %5, %6, %7, %8, %9, %10, %11, %12, %13}, {%22, %23, %24, %25}, tb, p1, 1, 1, 1;\n"
        "}\n"
        : "+r"(d[0]), "+r"(d[1]), "+r"(d[2]), "+r"(d[3]), "+r"(d[4]), "+r"(d[5]), "+r"(d[6]), "+r"(d[7]), "+r"(d[8]), "+r"(d[9]), "+r"(d[10]), "+r"(d[11]), "+r"(d[12]), "+r"(d[13])
        : "r"(a[AOFF + 0][0]), "r"(a[AOFF + 0][1]), "r"(a[AOFF + 0][2]), "r"(a[AOFF + 0][3]), "r"(a[AOFF + 1][0]), "r"(a[AOFF + 1][1]), "r"(a[AOFF + 1][2]), "r"(a[AOFF + 1][3]), "r"(a[AOFF + 2][0]), "r"(a[AOFF + 2][1]), "r"(a[AOFF + 2][2]), "r"(a[AOFF + 2][3]), "l"(descB), "n"(BOFF >> 4));
}

template <int AOFF, int BOFF>
__device__ __forceinline__ void mma_proj(float (&d)[96], uint64_t descA, uint64_t descB) {
    asm volatile(
        "{\n"
        ".reg .pred p0, p1;\n"
        ".reg .b64 ta, ta0, tb, tb0;\n"
        "setp.ne.b32 p0, 0, 0;\n"
        "setp.eq.b32 p1, 0, 0;\n"
        "add.s64 tb0, %98, %99;\n"
        "add.s64 ta0, %96, %97;\n"
        "add.s64 tb, tb0, 0;\n"
        "add.s64 ta, ta0, 0;\n"
        "wgmma.mma_async.sync.aligned.m64n192k16.f32.f16.f16 {%0, %1, %2, %3, %4, %5, %6, %7, %8, %9, %10, %11, %12, %13, %14, %15, %16, %17, %18, %19, %20, %21, %22, %23, %24, %25, %26, %27, %28, %29, %30, %31, %32, %33, %34, %35, %36, %37, %38, %39, %40, %41, %42, %43, %44, %45, %46, %47, %48, %49, %50, %51, %52, %53, %54, %55, %56, %57, %58, %59, %60, %61, %62, %63, %64, %65, %66, %67, %68, %69, %70, %71, %72, %73, %74, %75, %76, %77, %78, %79, %80, %81, %82, %83, %84, %85, %86, %87, %88, %89, %90, %91, %92, %93, %94, %95}, ta, tb, p0, 1, 1, 0, 1;\n"
        "add.s64 tb, tb0, 64;\n"
        "add.s64 ta, ta0, 2;\n"
        "wgmma.mma_async.sync.aligned.m64n192k16.f32.f16.f16 {%0, %1, %2, %3, %4, %5, %6, %7, %8, %9, %10, %11, %12, %13, %14, %15, %16, %17, %18, %19, %20, %21, %22, %23, %24, %25, %26, %27, %28, %29, %30, %31, %32, %33, %34, %35, %36, %37, %38, %39, %40, %41, %42, %43, %44, %45, %46, %47, %48, %49, %50, %51, %52, %53, %54, %55, %56, %57, %58, %59, %60, %61, %62, %63, %64, %65, %66, %67, %68, %69, %70, %71, %72, %73, %74, %75, %76, %77, %78, %79, %80, %81, %82, %83, %84, %85, %86, %87, %88, %89, %90, %91, %92, %93, %94, %95}, ta, tb, p1, 1, 1, 0, 1;\n"
        "add.s64 tb, tb0, 128;\n"
        "add.s64 ta, ta0, 4;\n"
        "wgmma.mma_async.sync.aligned.m64n192k16.f32.f16.f16 {%0, %1, %2, %3, %4, %5, %6, %7, %8, %9, %10, %11, %12, %13, %14, %15, %16, %17, %18, %19, %20, %21, %22, %23, %24, %25, %26, %27, %28, %29, %30, %31, %32, %33, %34, %35, %36, %37, %38, %39, %40, %41, %42, %43, %44, %45, %46, %47, %48, %49, %50, %51, %52, %53, %54, %55, %56, %57, %58, %59, %60, %61, %62, %63, %64, %65, %66, %67, %68, %69, %70, %71, %72, %73, %74, %75, %76, %77, %78, %79, %80, %81, %82, %83, %84, %85, %86, %87, %88, %89, %90, %91, %92, %93, %94, %95}, ta, tb, p1, 1, 1, 0, 1;\n"
        "add.s64 tb, tb0, 192;\n"
        "add.s64 ta, ta0, 6;\n"
        "wgmma.mma_async.sync.aligned.m64n192k16.f32.f16.f16 {%0, %1, %2, %3, %4, %5, %6, %7, %8, %9, %10, %11, %12, %13, %14, %15, %16, %17, %18, %19, %20, %21, %22, %23, %24, %25, %26, %27, %28, %29, %30, %31, %32, %33, %34, %35, %36, %37, %38, %39, %40, %41, %42, %43, %44, %45, %46, %47, %48, %49, %50, %51, %52, %53, %54, %55, %56, %57, %58, %59, %60, %61, %62, %63, %64, %65, %66, %67, %68, %69, %70, %71, %72, %73, %74, %75, %76, %77, %78, %79, %80, %81, %82, %83, %84, %85, %86, %87, %88, %89, %90, %91, %92, %93, %94, %95}, ta, tb, p1, 1, 1, 0, 1;\n"
        "add.s64 tb, tb0, 256;\n"
        "add.s64 ta, ta0, 512;\n"
        "wgmma.mma_async.sync.aligned.m64n192k16.f32.f16.f16 {%0, %1, %2, %3, %4, %5, %6, %7, %8, %9, %10, %11, %12, %13, %14, %15, %16, %17, %18, %19, %20, %21, %22, %23, %24, %25, %26, %27, %28, %29, %30, %31, %32, %33, %34, %35, %36, %37, %38, %39, %40, %41, %42, %43, %44, %45, %46, %47, %48, %49, %50, %51, %52, %53, %54, %55, %56, %57, %58, %59, %60, %61, %62, %63, %64, %65, %66, %67, %68, %69, %70, %71, %72, %73, %74, %75, %76, %77, %78, %79, %80, %81, %82, %83, %84, %85, %86, %87, %88, %89, %90, %91, %92, %93, %94, %95}, ta, tb, p1, 1, 1, 0, 1;\n"
        "add.s64 tb, tb0, 320;\n"
        "add.s64 ta, ta0, 514;\n"
        "wgmma.mma_async.sync.aligned.m64n192k16.f32.f16.f16 {%0, %1, %2, %3, %4, %5, %6, %7, %8, %9, %10, %11, %12, %13, %14, %15, %16, %17, %18, %19, %20, %21, %22, %23, %24, %25, %26, %27, %28, %29, %30, %31, %32, %33, %34, %35, %36, %37, %38, %39, %40, %41, %42, %43, %44, %45, %46, %47, %48, %49, %50, %51, %52, %53, %54, %55, %56, %57, %58, %59, %60, %61, %62, %63, %64, %65, %66, %67, %68, %69, %70, %71, %72, %73, %74, %75, %76, %77, %78, %79, %80, %81, %82, %83, %84, %85, %86, %87, %88, %89, %90, %91, %92, %93, %94, %95}, ta, tb, p1, 1, 1, 0, 1;\n"
        "add.s64 tb, tb0, 384;\n"
        "add.s64 ta, ta0, 516;\n"
        "wgmma.mma_async.sync.aligned.m64n192k16.f32.f16.f16 {%0, %1, %2, %3, %4, %5, %6, %7, %8, %9, %10, %11, %12, %13, %14, %15, %16, %17, %18, %19, %20, %21, %22, %23, %24, %25, %26, %27, %28, %29, %30, %31, %32, %33, %34, %35, %36, %37, %38, %39, %40, %41, %42, %43, %44, %45, %46, %47, %48, %49, %50, %51, %52, %53, %54, %55, %56, %57, %58, %59, %60, %61, %62, %63, %64, %65, %66, %67, %68, %69, %70, %71, %72, %73, %74, %75, %76, %77, %78, %79, %80, %81, %82, %83, %84, %85, %86, %87, %88, %89, %90, %91, %92, %93, %94, %95}, ta, tb, p1, 1, 1, 0, 1;\n"
        "add.s64 tb, tb0, 448;\n"
        "add.s64 ta, ta0, 518;\n"
        "wgmma.mma_async.sync.aligned.m64n192k16.f32.f16.f16 {%0, %1, %2, %3, %4, %5, %6, %7, %8, %9, %10, %11, %12, %13, %14, %15, %16, %17, %18, %19, %20, %21, %22, %23, %24, %25, %26, %27, %28, %29, %30, %31, %32, %33, %34, %35, %36, %37, %38, %39, %40, %41, %42, %43, %44, %45, %46, %47, %48, %49, %50, %51, %52, %53, %54, %55, %56, %57, %58, %59, %60, %61, %62, %63, %64, %65, %66, %67, %68, %69, %70, %71, %72, %73, %74, %75, %76, %77, %78, %79, %80, %81, %82, %83, %84, %85, %86, %87, %88, %89, %90, %91, %92, %93, %94, %95}, ta, tb, p1, 1, 1, 0, 1;\n"
        "add.s64 tb, tb0, 512;\n"
        "add.s64 ta, ta0, 1024;\n"
        "wgmma.mma_async.sync.aligned.m64n192k16.f32.f16.f16 {%0, %1, %2, %3, %4, %5, %6, %7, %8, %9, %10, %11, %12, %13, %14, %15, %16, %17, %18, %19, %20, %21, %22, %23, %24, %25, %26, %27, %28, %29, %30, %31, %32, %33, %34, %35, %36, %37, %38, %39, %40, %41, %42, %43, %44, %45, %46, %47, %48, %49, %50, %51, %52, %53, %54, %55, %56, %57, %58, %59, %60, %61, %62, %63, %64, %65, %66, %67, %68, %69, %70, %71, %72, %73, %74, %75, %76, %77, %78, %79, %80, %81, %82, %83, %84, %85, %86, %87, %88, %89, %90, %91, %92, %93, %94, %95}, ta, tb, p1, 1, 1, 0, 1;\n"
        "add.s64 tb, tb0, 576;\n"
        "add.s64 ta, ta0, 1026;\n"
        "wgmma.mma_async.sync.aligned.m64n192k16.f32.f16.f16 {%0, %1, %2, %3, %4, %5, %6, %7, %8, %9, %10, %11, %12, %13, %14, %15, %16, %17, %18, %19, %20, %21, %22, %23, %24, %25, %26, %27, %28, %29, %30, %31, %32, %33, %34, %35, %36, %37, %38, %39, %40, %41, %42, %43, %44, %45, %46, %47, %48, %49, %50, %51, %52, %53, %54, %55, %56, %57, %58, %59, %60, %61, %62, %63, %64, %65, %66, %67, %68, %69, %70, %71, %72, %73, %74, %75, %76, %77, %78, %79, %80, %81, %82, %83, %84, %85, %86, %87, %88, %89, %90, %91, %92, %93, %94, %95}, ta, tb, p1, 1, 1, 0, 1;\n"
        "add.s64 tb, tb0, 640;\n"
        "add.s64 ta, ta0, 1028;\n"
        "wgmma.mma_async.sync.aligned.m64n192k16.f32.f16.f16 {%0, %1, %2, %3, %4, %5, %6, %7, %8, %9, %10, %11, %12, %13, %14, %15, %16, %17, %18, %19, %20, %21, %22, %23, %24, %25, %26, %27, %28, %29, %30, %31, %32, %33, %34, %35, %36, %37, %38, %39, %40, %41, %42, %43, %44, %45, %46, %47, %48, %49, %50, %51, %52, %53, %54, %55, %56, %57, %58, %59, %60, %61, %62, %63, %64, %65, %66, %67, %68, %69, %70, %71, %72, %73, %74, %75, %76, %77, %78, %79, %80, %81, %82, %83, %84, %85, %86, %87, %88, %89, %90, %91, %92, %93, %94, %95}, ta, tb, p1, 1, 1, 0, 1;\n"
        "add.s64 tb, tb0, 704;\n"
        "add.s64 ta, ta0, 1030;\n"
        "wgmma.mma_async.sync.aligned.m64n192k16.f32.f16.f16 {%0, %1, %2, %3, %4, %5, %6, %7, %8, %9, %10, %11, %12, %13, %14, %15, %16, %17, %18, %19, %20, %21, %22, %23, %24, %25, %26, %27, %28, %29, %30, %31, %32, %33, %34, %35, %36, %37, %38, %39, %40, %41, %42, %43, %44, %45, %46, %47, %48, %49, %50, %51, %52, %53, %54, %55, %56, %57, %58, %59, %60, %61, %62, %63, %64, %65, %66, %67, %68, %69, %70, %71, %72, %73, %74, %75, %76, %77, %78, %79, %80, %81, %82, %83, %84, %85, %86, %87, %88, %89, %90, %91, %92, %93, %94, %95}, ta, tb, p1, 1, 1, 0, 1;\n"
        "}\n"
        : "+f"(d[0]), "+f"(d[1]), "+f"(d[2]), "+f"(d[3]), "+f"(d[4]), "+f"(d[5]), "+f"(d[6]), "+f"(d[7]), "+f"(d[8]), "+f"(d[9]), "+f"(d[10]), "+f"(d[11]), "+f"(d[12]), "+f"(d[13]), "+f"(d[14]), "+f"(d[15]), "+f"(d[16]), "+f"(d[17]), "+f"(d[18]), "+f"(d[19]), "+f"(d[20]), "+f"(d[21]), "+f"(d[22]), "+f"(d[23]), "+f"(d[24]), "+f"(d[25]), "+f"(d[26]), "+f"(d[27]), "+f"(d[28]), "+f"(d[29]), "+f"(d[30]), "+f"(d[31]), "+f"(d[32]), "+f"(d[33]), "+f"(d[34]), "+f"(d[35]), "+f"(d[36]), "+f"(d[37]), "+f"(d[38]), "+f"(d[39]), "+f"(d[40]), "+f"(d[41]), "+f"(d[42]), "+f"(d[43]), "+f"(d[44]), "+f"(d[45]), "+f"(d[46]), "+f"(d[47]), "+f"(d[48]), "+f"(d[49]), "+f"(d[50]), "+f"(d[51]), "+f"(d[52]), "+f"(d[53]), "+f"(d[54]), "+f"(d[55]), "+f"(d[56]), "+f"(d[57]), "+f"(d[58]), "+f"(d[59]), "+f"(d[60]), "+f"(d[61]), "+f"(d[62]), "+f"(d[63]), "+f"(d[64]), "+f"(d[65]), "+f"(d[66]), "+f"(d[67]), "+f"(d[68]), "+f"(d[69]), "+f"(d[70]), "+f"(d[71]), "+f"(d[72]), "+f"(d[73]), "+f"(d[74]), "+f"(d[75]), "+f"(d[76]), "+f"(d[77]), "+f"(d[78]), "+f"(d[79]), "+f"(d[80]), "+f"(d[81]), "+f"(d[82]), "+f"(d[83]), "+f"(d[84]), "+f"(d[85]), "+f"(d[86]), "+f"(d[87]), "+f"(d[88]), "+f"(d[89]), "+f"(d[90]), "+f"(d[91]), "+f"(d[92]), "+f"(d[93]), "+f"(d[94]), "+f"(d[95])
        : "l"(descA), "n"(AOFF >> 4), "l"(descB), "n"(BOFF >> 4));
}

template <int AOFF, int BOFF>
__device__ __forceinline__ void mma_projh(uint32_t (&d)[48], uint64_t descA, uint64_t descB) {
    asm volatile(
        "{\n"
        ".reg .pred p0, p1;\n"
        ".reg .b64 ta, ta0, tb, tb0;\n"
        "setp.ne.b32 p0, 0, 0;\n"
        "setp.eq.b32 p1, 0, 0;\n"
        "add.s64 tb0, %50, %51;\n"
        "add.s64 ta0, %48, %49;\n"
        "add.s64 tb, tb0, 0;\n"
        "add.s64 ta, ta0, 0;\n"
        "wgmma.mma_async.sync.aligned.m64n192k16.f16.f16.f16 {%0, %1, %2, %3, %4, %5, %6, %7, %8, %9, %10, %11, %12, %13, %14, %15, %16, %17, %18, %19, %20, %21, %22, %23, %24, %25, %26, %27, %28, %29, %30, %31, %32, %33, %34, %35, %36, %37, %38, %39, %40, %41, %42, %43, %44, %45, %46, %47}, ta, tb, p0, 1, 1, 0, 1;\n"
        "add.s64 tb, tb0, 64;\n"
        "add.s64 ta, ta0, 2;\n"
        "wgmma.mma_async.sync.aligned.m64n192k16.f16.f16.f16 {%0, %1, %2, %3, %4, %5, %6, %7, %8, %9, %10, %11, %12, %13, %14, %15, %16, %17, %18, %19, %20, %21, %22, %23, %24, %25, %26, %27, %28, %29, %30, %31, %32, %33, %34, %35, %36, %37, %38, %39, %40, %41, %42, %43, %44, %45, %46, %47}, ta, tb, p1, 1, 1, 0, 1;\n"
        "add.s64 tb, tb0, 128;\n"
        "add.s64 ta, ta0, 4;\n"
        "wgmma.mma_async.sync.aligned.m64n192k16.f16.f16.f16 {%0, %1, %2, %3, %4, %5, %6, %7, %8, %9, %10, %11, %12, %13, %14, %15, %16, %17, %18, %19, %20, %21, %22, %23, %24, %25, %26, %27, %28, %29, %30, %31, %32, %33, %34, %35, %36, %37, %38, %39, %40, %41, %42, %43, %44, %45, %46, %47}, ta, tb, p1, 1, 1, 0, 1;\n"
        "add.s64 tb, tb0, 192;\n"
        "add.s64 ta, ta0, 6;\n"
        "wgmma.mma_async.sync.aligned.m64n192k16.f16.f16.f16 {%0, %1, %2, %3, %4, %5, %6, %7, %8, %9, %10, %11, %12, %13, %14, %15, %16, %17, %18, %19, %20, %21, %22, %23, %24, %25, %26, %27, %28, %29, %30, %31, %32, %33, %34, %35, %36, %37, %38, %39, %40, %41, %42, %43, %44, %45, %46, %47}, ta, tb, p1, 1, 1, 0, 1;\n"
        "add.s64 tb, tb0, 256;\n"
        "add.s64 ta, ta0, 512;\n"
        "wgmma.mma_async.sync.aligned.m64n192k16.f16.f16.f16 {%0, %1, %2, %3, %4, %5, %6, %7, %8, %9, %10, %11, %12, %13, %14, %15, %16, %17, %18, %19, %20, %21, %22, %23, %24, %25, %26, %27, %28, %29, %30, %31, %32, %33, %34, %35, %36, %37, %38, %39, %40, %41, %42, %43, %44, %45, %46, %47}, ta, tb, p1, 1, 1, 0, 1;\n"
        "add.s64 tb, tb0, 320;\n"
        "add.s64 ta, ta0, 514;\n"
        "wgmma.mma_async.sync.aligned.m64n192k16.f16.f16.f16 {%0, %1, %2, %3, %4, %5, %6, %7, %8, %9, %10, %11, %12, %13, %14, %15, %16, %17, %18, %19, %20, %21, %22, %23, %24, %25, %26, %27, %28, %29, %30, %31, %32, %33, %34, %35, %36, %37, %38, %39, %40, %41, %42, %43, %44, %45, %46, %47}, ta, tb, p1, 1, 1, 0, 1;\n"
        "add.s64 tb, tb0, 384;\n"
        "add.s64 ta, ta0, 516;\n"
        "wgmma.mma_async.sync.aligned.m64n192k16.f16.f16.f16 {%0, %1, %2, %3, %4, %5, %6, %7, %8, %9, %10, %11, %12, %13, %14, %15, %16, %17, %18, %19, %20, %21, %22, %23, %24, %25, %26, %27, %28, %29, %30, %31, %32, %33, %34, %35, %36, %37, %38, %39, %40, %41, %42, %43, %44, %45, %46, %47}, ta, tb, p1, 1, 1, 0, 1;\n"
        "add.s64 tb, tb0, 448;\n"
        "add.s64 ta, ta0, 518;\n"
        "wgmma.mma_async.sync.aligned.m64n192k16.f16.f16.f16 {%0, %1, %2, %3, %4, %5, %6, %7, %8, %9, %10, %11, %12, %13, %14, %15, %16, %17, %18, %19, %20, %21, %22, %23, %24, %25, %26, %27, %28, %29, %30, %31, %32, %33, %34, %35, %36, %37, %38, %39, %40, %41, %42, %43, %44, %45, %46, %47}, ta, tb, p1, 1, 1, 0, 1;\n"
        "add.s64 tb, tb0, 512;\n"
        "add.s64 ta, ta0, 1024;\n"
        "wgmma.mma_async.sync.aligned.m64n192k16.f16.f16.f16 {%0, %1, %2, %3, %4, %5, %6, %7, %8, %9, %10, %11, %12, %13, %14, %15, %16, %17, %18, %19, %20, %21, %22, %23, %24, %25, %26, %27, %28, %29, %30, %31, %32, %33, %34, %35, %36, %37, %38, %39, %40, %41, %42, %43, %44, %45, %46, %47}, ta, tb, p1, 1, 1, 0, 1;\n"
        "add.s64 tb, tb0, 576;\n"
        "add.s64 ta, ta0, 1026;\n"
        "wgmma.mma_async.sync.aligned.m64n192k16.f16.f16.f16 {%0, %1, %2, %3, %4, %5, %6, %7, %8, %9, %10, %11, %12, %13, %14, %15, %16, %17, %18, %19, %20, %21, %22, %23, %24, %25, %26, %27, %28, %29, %30, %31, %32, %33, %34, %35, %36, %37, %38, %39, %40, %41, %42, %43, %44, %45, %46, %47}, ta, tb, p1, 1, 1, 0, 1;\n"
        "add.s64 tb, tb0, 640;\n"
        "add.s64 ta, ta0, 1028;\n"
        "wgmma.mma_async.sync.aligned.m64n192k16.f16.f16.f16 {%0, %1, %2, %3, %4, %5, %6, %7, %8, %9, %10, %11, %12, %13, %14, %15, %16, %17, %18, %19, %20, %21, %22, %23, %24, %25, %26, %27, %28, %29, %30, %31, %32, %33, %34, %35, %36, %37, %38, %39, %40, %41, %42, %43, %44, %45, %46, %47}, ta, tb, p1, 1, 1, 0, 1;\n"
        "add.s64 tb, tb0, 704;\n"
        "add.s64 ta, ta0, 1030;\n"
        "wgmma.mma_async.sync.aligned.m64n192k16.f16.f16.f16 {%0, %1, %2, %3, %4, %5, %6, %7, %8, %9, %10, %11, %12, %13, %14, %15, %16, %17, %18, %19, %20, %21, %22, %23, %24, %25, %26, %27, %28, %29, %30, %31, %32, %33, %34, %35, %36, %37, %38, %39, %40, %41, %42, %43, %44, %45, %46, %47}, ta, tb, p1, 1, 1, 0, 1;\n"
        "}\n"
        : "=r"(d[0]), "=r"(d[1]), "=r"(d[2]), "=r"(d[3]), "=r"(d[4]), "=r"(d[5]), "=r"(d[6]), "=r"(d[7]), "=r"(d[8]), "=r"(d[9]), "=r"(d[10]), "=r"(d[11]), "=r"(d[12]), "=r"(d[13]), "=r"(d[14]), "=r"(d[15]), "=r"(d[16]), "=r"(d[17]), "=r"(d[18]), "=r"(d[19]), "=r"(d[20]), "=r"(d[21]), "=r"(d[22]), "=r"(d[23]), "=r"(d[24]), "=r"(d[25]), "=r"(d[26]), "=r"(d[27]), "=r"(d[28]), "=r"(d[29]), "=r"(d[30]), "=r"(d[31]), "=r"(d[32]), "=r"(d[33]), "=r"(d[34]), "=r"(d[35]), "=r"(d[36]), "=r"(d[37]), "=r"(d[38]), "=r"(d[39]), "=r"(d[40]), "=r"(d[41]), "=r"(d[42]), "=r"(d[43]), "=r"(d[44]), "=r"(d[45]), "=r"(d[46]), "=r"(d[47])
        : "l"(descA), "n"(AOFF >> 4), "l"(descB), "n"(BOFF >> 4));
}

struct Params {
    const __nv_bfloat16* x;
    const __nv_bfloat16* wqkv;
    const __nv_bfloat16* wo;
    const __nv_bfloat16* logit_scale;
    const __nv_bfloat16* cpb_w1;
    const __nv_bfloat16* cpb_w2;
    const __nv_bfloat16* rel_coords;
    const int*           rel_idx;
    const __nv_bfloat16* mask;
    __nv_bfloat16*       out;
    unsigned long long   z1;
    int                  npair;
    uint32_t             need;
    int                  spread;
    int                  t1;
};

constexpr uint32_t POS_END = 0x8000;
__device__ __forceinline__ uint32_t pos_add(uint32_t pos, int n) {
    pos += n;
    return (pos & 127) >= NWS ? pos + (128 - NWS) : pos;
}
__device__ __forceinline__ int role_of(const Params& P, int b) {
    const int n0 = ((b >> 1) * P.spread) >> 16, n1 = (((b >> 1) + 1) * P.spread) >> 16;
    return n1 != n0 ? 2 * P.npair + 2 * n0 + (b & 1) : b - 2 * n0;
}
__device__ __forceinline__ void finish(uint32_t total) {
    __threadfence();
    if (atomicAdd(&g_done, 1u) == total - 1) {
        for (int i = 0; i < NWS; i++) g_cnt[i] = 0;
        g_next[0] = 0; g_next[1] = 0;
        g_done = 0;
    }
}

constexpr int FB_PITCH = 584, FB_X = TOK * FB_PITCH * 2, FB_TAB = FB_X + TOK * 384, FB_BYTES = FB_TAB + 169 * 8 + 8;
static_assert(3 * FB_BYTES <= SM_PBAR && FB_BYTES % 16 == 0 && SM_BAR + B_ROWS == SM_PBAR + 64 && PCHUNK, "smem");
__device__ __forceinline__ void redo(const Params& P, uint8_t* sm, uint32_t tag, int barid) {
    typedef __nv_bfloat16 bf;
    const int t = threadIdx.x & 127, lane = t & 31;
    bf* const qkv = reinterpret_cast<bf*>(sm);
    bf* const xs = reinterpret_cast<bf*>(sm + FB_X);
    bf* const tab = reinterpret_cast<bf*>(sm + FB_TAB);
    volatile int* const next = reinterpret_cast<volatile int*>(sm + FB_TAB + 169 * 8);
#pragma unroll 1
    for (uint32_t n = 0; n < (1u << 22); n++) {
        uint32_t a;
        asm volatile("ld.acquire.gpu.global.u32 %0, [%1];\n" : "=r"(a) : "l"(g_guard) : "memory");
        if (a == tag + 1) break;
        __nanosleep(256);
    }
    asm volatile("fence.proxy.async;\n" ::: "memory");
#pragma unroll 1
    for (int i = t; i < 169 * 4; i += 128) {
        float a = 0.f;
#pragma unroll 1
        for (int u = 0; u < 16; u++) {
            const float h = round_bf16(__bfloat162float(P.rel_coords[(i >> 2) * 2]) * __bfloat162float(P.cpb_w1[u]) +
                                       __bfloat162float(P.rel_coords[(i >> 2) * 2 + 1]) * __bfloat162float(P.cpb_w1[16 + u]));
            a += (h > 0.f ? h : h * 0.f) * __bfloat162float(P.cpb_w2[u * 4 + (i & 3)]);
        }
        tab[i] = __float2bfloat16_rn(16.f * round_bf16(1.f / (1.f + expf(-round_bf16(a)))));
    }
#pragma unroll 1
    for (;;) {
        wg_bar(barid);
        if (t == 0) *next = (int)atomicAdd(g_guard + 2, 1u);
        wg_bar(barid);
        const int win = *next;
        if (win >= NWINDOWS) return;
        const int y0 = 7 * (win / NWS) + 3, x0 = 7 * (win % NWS) + 3;
        auto pixel = [&](int r) { return (size_t)(((y0 + r / 7) % IMG) * IMG + (x0 + r % 7) % IMG) * 192; };
#pragma unroll 1
        for (int i = t; i < TOK * 24; i += 128)
            reinterpret_cast<uint4*>(xs)[i] = reinterpret_cast<const uint4*>(P.x + pixel(i / 24))[i % 24];
#pragma unroll 1
        for (int ph = 0; ph < 2; ph++) {
            const bf* const a = ph ? qkv : xs;
            bf* const d = ph ? xs : qkv;
            const int n = ph ? 192 : 576, pa = ph ? FB_PITCH : 192, pd = ph ? 192 : FB_PITCH;
            wg_bar(barid);
#pragma unroll 1
            for (int col = t; col < n; col += 128) {
                const bf* w = (ph ? P.wo : P.wqkv) + col;
                float acc[TOK];
#pragma unroll
                for (int r = 0; r < TOK; r++) acc[r] = 0.f;
#pragma unroll 1
                for (int k = 0; k < 192; k += 2) {
                    const float w0 = __bfloat162float(w[k * n]), w1 = __bfloat162float(w[(k + 1) * n]);
#pragma unroll
                    for (int r = 0; r < TOK; r++) {
                        const uint32_t v = *reinterpret_cast<const uint32_t*>(a + r * pa + k);
                        acc[r] = fmaf(bf16hi(v), w1, fmaf(bf16lo(v), w0, acc[r]));
                    }
                }
#pragma unroll
                for (int r = 0; r < TOK; r++) d[r * pd + col] = __float2bfloat16_rn(acc[r]);
            }
            wg_bar(barid);
            if (ph) break;
#pragma unroll 1
            for (int i = t; i < TOK * 8; i += 128) {
                bf* const v = qkv + (i % TOK) * FB_PITCH + (i / TOK) * 48;
                float s = 0.f;
#pragma unroll 1
                for (int j = 0; j < 48; j++) s = fmaf(__bfloat162float(v[j]), __bfloat162float(v[j]), s);
                s = round_bf16(1.f / sqrtf(round_bf16(round_bf16(s) + 1e-12f)));
#pragma unroll 1
                for (int j = 0; j < 48; j++) v[j] = __float2bfloat16_rn(__bfloat162float(v[j]) * s);
            }
            wg_bar(barid);
#pragma unroll 1
            for (int i = t; i < TOK * 4; i += 128) {
                const int r = i % TOK, h = i / TOK;
                uint32_t* const q = reinterpret_cast<uint32_t*>(qkv + r * FB_PITCH + h * 48);
                const float tau = round_bf16(expf(round_bf16(fminf(fmaxf(__bfloat162float(P.logit_scale[h]), -100.f), 4.6052f))));
                float v[48], mx = -INFINITY, sum = 0.f;
#pragma unroll
                for (int j = 0; j < 24; j++) { v[2 * j] = bf16lo(q[j]); v[2 * j + 1] = bf16hi(q[j]); }
#pragma unroll 1
                for (int j = 0; j < TOK; j++) {
                    const uint32_t* kk = reinterpret_cast<const uint32_t*>(qkv + j * FB_PITCH + 192 + h * 48);
                    float s = 0.f;
#pragma unroll
                    for (int u = 0; u < 24; u++) s = fmaf(v[2 * u + 1], bf16hi(kk[u]), fmaf(v[2 * u], bf16lo(kk[u]), s));
                    s = round_bf16(round_bf16(s) * tau);
                    s = round_bf16(s + __bfloat162float(tab[min(max(P.rel_idx[r * TOK + j], 0), 168) * 4 + h]));
                    s = round_bf16(s + __bfloat162float(P.mask[(size_t)win * (TOK * TOK) + r * TOK + j]));
                    xs[j * 128 + t] = __float2bfloat16_rn(s);
                    mx = fmaxf(mx, s);
                }
#pragma unroll 1
                for (int j = 0; j < TOK; j++) sum += expf(__bfloat162float(xs[j * 128 + t]) - mx);
#pragma unroll
                for (int j = 0; j < 48; j++) v[j] = 0.f;
#pragma unroll 1
                for (int j = 0; j < TOK; j++) {
                    const uint32_t* vv = reinterpret_cast<const uint32_t*>(qkv + j * FB_PITCH + 384 + h * 48);
                    const float p = round_bf16(expf(__bfloat162float(xs[j * 128 + t]) - mx) / sum);
#pragma unroll
                    for (int u = 0; u < 24; u++) {
                        v[2 * u] = fmaf(p, bf16lo(vv[u]), v[2 * u]);
                        v[2 * u + 1] = fmaf(p, bf16hi(vv[u]), v[2 * u + 1]);
                    }
                }
#pragma unroll
                for (int j = 0; j < 24; j++) q[j] = pack_bf16(v[2 * j], v[2 * j + 1]);
            }
        }
#pragma unroll 1
        for (int r = t >> 5; r < TOK; r += 4) {
            float v[6], m = 0.f, s = 0.f;
#pragma unroll
            for (int j = 0; j < 6; j++) { v[j] = __bfloat162float(xs[r * 192 + j * 32 + lane]); m += v[j]; }
#pragma unroll
            for (int o = 16; o; o >>= 1) m += __shfl_xor_sync(0xffffffffu, m, o);
            m *= 1.f / 192.f;
#pragma unroll
            for (int j = 0; j < 6; j++) s = fmaf(v[j] - m, v[j] - m, s);
#pragma unroll
            for (int o = 16; o; o >>= 1) s += __shfl_xor_sync(0xffffffffu, s, o);
            s = round_bf16(sqrtf(round_bf16(round_bf16(s * (1.f / 192.f)) + 1e-5f)));
            m = round_bf16(m);
#pragma unroll
            for (int j = 0; j < 6; j++) P.out[pixel(r) + j * 32 + lane] = __float2bfloat16_rn(round_bf16(v[j] - m) / s);
        }
    }
}

__global__ void __launch_bounds__(NTHREADS, 1)
swin_window_attn_kernel(const Params P, const __grid_constant__ CUtensorMap xmap, const __grid_constant__ CUtensorMap xmap4,
                        const __grid_constant__ CUtensorMap xmap3,
                        const __grid_constant__ CUtensorMap omap, const __grid_constant__ CUtensorMap wmap,
                        const __grid_constant__ CUtensorMap smap, const __grid_constant__ CUtensorMap omapb,
                        const __grid_constant__ CUtensorMap xmapa, const __grid_constant__ CUtensorMap xmapb,
                        const __grid_constant__ CUtensorMap smap3, const __grid_constant__ CUtensorMap wraw,
                        const __grid_constant__ CUtensorMap smapw) {
    extern __shared__ __align__(1024) uint8_t smem[];
    constexpr uint32_t sbase = 1024;
    if (smem_u32(smem) != sbase) return;
    const int tid = threadIdx.x;
    const int wg = __shfl_sync(0xffffffffu, tid >> 7, 0);
    const int warp = __shfl_sync(0xffffffffu, (tid >> 5) & 3, 0);
    const int lane = tid & 31;
    const int g = lane >> 2, c = lane & 3;

    TR(26, wg);
    if (wg == 0) { ST(0); SC(27); }
    const int role = role_of(P, blockIdx.x);
    const bool attn = role < 2 * P.npair;
    const int pair = role >> 1, half = role & 1;
    const uint32_t bars = sbase + SM_BAR;
    const bool first = wg == 3 && warp == 3;
    if (first) {
        if (lane == 0) {
            mbar_init(bars + B_WRAW, 1);
            mbar_init(bars + B_WFULL, 1);
            mbar_init(bars + B_MFULL, 1);
            for (int b = 0; b < 4; b++) mbar_init(bars + B_XFULL + b * 8, 2);
            asm volatile("fence.mbarrier_init.release.cluster;\n" ::: "memory");
            fence_async_smem();
        }
        __syncwarp();
        asm volatile("bar.arrive 0, 512;\n" ::: "memory");
        if (attn && elect_one()) {
            mbar_arrive_expect_tx(bars + B_WRAW, 12 * W_ATOM);
            TR(26, 30);
            asm volatile("prefetch.tensormap [%0];\n" :: "l"(reinterpret_cast<uint64_t>(&wmap)) : "memory");
            asm volatile("prefetch.tensormap [%0];\n" :: "l"(reinterpret_cast<uint64_t>(XPF ? &wraw : &xmap)) : "memory");
            if (XPF == 1) {
                const uint32_t pos = half ? pos_add(pair, P.npair) : pair;
#pragma unroll
                for (int ch = 0; ch < 3; ch++)
                    asm volatile("cp.async.bulk.prefetch.tensor.3d.L2.global.tile [%0, {%1, %2, %3}];\n"
                                 :: "l"(reinterpret_cast<uint64_t>(&xmap)), "r"(ch * 64), "r"(7 * (pos & 127) + 3), "r"(7 * (pos >> 7) + 3)
                                 : "memory");
            }
            if (XPF == 2) {
                const uint32_t pos = half ? pos_add(pair, P.npair) : pair;
                const char* src = reinterpret_cast<const char*>(P.x) + ((7 * (pos >> 7) + 3) * IMG + 7 * (pos & 127) + 3) * 384;
#pragma unroll
                for (int r = 0; r < 7; r++)
                    asm volatile("cp.async.bulk.prefetch.L2.global [%0], 2688;\n" :: "l"(src + r * IMG * 384) : "memory");
                asm volatile("prefetch.tensormap [%0];\n" :: "l"(reinterpret_cast<uint64_t>(&xmap)) : "memory");
            }
#pragma unroll
            for (int i = 0; i < 2; i++) tma_2d(sbase + i * 6 * W_ATOM, &wraw, bars + B_WRAW, i * 192 + half * 128, 0);
            TR(26, 31);
#pragma unroll
            for (int i = 0; i < 2; i++) tma_2d(sbase + (i * 6 + 4) * W_ATOM, &wmap, bars + B_WRAW, i * 192 + 64 + half * 32, 0);
            TR(26, 33);
            int wh = 0, ww = pair;
#pragma unroll
            for (int j = 0; j < NEARLY; j++) {
                if (ww < NWS - 1) {
                    const uint32_t bar = bars + B_XFULL + (j ? j - 1 : 0) * 8;
                    if (j >= 2) mbar_arrive(bar);
                    mbar_arrive_expect_tx(bar, 3 * XCH);
#pragma unroll
                    for (int ch = 0; ch < 3; ch++)
                        tma_3d(sbase + SM_QK + ((j + 3) & 3) * XCH + ch * QK_CHUNK, &xmap, bar, ch * 64, 7 * ww + 3, 7 * wh + 3);
                }
                ww += P.npair; if (ww >= NWS) { ww -= NWS; wh++; }
                TR(26, 40 + j);
                if (j == 1) {
                    mbar_arrive_expect_tx(bars + B_WFULL, 6 * W_ATOM);
                    tma_2d(sbase + SM_WV, &wraw, bars + B_WFULL, 384 + half * 128, 0);
                    tma_2d(sbase + SM_WV + 4 * W_ATOM, &wmap, bars + B_WFULL, 384 + 64 + half * 32, 0);
                    mbar_arrive_expect_tx(bars + B_MFULL, 4816);
                    asm volatile("cp.async.bulk.shared::cluster.global.mbarrier::complete_tx::bytes [%0], [%1], 4816, [%2];\n"
                                 :: "r"(sbase + SM_MASK), "l"(reinterpret_cast<const char*>(P.mask) + (((uint32_t)pair * 4802u) & ~15u)),
                                    "r"(bars + B_MFULL) : "memory");
                    TR(26, 50);
                }
            }
        }
        __syncwarp();
    }
    const int t0 = min(warp * 16 + g, TOK - 1), t1 = min(warp * 16 + g + 8, TOK - 1);
    int ridx[26];
    uint32_t rc, w2[16];
    uint4 w1[4];
    if (attn && wg == 0) rc = reinterpret_cast<const uint32_t*>(P.logit_scale)[half];
    if (attn && (wg == 1 || wg == 2)) {
        rc = reinterpret_cast<const uint32_t*>(P.rel_coords)[min(tid - 128, 168)];
#pragma unroll
        for (int i = 0; i < 4; i++) w1[i] = reinterpret_cast<const uint4*>(P.cpb_w1)[i];
#pragma unroll
        for (int u = 0; u < 16; u++) w2[u] = reinterpret_cast<const uint32_t*>(P.cpb_w2)[2 * u + half];
#pragma unroll
        for (int rh = 0; rh < 2; rh++) {
            const int* ri = P.rel_idx + (rh ? t1 : t0) * TOK;
#pragma unroll
            for (int j = 0; j < 12; j++) ridx[13 * rh + j] = ri[8 * (j >> 1) + 2 * c + (j & 1)];
            ridx[13 * rh + 12] = ri[48];
        }
    }
    {
        if (tid == 416) {
            const CUtensorMap* maps[4] = {attn ? &smap : &omap, &smap3, &xmapa, &xmapb};
#pragma unroll
            for (int i = 0; i < 4; i++) asm volatile("prefetch.tensormap [%0];\n" :: "l"(reinterpret_cast<uint64_t>(maps[i])) : "memory");
        }
        if (tid == 384) {
            for (int b = 0; b < 4; b++) {
                mbar_init(bars + B_QKRAW + b * 8, 4);
                mbar_init(bars + B_VRAW + b * 8, 4);
                mbar_init(bars + B_VFREE + b * 8, 2);
                mbar_init(bars + B_QKFREE + b * 8, 4);
                mbar_init(bars + B_ODONE + b * 8, 4);
            }
            sts32(bars + B_MSTATE, 0);
            sts32(bars + B_MSTATE + 4, 0x7FFFFFFF);
            sts32(bars + B_NTILES, 0x7FFFFFFF);
            sts128(bars + B_DYN, ~0u, ~0u, ~0u, ~0u);
            sts128(bars + B_DYN + 16, ~0u, ~0u, ~0u, ~0u);
            mbar_init(bars + B_GDONE, 4);
            sts32(bars + B_ROWS, 0xFFFFFFFFu);
            if (WPOLL) sts32(bars + B_ROWS + 8, 0);
            mbar_init(bars + B_MCONS, 4);
            mbar_init(bars + B_XCONS, 4);
            for (int b = 0; b < 4; b++) mbar_init(bars + B_STORED + b * 8, 1);
            for (int b = 0; b < 6; b++) {
                mbar_init(sbase + SM_PBAR + b * 8, 1);
                if (PCHUNK) sts32(sbase + SM_PBAR + 48, 0); else
                mbar_init(sbase + SM_PBAR + 48 + b * 8, PSTORE ? 1 : 4);
                mbar_init(sbase + SM_PBAR + 104 + b * 8, 4);
            }
            mbar_init(sbase + SM_PBAR + 96, attn ? 13 : 12);
            if (MPRE && !attn) for (int b = 0; b < (MBG ? 32 : 12 * MBUFS); b++) mbar_init(sbase + SM_MBAR + b * 8, 1);
            mbar_init(sbase + SM_PBAR + 56, 12);
            asm volatile("fence.mbarrier_init.release.cluster;\n" ::: "memory");
        }
        if (wg == 3) {
            static_assert(4 * O_STRIDE == 3 * V_STRIDE + 13 * GRP, "layout");
            if (attn && lane < 16 && warp < 3)
                *reinterpret_cast<uint4*>(smem + SM_V + warp * V_STRIDE + 13 * GRP + lane * 16) = make_uint4(0, 0, 0, 0);
            fence_async_smem();
        }
        if (!first) asm volatile("bar.sync 0, 512;\n" ::: "memory");
        if (wg == 3 && warp == 0) asm volatile("bar.arrive 15, 64;\n" ::: "memory");
        if (first) asm volatile("bar.sync 15, 64;\n" ::: "memory");
        TR(26, 4 + wg);
        TR(26, 13);
    }

    auto raw_w = [&](int rg, int cc) {
        const uint32_t ca = cc - 4 * half, row = rg * 8 + (lane & 7);
        return ca < 8 ? row * 128 + ((ca ^ (lane & 7)) << 4) : 4 * W_ATOM + row * 64 + (((cc ^ (lane >> 1)) & 3) << 4);
    };
    auto permute_a = [&]() {
        uint2 w[9][4];
        uint32_t src[3][2], step[3][2];
        const int rg = ((tid >> 5) - 4) * 3;
#pragma unroll
        for (int i = 0; i < 6; i++) {
            const int cc = (i >> 1) * 2 + (i & 1) * 6;
            src[i >> 1][i & 1] = raw_w(rg, cc + (lane >> 4)) + (lane & 8);
            step[i >> 1][i & 1] = (uint32_t)(cc - 4 * half) < 8 ? 1024 : 512;
        }
        reg_fence(src);
        TR(26, 16 + wg);
        mbar_wait(bars + B_WRAW, 0);
        TR(26, 20 + wg);
#pragma unroll
        for (int i = 0; i < 9; i++)
#pragma unroll
            for (int m = 0; m < 4; m++)
                w[i][m] = *reinterpret_cast<const uint2*>(smem + (m >> 1) * 6 * W_ATOM + src[i % 3][m & 1] + (i / 3) * step[i % 3][m & 1]);
        asm volatile("bar.sync 2, 256;\n" ::: "memory");
        TR(26, 24 + wg);
        const uint32_t d = sbase + (lane >> 3) * W_ATOM + (rg * 8 + (lane & 7)) * 32 + ((lane >> 2) & 1) * 16;
#pragma unroll
        for (int i = 0; i < 9; i++) {
            sts128(d + (i % 3) * 4 * W_ATOM + (i / 3) * 256, bf2h(w[i][0].x), bf2h(w[i][1].x), bf2h(w[i][2].x), bf2h(w[i][3].x));
            sts128((d ^ 16) + (i % 3) * 4 * W_ATOM + (i / 3) * 256, bf2h(w[i][0].y), bf2h(w[i][1].y), bf2h(w[i][2].y), bf2h(w[i][3].y));
        }
    };
    auto permute_w = [&]() {
        uint4 w[3][4];
        uint32_t src[3][2];
#pragma unroll
        for (int it = 0; it < 3; it++) {
            const int o = ((tid >> 5) * 3 + it) * 4 + (lane >> 3);
            src[it][0] = raw_w(o / 6, o % 6);
            src[it][1] = raw_w(o / 6, o % 6 + 6);
        }
        reg_fence(src);
        TR(26, 16 + wg);
        mbar_wait(bars + B_WRAW, 0);
        TR(26, 20 + wg);
#pragma unroll
        for (int it = 0; it < 3; it++) {
#pragma unroll
            for (int m = 0; m < 4; m++)
                w[it][m] = *reinterpret_cast<const uint4*>(smem + (m >> 1) * 6 * W_ATOM + src[it][m & 1]);
        }
        asm volatile("bar.sync 2, 384;\n" ::: "memory");
        TR(26, 24 + wg);
#pragma unroll
        for (int it = 0; it < 3; it++) {
            const int o = ((tid >> 5) * 3 + it) * 4 + (lane >> 3);
            const uint32_t d = sbase + (o % 6) * 2 * W_ATOM + ((o / 6) * 8 + (lane & 7)) * 32 + ((lane >> 2) & 1) * 16;
            sts128(d, bf2h(w[it][0].x), bf2h(w[it][1].x), bf2h(w[it][2].x), bf2h(w[it][3].x));
            sts128(d ^ 16, bf2h(w[it][0].y), bf2h(w[it][1].y), bf2h(w[it][2].y), bf2h(w[it][3].y));
            sts128(d + W_ATOM, bf2h(w[it][0].z), bf2h(w[it][1].z), bf2h(w[it][2].z), bf2h(w[it][3].z));
            sts128((d ^ 16) + W_ATOM, bf2h(w[it][0].w), bf2h(w[it][1].w), bf2h(w[it][2].w), bf2h(w[it][3].w));
        }
    };
    const uint32_t nfinish = gridDim.x + (POLLER ? 0 : 2 * P.npair);
#define PROJ_SCHEDULE                                                                                   \
    int bid = blockIdx.x;                                                                               \
    asm volatile("" : "+r"(bid));                      \
    bid = role_of(P, bid);                                                                              \
    const bool at = bid < 2 * P.npair;                                                                  \
    const int tile0 = at ? P.t1 - NOLD + bid : NOLD + bid - 2 * P.npair;                                \
    const int told = at ? P.t1 - NOLD : 0;                                                              \
    const int tstep = at ? 2 * P.npair : (int)gridDim.x - 2 * P.npair;                                  \
    const int tend = at ? TILES : P.t1;
    if (wg == 3) {
        TR(26, 60 + warp);
        asm volatile("setmaxnreg.dec.sync.aligned.u32 %0;\n" :: "n"(REG_H));
        TR(26, 64 + warp);
#define MST_OFF 0
        if (warp == 1 && attn) {
            const uint16_t mlast = reinterpret_cast<const uint16_t*>(P.mask)[NWINDOWS * TOK * TOK - 1];
            const uint32_t ma = sbase + SM_MASK + 16 + lane * 16, mb = sbase + SM_MASK + min(289 + lane, 299) * 16;
            const uint32_t mc = sbase + SM_MASK + (lane & 7) * 2 + (lane & 8) * 600;
            uint32_t ph = 0, win = pair, fp = 0, nzl = 0;
#pragma unroll 1
            for (int k = 0;; k++) {
                mbar_wait(bars + B_MFULL, fp);
                uint32_t acc = lds16(mc);
                if ((lane & 15) - (win & 7) > 8u) acc = 0;
#pragma unroll
                for (int i = 0; i < 10; i += MRND) {
                    uint32_t w[MRND][4];
#pragma unroll
                    for (int j = 0; j < MRND; j++) if (i + j < 10) lds128(w[j], i + j < 9 ? ma + (i + j) * 512 : mb);
#pragma unroll
                    for (int j = 0; j < MRND; j++) if (i + j < 10) acc |= w[j][0] | w[j][1] | w[j][2] | w[j][3];
                    asm volatile("" : "+r"(acc) :: "memory");
                }
                uint32_t nz = __any_sync(0xffffffffu, (acc & 0x7FFF7FFFu) != 0) ? 1 : 0;
                if (lane == 0) asm volatile("st.volatile.shared.b32 [%0], %1;\n" :: "r"(MST_OFF ? sbase + SM_DUMP : bars + B_MSTATE), "r"(32 * k + 32 - 16 * nz + (2 * win & 14) + fp) : "memory");
                fp ^= 1;
                if (k + 1 == MPRE) {
                    uint32_t tag;
                    asm volatile("ld.relaxed.gpu.global.u32 %0, [%1];\n" : "=r"(tag) : "l"(g_guard) : "memory");
#pragma unroll 1
                    for (uint32_t n = 0; n < (1u << 20); n++) {
                        bool ok = true;
                        nzl = 0;
#pragma unroll
                        for (int j = 0; j < 3; j++) {
                            uint32_t f;
                            asm volatile("ld.relaxed.gpu.global.u32 %0, [%1];\n" : "=r"(f) : "l"(g_mz + pair * 128 + 32 * j + lane) : "memory");
                            ok = ok && ((f | 1) == (tag | 255) || 32 * j + lane < MPRE || 32 * j + lane >= MEND);
                            nzl |= (~f & 1) << j;
                        }
                        if (__all_sync(0xffffffffu, ok)) break;
                        nzl = 7;
                        __nanosleep(RSLEEP);
                    }
                }
                if (k + 1 >= MPRE && k + 1 < MEND) {
                    uint32_t kn = MEND;
#pragma unroll
                    for (int j = 0; j < 3; j++) if ((nzl >> j & 1) && 32 * j + lane > k) kn = min(kn, 32 * j + lane);
                    kn = __reduce_min_sync(0xffffffffu, kn);
                    if (kn > k + 1) {
                        if (nz) { mbar_wait(bars + B_MCONS, ph); ph ^= 1; fence_async_smem(); nz = 0; }
                        if (lane == 0) asm volatile("st.volatile.shared.b32 [%0], %1;\n" :: "r"(bars + B_MSTATE), "r"(32 * kn) : "memory");
                        k = kn - 1;
                        win = pair + k * P.npair;
                    }
                }
                win += P.npair;
                if (k + 1 >= NSTATIC) {
                    uint32_t e = 0xFFFF;
#pragma unroll 1
                    for (uint32_t n = 0; n < (1u << 20); n++) {
                        e = lds16v(bars + B_DYN + (k + 1 - NSTATIC) * 2);
                        if (__all_sync(0xffffffffu, e != 0xFFFF)) break;
                        __nanosleep(RSLEEP);
                    }
                    if (__any_sync(0xffffffffu, e >= POS_END)) break;
                    win = e - (e >> 7) * (128 - NWS);
                }
                if (nz && !MST_OFF) { mbar_wait(bars + B_MCONS, ph); ph ^= 1; fence_async_smem(); }
                if (elect_one()) {
                    uint32_t bytes = 4816;
                    if (win == NWINDOWS - 1) {
                        bytes = 4800;
                        asm volatile("st.shared.u16 [%0], %1;\n" :: "r"(sbase + SM_MASK + 4800), "h"(mlast) : "memory");
                    }
                    TR(25, k + 1);
                    mbar_arrive_expect_tx(bars + B_MFULL, bytes);
                    asm volatile("cp.async.bulk.shared::cluster.global.mbarrier::complete_tx::bytes [%0], [%1], %2, [%3];\n"
                                 :: "r"(sbase + SM_MASK),
                                    "l"(reinterpret_cast<const char*>(P.mask) + (((uint32_t)win * 4802u) & ~15u)),
                                    "r"(bytes), "r"(bars + B_MFULL) : "memory");
                    if (MPF && half == (win & 1) && win + MPF * P.npair < NWINDOWS && (!MPRE || k + 1 + MPF < MPRE || k + 1 >= MLIM))
                        asm volatile("cp.async.bulk.prefetch.L2.global [%0], %1;\n"
                                     :: "l"(reinterpret_cast<const char*>(P.mask) + (((uint32_t)(win + MPF * P.npair) * 4802u) & ~15u)),
                                        "r"(4800) : "memory");
                }
                __syncwarp();
            }
            {
                const int r0 = min(64 * P.t1 / (7 * IMG), NWS - 1);
                int ready = -1;
#pragma unroll 1
                for (uint32_t n = 0; n < (1u << 20); n++) {
                    const uint32_t over = mbar_test(sbase + SM_PBAR + 96, 0);
                    uint32_t a;
                    asm volatile("ld.relaxed.gpu.global.u32 %0, [%1];\n" : "=r"(a) : "l"(g_cnt + min(r0 + lane, NWS)) : "memory");
                    const int r = r0 - 2 + __ffs(__ballot_sync(0xffffffffu, a < P.need));
                    if (r > ready && r >= r0) {
                        ready = r;
                        asm volatile("fence.acquire.gpu;\n" ::: "memory");
                        asm volatile("fence.proxy.async.global;\n" ::: "memory");
                        __syncwarp();
                        if (lane == 0) asm volatile("st.volatile.shared.b32 [%0], %1;\n" :: "r"(bars + B_ROWS), "r"(r) : "memory");
                    }
                    if (__any_sync(0xffffffffu, over)) break;
                    __nanosleep(WPOLL * 100);
                }
                __syncwarp();
                if (lane == 0) asm volatile("st.volatile.shared.b32 [%0], %1;\n" :: "r"(bars + B_ROWS + 8), "r"(1) : "memory");
            }
        }
        if (!elect_one()) return;
        TR(26, 68 + warp);
        if (warp == 0) {
          if (attn) {
            int kmax = 1 << 20, rows = 1 << 30;
            uint32_t cur = pair, pos1 = pos_add(cur, P.npair), pos2 = pos_add(pos1, P.npair);
#pragma unroll 1
            for (int k = -4; k + 4 <= kmax; k++) {
                const int row0 = (k + 4) * TOK;
                const uint32_t dst = sbase + SM_QK + ((k + 3) & 3) * XCH, bar = bars + B_XFULL + ((row0 >> 6) & 3) * 8;
                const bool alone = (row0 & 63) >= 64 - TOK && (row0 & 63) < TOK;
                const int wh = cur >> 7, ww = cur & 127;
                uint32_t claim = NWINDOWS;
                if (k + 7 >= NSTATIC && k + 7 < NSTATIC + 15 && pos2 < POS_END)
                    asm volatile("atom.relaxed.gpu.global.add.u32 %0, [%1], 1;\n" : "=r"(claim) : "l"(g_next + half) : "memory");
                const int x0 = 7 * ww + 3, y0 = 7 * wh + 3;
                const bool done = k < NEARLY - 4 && ww < NWS - 1;
                if (k >= 0) mbar_wait(bars + B_QKFREE + ((k + 3) & 3) * 8, (k >> 2) & 1);
                if (alone && !done) mbar_arrive(bar);
                if (row0 >= rows || ((EXP & 32) && k >= 0)) {
                    mbar_arrive(bar);
                    continue;
                }
                TR(20, k + 4);
                const bool inner = wh < NWS - 1 && ww < NWS - 1;
                if (done) {
                } else if (XSPLIT && inner && (row0 & 63) >= 64 - 21) {
                    const uint32_t bar2 = bars + B_XFULL + (((row0 >> 6) + 1) & 3) * 8;
                    mbar_arrive_expect_tx(bar, 3 * 21 * 128);
#pragma unroll
                    for (int ch = 0; ch < 3; ch++) tma_3d(dst + ch * QK_CHUNK, &xmapa, bar, ch * 64, x0, y0);
                    asm volatile("mbarrier.expect_tx.relaxed.cta.shared::cta.b64 [%0], %1;\n" :: "r"(bar2), "r"(3 * 28 * 128) : "memory");
#pragma unroll
                    for (int ch = 0; ch < 3; ch++) tma_3d(dst + ch * QK_CHUNK + 21 * 128, &xmapb, bar2, ch * 64, x0, y0 + 3);
                } else if (inner) {
                    mbar_arrive_expect_tx(bar, 3 * XCH);
#pragma unroll
                    for (int ch = 0; ch < 3; ch++) tma_3d(dst + ch * QK_CHUNK, &xmap, bar, ch * 64, x0, y0);
                } else if (ww < NWS - 1) {
                    mbar_arrive_expect_tx(bar, 3 * XCH);
#pragma unroll
                    for (int ch = 0; ch < 3; ch++) {
                        tma_3d(dst + ch * QK_CHUNK, &xmapb, bar, ch * 64, x0, y0);
                        tma_3d(dst + ch * QK_CHUNK + 28 * 128, &xmapa, bar, ch * 64, x0, 0);
                    }
                } else {
                    mbar_arrive_expect_tx(bar, 3 * XCH);
                    const int x1 = (ww == NWS - 1) ? 0 : x0 + 4;
#pragma unroll 1
                    for (int i = 0; i < 7; i++) {
                        const int y = (y0 + i >= IMG) ? y0 + i - IMG : y0 + i;
#pragma unroll
                        for (int ch = 0; ch < 3; ch++) {
                            tma_3d(dst + ch * QK_CHUNK + i * 896, &xmap4, bar, ch * 64, x0, y);
                            tma_3d(dst + ch * QK_CHUNK + i * 896 + 512, &xmap3, bar, ch * 64, x1, y);
                        }
                    }
                }
                if (pos1 < POS_END) cur = pos1;
                pos1 = pos2;
                if (k + 7 < NSTATIC) {
                    pos2 = pos_add(pos2, P.npair);
                } else if (pos2 < POS_END) {
                    sts32(bars + B_NTILES + 4, claim);
                    const uint32_t w = lds32v(bars + B_NTILES + 4) + NSTATIC * P.npair;
                    pos2 = w < NWINDOWS ? w + __umulhi(w, 58835169u) * (128 - NWS) : POS_END;
                    sts16(bars + B_DYN + (k + 7 - NSTATIC) * 2, pos2);
                    if (pos2 == POS_END) {
                        rows = (row0 + 3 * TOK + 63) & ~63;
                        kmax = (rows + 63) / TOK;
                        sts32(bars + B_MSTATE + 4, k + 7);
                        sts32(bars + B_NTILES, rows >> 6);
                        if (role < SM_STAGE / 1024)
                            asm volatile("cp.async.bulk.prefetch.L2.global [%0], 1024;\n" :: "l"(g_wo + role * 1024) : "memory");
                    }
                }
                if (!NOPF && half == (PFALT ? (k & 1) : 0) && pos2 < POS_END) {
#pragma unroll
                    for (int ch = 0; ch < 3; ch++)
                        asm volatile("cp.async.bulk.prefetch.tensor.3d.L2.global.tile [%0, {%1, %2, %3}];\n"
                                     :: "l"(reinterpret_cast<uint64_t>(&xmap)), "r"(ch * 64), "r"(7 * (pos2 & 127) + 3), "r"(7 * (pos2 >> 7) + 3)
                                     : "memory");
                }
            }
            {
#pragma unroll 1
                for (uint32_t n = 0; n < (1u << 22); n++) {
                    uint32_t a, b;
                    asm volatile("ld.relaxed.gpu.global.u32 %0, [%1];\n" : "=r"(b) : "l"(g_guard) : "memory");
                    asm volatile("ld.acquire.gpu.global.u32 %0, [%1];\n" : "=r"(a) : "l"(g_guard + 3) : "memory");
                    if (a == (b | 255)) break;
                }
                asm volatile("fence.proxy.async.global;\n" ::: "memory");
                mbar_arrive_expect_tx(bars + B_WRAW, SM_STAGE);
                mbar_wait(bars + B_GDONE, 0);
#pragma unroll
                for (int i = 0; i < WOSPLIT; i++)
                    asm volatile("cp.async.bulk.shared::cluster.global.mbarrier::complete_tx::bytes [%0], [%1], %2, [%3];\n"
                                 :: "r"(sbase + SM_WO + i * (SM_STAGE / WOSPLIT)), "l"(g_wo + i * (SM_STAGE / WOSPLIT)),
                                    "n"(SM_STAGE / WOSPLIT), "r"(bars + B_WRAW) : "memory");
            }
          }
            mbar_wait(sbase + SM_PBAR + 96, 0);
            ST(15);
            if (EDELAY && attn) {
                const uint32_t c0 = clock();
#pragma unroll 1
                while ((uint32_t)clock() - c0 < EDELAY) {}
            }
            fence_async_smem();
            PROJ_SCHEDULE
            int st = 0, ready = -1, want = -6 * PSM, freed = 0;
            uint32_t ph = 1;
#pragma unroll 1
            for (int u = tile0; u < tend; u += tstep) {
                const int t = (NOLD && u < P.t1) ? u - told : u;
                const int p0 = (t < TILES_A) ? SEG_B + 64 * (t & PWRAP) : 64 * (t - TILES_A);
                const int w1 = (t < TILES_A) ? min((64 * t + 63) / (7 * IMG), NWS - 1) : NWS - 1;
#pragma unroll 1
                for (uint32_t n = 0; n < (1u << 24) && ready < w1; n++) ready = (int)lds32v(bars + B_ROWS);
#pragma unroll
                for (int ch = 0; ch < PSM; ch++) {
                    want++;
#pragma unroll 1
                    for (uint32_t n = 0; n < (1u << 22) && freed < want; n++) freed = (int)lds32v(sbase + SM_PBAR + 48);
                    if (ch == 0) mbar_arrive_expect_tx(sbase + SM_PBAR + st * 8, STAGE_BYTES);
                    tma_2d(sbase + SM_STAGE + st * STAGE_BYTES + ch * 8192, &omap, sbase + SM_PBAR + st * 8, ch * 64, p0);
                    if (ch == 0) {
#pragma unroll
                        for (int c2 = PSM; c2 < 3; c2++)
                            tma_2d(sbase + SM_STAGE + st * STAGE_BYTES + c2 * 8192, &omap, sbase + SM_PBAR + st * 8, c2 * 64, p0);
                    }
                }
                if (++st == 6) st = 0;
            }
            if (!POLLER) finish(nfinish);
        } else if (warp == 2 && (POLLER || attn)) {
            CK(0);
            uint32_t rows = 0, cur = attn ? pair : POS_END;
#pragma unroll 1
            for (int k = 0; cur < POS_END; k++) {
                const uint32_t wh = cur >> 7;
                mbar_wait(bars + B_STORED + (k & 1) * 8, (k >> 1) & 1);
                mbar_arrive(bars + B_PUBD + (k & 1) * 8);
                rows = rows * 128 + wh + 1;
                cur = k + 1 < NSTATIC ? pos_add(cur, P.npair) : lds16v(bars + B_DYN + (k + 1 - NSTATIC) * 2);
                if (rows >= (1u << (7 * PUBN - 7)) || k < 2 || cur >= (NWS - PUBT) * 128) {
                    asm volatile("fence.release.gpu;\n" ::: "memory");
#pragma unroll 1
                    for (; rows; rows >>= 7)
                        asm volatile("red.relaxed.gpu.global.add.u32 [%0], 1;\n" :: "l"(g_cnt + ((rows & 127) - 1)) : "memory");
                }
                TR(24, k);
                CK(k + 1);
                if (k == 30) { ST(9); SC(29); }
                if (k == 60) { ST(10); SC(30); }
                if (k == 90) { ST(11); SC(31); }
            }
            ST(14);
            const int r1 = attn ? NWS - 1 : min((64 * P.t1 - 1) / (7 * IMG), NWS - 1);
            if (NOLD && attn) {
#pragma unroll 1
                for (uint32_t n = 0; n < (1u << 24) && (int)lds32v(bars + B_ROWS) < 0; n++) {}
            }
            int rs = attn ? min(64 * P.t1 / (7 * IMG), NWS - 1) : 64 * NOLD / (7 * IMG);
            if (WPOLL && attn) {
#pragma unroll 1
                for (uint32_t n = 0; n < (1u << 24) && lds32v(bars + B_ROWS + 8) == 0; n++) {}
                rs = max(rs, (int)lds32v(bars + B_ROWS) + 1);
            }
#pragma unroll 1
            for (int r = rs; r <= r1; r++) {
#pragma unroll 1
                for (uint32_t n = 0; n < (1u << 22); n++) {
                    uint32_t a;
                    asm volatile("ld.relaxed.gpu.global.u32 %0, [%1];\n" : "=r"(a) : "l"(g_cnt + r) : "memory");
                    if (a >= P.need) break;
                    __nanosleep(64);
                }
                asm volatile("fence.acquire.gpu;\n" ::: "memory");
                asm volatile("fence.proxy.async.global;\n" ::: "memory");
                asm volatile("st.volatile.shared.b32 [%0], %1;\n" :: "r"(bars + B_ROWS), "r"(r) : "memory");
                if (r >= 66) ST(20 + r - 66);
            }
            finish(nfinish);
        } else if (warp == 3 && attn) {
            for (int t = 0; t < 3; t++) mbar_arrive_n(bars + B_VFREE + t * 8, 2);
            uint32_t cur = pair;
#pragma unroll 1
            for (int k = 0; cur < POS_END; k++) {
                const int wh = cur >> 7, ww = cur & 127;
                const uint32_t src = sbase + SM_V + (k & 3) * O_STRIDE;
                const int x0 = 7 * ww + 3, y0 = 7 * wh + 3;
                mbar_wait(bars + B_ODONE + (k & 3) * 8, (k >> 2) & 1);
                if (!(WFEN & 2)) fence_async_smem();
                TR(22, k);
                if (ww == NWS - 1) {
#pragma unroll 1
                    for (int i = 0; i < 7; i++)
                        tma_store_4d(&smapw, src + ((7 * i + 4) & ~1) * 192, 0, 3 * half, ~i & 1, y0 + i >= IMG ? y0 + i - IMG : y0 + i);
                    asm volatile("cp.async.bulk.commit_group;\n" ::: "memory");
                    asm volatile("cp.async.bulk.wait_group 0;\n" ::: "memory");
                }
                tma_store_4d(&smap, src, 0, 3 * half, x0, y0);
                if (wh == NWS - 1) tma_store_4d(&smap3, src + 28 * 192, 0, 3 * half, x0, 0);
                asm volatile("cp.async.bulk.commit_group;\n" ::: "memory");
                asm volatile("cp.async.bulk.wait_group.read 0;\n" ::: "memory");
                {
                    const int row0 = (k + 4) * TOK;
                    mbar_arrive_n(bars + B_VFREE + ((row0 >> 6) & 3) * 8, ((row0 & 63) >= 64 - TOK && (row0 & 63) < TOK) ? 2 : 1);
                }
                TR(23, k);
                cur = k + 1 < NSTATIC ? pos_add(cur, P.npair) : lds16v(bars + B_DYN + (k + 1 - NSTATIC) * 2);
                asm volatile("cp.async.bulk.wait_group 0;\n" ::: "memory");
                asm volatile("fence.proxy.async.global;\n" ::: "memory");
                mbar_wait(bars + B_PUBD + (k & 1) * 8, ((k >> 1) + 1) & 1);
                mbar_arrive(bars + B_STORED + (k & 1) * 8);
            }
            mbar_arrive(sbase + SM_PBAR + 96);
        }
        if (PSTORE && warp == 1) {
            PROJ_SCHEDULE
            int st = 0, prev = -1, done = 0;
            uint32_t ph = 0;
            if (bid == gridDim.x - 1) { g_guard[2] = 0; __threadfence(); }
#pragma unroll 1
            for (int u = tile0; u < tend; u += tstep) {
                const int t = (NOLD && u < P.t1) ? u - told : u;
                const int p0 = (t < TILES_A) ? SEG_B + 64 * (t & PWRAP) : 64 * (t - TILES_A);
                mbar_wait(sbase + SM_PBAR + 104 + st * 8, ph);
                if (!(WFEN & 1)) fence_async_smem();
                if (!at) TR(22, (t - tile0) / tstep);
                if (!at && done == 40 * PSM) ST(9);
                if (!at && done == 90 * PSM) ST(10);
                if (!at && done == 130 * PSM) ST(11);
                if (!at && done == 140 * PSM) ST(12);
#pragma unroll
                for (int ch = 0; ch < PSM; ch++) {
                    asm volatile("cp.async.bulk.tensor.2d.global.shared::cta.tile.bulk_group.L2::cache_hint [%0, {%2, %3}], [%1], %4;\n"
                                 :: "l"(reinterpret_cast<uint64_t>(t < TILES_A ? &omap : &omapb)),
                                    "r"(sbase + SM_STAGE + st * STAGE_BYTES + ch * 8192), "r"(ch * 64), "r"(p0), "l"(EVICT_FIRST) : "memory");
                    asm volatile("cp.async.bulk.commit_group;\n" ::: "memory");
                    asm volatile("cp.async.bulk.wait_group.read %0;\n" :: "n"(PCHUNK) : "memory");
                    asm volatile("st.volatile.shared.b32 [%0], %1;\n" :: "r"(sbase + SM_PBAR + 48), "r"(max(done + ch + 1 - PCHUNK, 0)) : "memory");
                }
                done += PSM;
                if (!mbar_test(sbase + SM_PBAR + 104 + (st == 5 ? 0 : st + 1) * 8, st == 5 ? ph ^ 1 : ph)) {
                    if (PCHUNK > 1) {
                        asm volatile("cp.async.bulk.wait_group.read 1;\n" ::: "memory");
                        asm volatile("st.volatile.shared.b32 [%0], %1;\n" :: "r"(sbase + SM_PBAR + 48), "r"(done - 1) : "memory");
                    }
                    asm volatile("cp.async.bulk.wait_group.read 0;\n" ::: "memory");
                    asm volatile("st.volatile.shared.b32 [%0], %1;\n" :: "r"(sbase + SM_PBAR + 48), "r"(done) : "memory");
                }
                prev = st;
                if (++st == 6) { st = 0; ph ^= 1; }
            }
            mbar_wait(sbase + SM_PBAR + 56, 0);
            asm volatile("fence.release.gpu;\n" ::: "memory");
            asm volatile("cp.async.bulk.wait_group 0;\n" ::: "memory");
            asm volatile("red.relaxed.gpu.global.add.u32 [%0], %1;\n" :: "l"(g_guard), "r"(bid == 0 ? 257 - gridDim.x : 1) : "memory");
            TR(30, 0);
            ST(13);
        }
        return;
    }
    bool bad = false;
    if (!attn) {
        asm volatile("setmaxnreg.inc.sync.aligned.u32 160;\n");
        uint32_t lo = 0x7F807F80u, hi = 0;
#pragma unroll 1
        for (int i = (role - 2 * P.npair) * 384 + tid; i < 192 * 96; i += (gridDim.x - 2 * P.npair) * 384) {
            const bool o = i >= 192 * 72;
            const uint4 w = o ? reinterpret_cast<const uint4*>(P.wo)[i - 192 * 72] : reinterpret_cast<const uint4*>(P.wqkv)[i];
            const uint32_t m = __vmaxu2(__vmaxu2(w.x & 0x7FFF7FFFu, w.y & 0x7FFF7FFFu), __vmaxu2(w.z & 0x7FFF7FFFu, w.w & 0x7FFF7FFFu));
            lo = __vminu2(lo, m);
            hi = __vmaxu2(hi, m + (o ? 0x02000200u : 0u));
        }
        bad = __vminu2(lo, 0x38803880u) != 0x38803880u || __vmaxu2(hi, 0x42004200u) != 0x42004200u;
    } else if (wg == 0) {
        float qs = 1.f;
        if (c < 2) qs = round_bf16(expf(round_bf16(fminf(fmaxf(c ? bf16hi(rc) : bf16lo(rc), -100.f), 4.6052f)))) * LOG2E;
        asm volatile("" : "+f"(qs) :: "memory");
        if (GLATE == 1) permute_w();
        TR(26, 28);
        asm volatile("setmaxnreg.inc.sync.aligned.u32 %0;\n" :: "n"(REG_G));
        TR(26, 29);
        uint32_t xa[8][4];
        uint32_t qk[2][48], vv[24];
        uint32_t rho = warp * 16 + (lane & 15), rq = warp * 16 + g;
        uint32_t rx = rho + 3 * TOK - (rho >= TOK ? 4 * TOK : 0);
        uint32_t hi = lane >> 4, lane0 = lane == 0, c2 = 2 * c;
        asm volatile("" : "+r"(hi), "+r"(lane0), "+r"(c2));
        auto row_addr = [&](uint32_t (&ax)[4], uint32_t r) {
            ax[0] = sbase + SM_QK + r * 128 + (((r & 7) ^ hi) << 4);
#pragma unroll
            for (int i = 1; i < 4; i++) ax[i] = ax[0] ^ (32 * i);
        };
#define XADDR(ax, s) ((ax)[((s) & 3) ^ (((s) >> 1) & 2)] + ((s) >> 2) * QK_CHUNK)
        uint64_t descW = make_desc(sbase, W_ATOM, 256, 3);
        const uint32_t zero = (uint32_t)P.z1;
        const uint32_t vbase = sbase + SM_V + (lane >> 4) * GRP;
        uint32_t ones = 0x3C003C00u | zero, ones2 = ones | (zero >> 1);
        asm volatile("" : "+r"(ones), "+r"(ones2));
        const uint32_t mh[2] = {0xFFFF0000u, 0xFFFF0000u}, ml[2] = {0x10000u, 0x10000u};
        uint32_t raw[48], xb[4][4];
        auto cvt = [&](auto& dst, int d0, const uint32_t (&raw)[48], int s0) {
#pragma unroll
            for (int s = 0; s < 4; s++) {
#pragma unroll
                for (int i = 0; i < 4; i++)
                    dst[d0 + s][i] = pack_f16(__uint_as_float(raw[4 * (s0 + s) + i] * ml[i & 1]), __uint_as_float(raw[4 * (s0 + s) + i] & mh[i & 1]));
                reg_fence(dst[d0 + s]);
            }
        };
        uint32_t ax[4];
        auto load_x = [&](int s0) {
#pragma unroll
            for (int s = s0; s < s0 + 4; s++) ldsm_x4(reinterpret_cast<uint32_t (&)[4]>(raw[4 * s]), XADDR(ax, s));
        };
        auto next_x = [&]() {
            row_addr(ax, rx);
            rx += 64;
            if (rx >= 4 * TOK) rx -= 4 * TOK;
        };
        if (!GLATE) permute_w();
        TR(26, 10);
        mbar_wait(bars + B_XFULL, 0);
        next_x();
        load_x(0); load_x(4); load_x(8);
        cvt(xa, 0, raw, 0); cvt(xa, 4, raw, 4); cvt(xb, 0, raw, 8);
        __syncwarp();
        mbar_arrive_if(bars + B_QKFREE + 24, lane0);
        TR(26, 8);
        asm volatile("bar.sync 7, 384;\n" ::: "memory");
        fence_async_smem();
        TR(26, 9);
        wgmma_fence();
        mma_qk_first<SM_WA, 0>(qk[0], xa, descW);
        mma_qk_next<SM_WA + 2048, 4>(qk[0], xa, descW);
        mma_qk_next<SM_WA + 4096, 0>(qk[0], xb, descW);
        wgmma_commit();
        TR(26, 11);
        asm volatile("bar.sync 11, 384;\n" ::: "memory");
        fence_async_smem();
        TR(26, 12);
        wgmma_fence();
        mma_v_first<SM_WV, 0>(vv, xa, descW);
        mma_v_next<SM_WV + 2048, 4>(vv, xa, descW);
        wgmma_commit();
        wgmma_wait<0>();
        ST(1); SC(28);
        uint32_t xok = 0, range = 0;
        int ntiles;
        auto body = [&](auto U_, int t) {
            constexpr int U = decltype(U_)::value;
            uint32_t (&cur)[48] = qk[U];
            uint32_t (&nxt)[48] = qk[U ^ 1];
            descW += P.z1;
            const uint32_t bt = bars + (t & 3) * 8, pt = (t >> 2) & 1;
            TR(1, t);
            wgmma_fence();
            mma_v_next<SM_WV + 4096, 0>(vv, xb, descW);
            wgmma_commit();
            next_x();
            mbar_wait_unless(xok, bars + ((t + 1) & 3) * 8 + B_XFULL, ((t + 1) >> 2) & 1);
            TR(2, t);
            load_x(0);
            load_x(4);
            uint32_t av = vbase + rho * 16 + ((rho * 1338) >> 16) * (V_STRIDE - GRP);
            uint32_t aq[2];
            aq[0] = sbase + SM_QK + rq * 128 + (((rq & 7) ^ c2) << 4);
            aq[1] = aq[0] + 1024;
            if (rq >= 4 * TOK - 8) aq[1] = (aq[1] - QK_CHUNK) ^ 64;
            rho += 64;
            if (rho >= 4 * TOK) rho -= 4 * TOK;
            rq += 64;
            if (rq >= 4 * TOK) rq -= 4 * TOK;
            asm volatile("" : "+r"(av), "+r"(aq[0]), "+r"(aq[1]), "+r"(rho), "+r"(rq));
            cvt(xa, 0, raw, 0);
            wgmma_fence();
            mma_qk_first<SM_WA, 0>(nxt, xa, descW);
            wgmma_commit();
            load_x(8);
            __syncwarp();
            mbar_arrive_if(bars + B_XCONS, lane0);
            const uint32_t vok = mbar_test(bt + B_VFREE, pt);
            ntiles = lds32v(bars + B_NTILES);
            cvt(xa, 4, raw, 4);
            TR(5, t);
            wgmma_fence();
            mma_qk_next<SM_WA + 2048, 4>(nxt, xa, descW);
            wgmma_commit();
            wgmma_wait<2>();
            reg_fence(cur);
            reg_fence(vv);
            TR(6, t);
            mbar_wait_unless(vok, bt + B_VFREE, pt);
            if (U == 0 && t == 2) asm volatile("bar.sync 3, 384;\n" ::: "memory");
#pragma unroll
            for (int p = 0; p < 6; p++)
                stsm_x4(av + (p < 3 ? 2 * p : 2 * p + 1) * GRP, vv[4 * p], vv[4 * p + 1], vv[4 * p + 2], vv[4 * p + 3]);
            stsm_x2(av + 6 * GRP, ones, ones2);
            __syncwarp();
            mbar_arrive_if(bt + B_VRAW, lane0);
            const uint32_t cok = mbar_test(bars + B_XCONS, U);
            TR(4, t);
            cvt(xb, 0, raw, 8);
            uint32_t ss[4];
#pragma unroll
            for (int i = 0; i < 4; i++) ss[i] = hmul2_f16(cur[i], cur[i]);
#pragma unroll
            for (int i = 4; i < ((EXP & 16) ? 4 : 48); i++) ss[i & 3] = hfma2_f16(cur[i], cur[i], ss[i & 3]);
            ss[0] = hadd2_f16(ss[0], ss[2]);
            ss[1] = hadd2_f16(ss[1], ss[3]);
            const float s0 = f16lo(ss[0]) + f16hi(ss[0]) + 1e-12f, s1 = f16lo(ss[1]) + f16hi(ss[1]) + 1e-12f;
            range = __viaddmax_u32(__float_as_uint(s0), 0u - SS_MIN, __viaddmax_u32(__float_as_uint(s1), 0u - SS_MIN, range));
            const float f0 = rsqrt_ftz(s0) * qs, f1 = rsqrt_ftz(s1) * qs;
            uint32_t f2[2] = {pack_f16_sat(f0, f0), pack_f16_sat(f1, f1)};
            reg_fence(f2);
            sched_fence16(zero, xb, f2[0], f2[1]);
            wgmma_fence();
            mma_v_first<SM_WV, 0>(vv, xa, descW);
            wgmma_commit();
            mbar_wait_unless_dep(cok, bars + B_XCONS, U, zero, f2[0], f2[1], aq[0], aq[1]);
            TR(7, t);
#pragma unroll
            for (int u = 0; u < 6; u++)
#pragma unroll
                for (int r = 0; r < 2; r++)
                    sts128((aq[r] ^ ((u & 1) * 16 + (u & 2) * 32)) + (u >> 1) * QK_CHUNK,
                           hmul2_f16(cur[8 * u + r], f2[r]), hmul2_f16(cur[8 * u + 2 + r], f2[r]),
                           hmul2_f16(cur[8 * u + 4 + r], f2[r]), hmul2_f16(cur[8 * u + 6 + r], f2[r]));
            __syncwarp();
            mbar_arrive_if(bt + B_QKRAW, lane0);
            TR(3, t);
            wgmma_fence();
            mma_v_next<SM_WV + 2048, 4>(vv, xa, descW);
            wgmma_commit();
            xok = mbar_test(bars + ((t + 2) & 3) * 8 + B_XFULL, ((t + 2) >> 2) & 1);
            mma_qk_next<SM_WA + 4096, 0>(nxt, xb, descW);
            wgmma_commit();
            TR(0, t + 1);
            wgmma_wait<GORD == 4 ? 2 : 1>();
        };
        for (int t = 0;; t += 2) {
            body(std::integral_constant<int, 0>(), t);
            if (__any_sync(0xffffffffu, t + 1 >= ntiles)) { wgmma_wait<0>(); reg_fence(qk[1]); break; }
            body(std::integral_constant<int, 1>(), t + 1);
            if (__any_sync(0xffffffffu, t + 2 >= ntiles)) { wgmma_wait<0>(); reg_fence(qk[0]); break; }
        }
        reg_fence(vv);
        bad = range >= F32_INF - SS_MIN;
        __syncwarp();
        mbar_arrive_if(bars + B_GDONE, lane0);
        asm volatile("setmaxnreg.dec.sync.aligned.u32 160;\n");
    } else {
        if (REG_A > 128) asm volatile("setmaxnreg.inc.sync.aligned.u32 %0;\n" :: "n"(REG_A));
        if (REG_A < 128) asm volatile("setmaxnreg.dec.sync.aligned.u32 %0;\n" :: "n"(REG_A));
        {
            const float c0 = bf16lo(rc), c1 = bf16hi(rc);
            float a0 = 0.f, a1 = 0.f;
#pragma unroll
            for (int u = 0; u < 16; u++) {
                const uint32_t p = reinterpret_cast<const uint32_t*>(w1)[u >> 1], q = reinterpret_cast<const uint32_t*>(w1)[8 + (u >> 1)];
                float h = round_bf16(c0 * ((u & 1) ? bf16hi(p) : bf16lo(p)) + c1 * ((u & 1) ? bf16hi(q) : bf16lo(q)));
                h = fmaxf(h, 0.f);
                a0 += h * bf16lo(w2[u]);
                a1 += h * bf16hi(w2[u]);
            }
            const float s0 = round_bf16(__fdividef(1.f, 1.f + expf(-round_bf16(a0))));
            const float s1 = round_bf16(__fdividef(1.f, 1.f + expf(-round_bf16(a1))));
            if (tid - 128 < 169) sts32(sbase + SM_TAB + (tid - 128) * 4, pack_f16(16.f * LOG2E * s0, 16.f * LOG2E * s1));
        }
        if (GLATE == 2) permute_a(); else permute_w();
        asm volatile("bar.arrive 7, 384;\n" ::: "memory");
        TR(26, 72 + wg);
        {
            uint4 w[9];
            const int rg = ((tid >> 5) - 4) * 3;
            mbar_wait(bars + B_WFULL, 0);
#pragma unroll
            for (int i = 0; i < 9; i++) w[i] = *reinterpret_cast<const uint4*>(smem + SM_WV + raw_w(rg + i / 3, (i % 3) * 4 + (lane >> 3)));
            asm volatile("bar.sync 1, 256;\n" ::: "memory");
            const uint32_t d = sbase + SM_WV + (lane >> 4) * W_ATOM + (rg * 8 + (lane & 7)) * 32 + (((lane >> 2) ^ (lane >> 3)) & 1) * 16;
#pragma unroll
            for (int i = 0; i < 9; i++)
                sts128(d + (i % 3) * 2 * W_ATOM + (i / 3) * 256, bf2h(w[i].x), bf2h(w[i].y), bf2h(w[i].z), bf2h(w[i].w));
            asm volatile("bar.arrive 11, 384;\n" ::: "memory");
            TR(26, 76 + wg);
        }
        uint32_t bias[28];
        {
            const uint32_t* tab = reinterpret_cast<const uint32_t*>(smem + SM_TAB);
#pragma unroll
            for (int rh = 0; rh < 2; rh++) {
#pragma unroll
                for (int j = 0; j < 6; j++) {
                    const uint32_t lo = tab[min(max(ridx[13 * rh + 2 * j], 0), 168)];
                    const uint32_t hi = tab[min(max(ridx[13 * rh + 2 * j + 1], 0), 168)];
                    bias[2 * j + rh]      = prmt(lo, hi, 0x5410);
                    bias[14 + 2 * j + rh] = prmt(lo, hi, 0x7632);
                }
                const uint32_t l = (c == 0) ? tab[min(max(ridx[13 * rh + 12], 0), 168)] : 0xFC00FC00u;
                bias[12 + rh] = (l & 0xFFFFu) | 0xFC000000u;
                bias[26 + rh] = (l >> 16) | 0xFC000000u;
            }
        }
#pragma unroll
        for (int i = 0; i < 28; i++)
            if (warp * 16 + g + (i & 1) * 8 >= TOK && i % 14 < 12) bias[i] = 0xFC00FC00u;
        reg_fence(bias);
        asm volatile("bar.arrive 3, 384;\n" ::: "memory");
        uint32_t os[3];
#pragma unroll
        for (int p = 0; p < 3; p++) {
            const int orow = warp * 16 + (lane & 7);
            uint32_t a = orow * 192 + p * 64;
            a += (((lane >> 3) ^ (a >> 7)) & 3) << 4;
            os[p] = sbase + SM_V + (wg - 1) * O_STRIDE + (orow < TOK ? a : 74 * 128 + (a & 127));
        }
        reg_fence(os);
        const int orow = warp * 16 + (lane & 7);
        const bool ov = orow < TOK;
        const uint32_t orel = sbase + (ov ? SM_V + orow * O_PITCH + (OONE == 2 && orow >= 28 ? 64 : 0) : SM_DUMP + ((lane + (OONE == 2 ? 7 : 3)) & 7) * 16) + (lane >> 3) * 16;
        const uint32_t oup = (OONE == 2 && warp == 1) ? (lane & 4) * 16 : 0;
        const uint32_t omul = ov ? O_STRIDE : 0;
        const uint64_t descK0 = make_desc(sbase + SM_QK, 16, 1024, 1);
        const uint64_t descV0 = make_desc(sbase + SM_V, 128, GRP, 0);
        const uint32_t mrel = sbase + SM_MASK + t0 * 98 + c * 4;
        const uint32_t mrow = (warp < 3) ? 784 : 0;
        const uint32_t pmask = (c == 0) ? 0xFFFFu : 0u;

        uint32_t mstate = 0;
        int nwin;
        const uint32_t barw = bars + (wg - 1) * 8;
        const uint64_t descKw = descK0 + (uint64_t)((wg - 1) * (XCH >> 4)), descVw = descV0 + (uint64_t)((wg - 1) * (V_STRIDE >> 4));
        uint32_t oa = orel + (wg - 1) * omul;
        const uint32_t oflip = oa ^ (oa + 2 * omul);
        uint32_t qok = 0;
        const uint32_t zero = (uint32_t)P.z1;
        auto window = [&](auto IT_, int k) {
            constexpr int IT = decltype(IT_)::value;
            const uint32_t bar = barw + 16 * IT;
            const int tl = (k * TOK + TOK - 1) >> 6, tn = ((k + 2) * TOK + TOK - 1) >> 6;
            const uint32_t bt = bars + (tl & 3) * 8, pt = (tl >> 2) & 1;
            TR(8, k);
            uint32_t sc0[14], sc1[14];
#pragma unroll
            for (int i = 0; i < 14; i++) { sc0[i] = bias[i]; sc1[i] = bias[14 + i]; }
            if (mstate < 32 * k + 32) {
#pragma unroll 1
                for (uint32_t n = 0; n < (1u << 22) && mstate < 32 * k + 16; n++) mstate = lds32v(bars + B_MSTATE);
                if (mstate < 32 * k + 32) {
                    mbar_wait(bars + B_MFULL, mstate & 1);
                    const uint32_t ma = mrel + (mstate & 14);
#pragma unroll
                    for (int i = 0; i < 14; i++) {
                        const uint32_t lo = lds16(ma + (i & 1) * mrow + (i >> 1) * 16);
                        const uint32_t hi = i < 12 ? lds16(ma + (i & 1) * mrow + (i >> 1) * 16 + 2) : 0u;
                        const uint32_t mk = pack_f16(__uint_as_float(lo << 16), __uint_as_float(hi << 16));
                        sc0[i] = hfma2_f16(mk, 0x3DC53DC5u, sc0[i]);
                        sc1[i] = hfma2_f16(mk, 0x3DC53DC5u, sc1[i]);
                    }
                    __syncwarp();
                    if (lane == 0) mbar_arrive(bars + B_MCONS);
                }
            }
            reg_fence(sc0);
            reg_fence(sc1);
            TR(10, k);
            mbar_wait_unless(qok, bt + B_QKRAW, pt);
            fence_async_smem();
            TR(11, k);
            wgmma_fence();
#if !(EXP & 128)
            mma_s0_f16<2 * IT * XCH, 2 * IT * XCH>(sc0, descKw, descKw);
            mma_s1_f16<2 * IT * XCH, 2 * IT * XCH>(sc1, descKw, descKw);
#endif
            wgmma_commit();
            const uint32_t vok = mbar_test(bt + B_VRAW, pt);
            uint32_t m[2];
            auto rowmax = [&](const uint32_t (&S)[14], int h) {
                uint32_t a[2];
#pragma unroll
                for (int o = 0; o < 2; o++)
                    a[o] = hmax2_f16(hmax2_f16(hmax2_f16(hmax2_f16(S[o], S[2 + o]), S[4 + o]), hmax2_f16(hmax2_f16(S[6 + o], S[8 + o]), S[10 + o])), S[12 + o]);
                m[h] = hmax2_f16(prmt(a[0], a[1], 0x5410), prmt(a[0], a[1], 0x7632));
            };
            wgmma_wait<0>();
            reg_fence(sc0);
            reg_fence(sc1);
            if (lane == 0) mbar_arrive(bar + B_QKFREE);
            TR(12, k);
            rowmax(sc0, 0);
            rowmax(sc1, 1);
#pragma unroll
            for (int i = 0; i < 2; i++) m[i] = hmax2_f16(m[i], __shfl_xor_sync(0xffffffffu, m[i], 1));
#pragma unroll
            for (int i = 0; i < 2; i++) m[i] = hmax2_f16(m[i], __shfl_xor_sync(0xffffffffu, m[i], 2));
            auto probs = [&](const uint32_t (&S)[14], uint32_t mm, uint32_t (&pa)[4][4]) {
#pragma unroll
                for (int j = 0; j < 6; j++) {
                    pa[j >> 1][(j & 1) * 2]     = ex2_f16x2(hsub2_bc<0>(S[2 * j], mm));
                    pa[j >> 1][(j & 1) * 2 + 1] = ex2_f16x2(hsub2_bc<1>(S[2 * j + 1], mm));
                }
                pa[3][0] = ex2_f16lo(hsub2_bc<0>(S[12], mm)) & pmask;
                pa[3][1] = ex2_f16lo(hsub2_bc<1>(S[13], mm)) & pmask;
                pa[3][2] = 0u; pa[3][3] = 0u;
                reg_fence(pa);
            };
            uint32_t pa0[4][4], pa1[4][4];
            uint32_t o0[14], o1[14];
            TR(13, k);
            mbar_wait_unless(vok, bt + B_VRAW, pt);
            fence_async_smem();
            TR(14, k);
            probs(sc0, m[0], pa0);
            wgmma_fence();
            mma_pv<2 * IT * V_STRIDE, 0>(o0, pa0, descVw);
            wgmma_commit();
            probs(sc1, m[1], pa1);
            wgmma_fence();
            mma_pv<2 * IT * V_STRIDE + 6 * GRP, 0>(o1, pa1, descVw);
            wgmma_commit();
            uint32_t w[24];
            wgmma_wait<1>();
            reg_fence(o0);
            {
                const float il0 = rcp_ftz(f16lo(o0[12])), il1 = rcp_ftz(f16lo(o0[13]));
                const uint32_t l0 = pack_f16(il0, il0), l1 = pack_f16(il1, il1);
#pragma unroll
                for (int j = 0; j < 12; j++) w[j] = hmul2_f16(o0[j], (j & 1) ? l1 : l0) & ~(OMASK * 0x10001u);
            }
            wgmma_wait<0>();
            reg_fence(o1);
            TR(15, k);
            asm volatile("{\n.reg .pred p;\nsetp.eq.u32 p, %0, 1;\n@p bar.sync 4, 128;\n@!p bar.sync 5, 128;\n}\n"
                         :: "r"(wg) : "memory");
            qok = mbar_test(bars + (tn & 3) * 8 + B_QKRAW, (tn >> 2) & 1);
            asm volatile("ld.volatile.shared.v2.b32 {%0, %1}, [%2];\n" : "=r"(mstate), "=r"(nwin) : "r"(bars + B_MSTATE) : "memory");
            {
                const float il2 = rcp_ftz(f16lo(o1[0])), il3 = rcp_ftz(f16lo(o1[1]));
                const uint32_t l2 = pack_f16(il2, il2), l3 = pack_f16(il3, il3);
#pragma unroll
                for (int j = 0; j < 12; j++) w[12 + j] = hmul2_f16(o1[j + 2], (j & 1) ? l3 : l2) & ~(OMASK * 0x10001u);
#pragma unroll
                for (int p = 0; p < 3; p++) stsm_x4(os[p] + 2 * IT * O_STRIDE, w[8 * p], w[8 * p + 2], w[8 * p + 4], w[8 * p + 6]);
#pragma unroll
                for (int p = 0; p < 3; p++) stsm_x4_if(warp < 3, os[p] + 2 * IT * O_STRIDE + 8 * 192, w[8 * p + 1], w[8 * p + 3], w[8 * p + 5], w[8 * p + 7]);
            }
            if (WFEN & 2) fence_async_smem();
            __syncwarp();
            if (lane == 0) mbar_arrive(bar + B_ODONE);
            TR(16, k);
        };
        for (int k = wg - 1;; k += 4) {
            window(std::integral_constant<int, 0>(), k);
            if (__any_sync(0xffffffffu, k + 2 >= nwin)) break;
            window(std::integral_constant<int, 1>(), k + 2);
            if (__any_sync(0xffffffffu, k + 4 >= nwin)) break;
        }
        (void)zero;
        asm volatile("setmaxnreg.inc.sync.aligned.u32 160;\n");
    }

    TR(27, wg);
    ST(2 + wg);
    uint32_t tag, seen;
    asm volatile("ld.relaxed.gpu.global.v2.u32 {%0, %1}, [%2];\n" : "=r"(tag), "=r"(seen) : "l"(g_guard) : "memory");
    if (attn || !MPRE) {
        __syncwarp();
        if (lane == 0) mbar_arrive(sbase + SM_PBAR + 96);
    }
    if (!attn) {
        uint4 wor[2][6];
#pragma unroll
        for (int i = 0; i < 12; i++)
            ldg_nc_v4(reinterpret_cast<uint32_t (&)[4]>(wor[i / 6][i % 6]), P.wo + ((tid >> 2) + i / 6 * 96) * 192 + 32 * (i % 6) + 8 * c);
        {
            const uint32_t wstep = (gridDim.x - 2 * P.npair) * 12, wend = MEND * P.npair;
            const uint32_t mbuf = sbase + (tid >> 5) * MBUFS * M_BUF, mbar = sbase + SM_MBAR + (tid >> 5) * MBUFS * 8;
            uint32_t w = MPRE * P.npair + (role - 2 * P.npair) * 12 + (tid >> 5);
            auto load = [&](uint32_t w, uint32_t i) {
                if (w < wend) {
                    const uint32_t o = (w * 4802u) & ~(MALIGN - 1), n = MALIGN == 16 ? 4816 : ((w * 4802u & ~15u) + 4816 - o + MALIGN - 1) & ~(MALIGN - 1);
                    mbar_arrive_expect_tx(mbar + i * 8, n);
                    asm volatile("cp.async.bulk.shared::cluster.global.mbarrier::complete_tx::bytes.L2::cache_hint [%0], [%1], %3, [%2], %4;\n"
                                 :: "r"(mbuf + i * M_BUF), "l"(reinterpret_cast<const char*>(P.mask) + o),
                                    "r"(mbar + i * 8), "r"(n), "l"(EVICT_FIRST) : "memory");
                }
            };
            if (elect_one()) {
                if (MDELAY) __nanosleep(MDELAY);
#pragma unroll 1
                for (int i = 0; i < MBUFS; i++) load(w + i * wstep, i);
            }
            __syncwarp();
            uint32_t i = 0, ph = 0;
#pragma unroll 1
            for (; w < wend; w += wstep) {
                const uint32_t b = mbuf + i * M_BUF + ((w * 4802u) & (MALIGN - 16));
                mbar_wait(mbar + i * 8, ph);
                uint32_t acc = lds16(b + (lane & 7) * 2 + (lane & 8) * 600);
                if ((lane & 15) - (w & 7) > 8u) acc = 0;
                uint32_t v[10][4];
#pragma unroll
                for (int j = 0; j < 10; j++) lds128(v[j], b + 16 * (j < 9 ? 1 + lane + 32 * j : min(289 + lane, 299)));
#pragma unroll
                for (int j = 0; j < 10; j++) acc |= v[j][0] | v[j][1] | v[j][2] | v[j][3];
                const uint32_t nz = __any_sync(0xffffffffu, (acc & 0x7FFF7FFFu) != 0) ? 1 : 0;
                if (elect_one()) {
                    load(w + MBUFS * wstep, i);
                    const uint32_t k = w / (uint32_t)P.npair;
                    asm volatile("st.relaxed.gpu.global.u32 [%0], %1;\n" :: "l"(g_mz + (w - k * P.npair) * 128 + k), "r"((tag | 255) - nz) : "memory");
                }
                __syncwarp();
                if (++i == MBUFS) { i = 0; ph ^= 1; }
            }
            if (lane == 0) mbar_arrive(sbase + SM_PBAR + 96);
            asm volatile("bar.sync 6, 384;\n" ::: "memory");
        }
#pragma unroll
        for (int rh = 0; rh < 2; rh++) {
            const int row = (tid >> 2) + 96 * rh;
            const uint4 (&w)[6] = wor[rh];
            float s = 0.f;
#pragma unroll
            for (int a = 0; a < 6; a++)
                s += ((bf16lo(w[a].x) + bf16hi(w[a].x)) + (bf16lo(w[a].y) + bf16hi(w[a].y))) +
                     ((bf16lo(w[a].z) + bf16hi(w[a].z)) + (bf16lo(w[a].w) + bf16hi(w[a].w)));
            s += __shfl_xor_sync(0xffffffffu, s, 1);
            s += __shfl_xor_sync(0xffffffffu, s, 2);
            s *= (1.f / 192.f);
            const uint32_t sw = (row >> 1) & 3;
            const uint32_t d = sbase + SM_WO + row * 64 + ((c ^ sw) << 4), e = sbase + SM_WO + row * 64 + c * 4;
#pragma unroll
            for (int a = 0; a < 6; a++) {
                uint32_t h[4] = {pack_f16(bf16lo(w[a].x) - s, bf16hi(w[a].x) - s), pack_f16(bf16lo(w[a].y) - s, bf16hi(w[a].y) - s),
                                       pack_f16(bf16lo(w[a].z) - s, bf16hi(w[a].z) - s), pack_f16(bf16lo(w[a].w) - s, bf16hi(w[a].w) - s)};
#pragma unroll
                for (int i = 0; i < 4; i++) h[i] = (h[i] + (WMASK + 1) / 2 * 0x10001u) & ~(WMASK * 0x10001u);
                if (a < 2 * PSM) {
                    sts128(d + a * 12288, h[0], h[1], h[2], h[3]);
                } else {
#pragma unroll
                    for (int i = 0; i < 4; i++) sts32(e + a * 12288 + ((i ^ sw) << 4), h[i]);
                }
            }
        }
        fence_async_smem();
        asm volatile("bar.sync 6, 384;\n" ::: "memory");
        if (role == 2 * P.npair && tid == 0) {
            asm volatile("cp.async.bulk.global.shared::cta.bulk_group [%0], [%1], %2;\n"
                         :: "l"(g_wo), "r"(sbase + SM_WO), "n"(SM_STAGE) : "memory");
            asm volatile("cp.async.bulk.commit_group;\n" ::: "memory");
            asm volatile("cp.async.bulk.wait_group 0;\n" ::: "memory");
            asm volatile("fence.proxy.async.global;\n" ::: "memory");
            asm volatile("st.release.gpu.global.u32 [%0], %1;\n" :: "l"(g_guard + 3), "r"(tag | 255) : "memory");
        }
        __syncwarp();
    } else {
        mbar_wait(bars + B_WRAW, 1);
    }
    tag |= 255;
    if (bad) g_guard[1] = tag;
    bad |= seen == tag;
    TR(27, 4 + wg);
    if (wg == 0) ST(5);
    {
        PROJ_SCHEDULE
        uint64_t descW = make_desc(sbase + SM_WO, 12288, 512, 2);
        const uint64_t descA = make_desc(sbase + SM_STAGE + wg * STAGE_BYTES, 16, 1024, 1);
        const uint32_t bar = sbase + SM_PBAR + wg * 8;
        const uint32_t yrel = sbase + SM_STAGE + wg * STAGE_BYTES + (warp * 16 + (lane & 15)) * 128 + (((lane & 7) ^ (lane >> 4)) << 4);
        uint32_t acch[48];
        uint32_t it = 0;
        for (int u = tile0 + wg * tstep; u < tend; u += 3 * tstep, it++) {
            const int tile = (NOLD && u < P.t1) ? u - told : u;
            descW += P.z1;
            mbar_wait(bar + (it & 1) * 24, (it >> 1) & 1);
            TR(28, it * 3 + wg);
            ST(6 + wg);
            if (it > 0 || wg > 0) asm volatile("bar.sync %0, 256;\n" :: "r"(8 + wg) : "memory");
            wgmma_fence();
            mma_projh<0, 0>(acch, descA + (uint64_t)((it & 1) * (3 * STAGE_BYTES >> 4)), descW);
            wgmma_commit();
            if (u + tstep < tend) asm volatile("bar.arrive %0, 256;\n" :: "r"(wg == 2 ? 8 : 9 + wg) : "memory");
            wgmma_wait<0>();
            reg_fence(acch);
            uint32_t a[4];
#pragma unroll
            for (int i = 0; i < 4; i++) a[i] = hmul2_f16(acch[i], acch[i]);
#pragma unroll
            for (int i = 4; i < 48; i++) a[i & 3] = hfma2_f16(acch[i], acch[i], a[i & 3]);
            float s0 = (f16lo(a[0]) + f16hi(a[0])) + (f16lo(a[2]) + f16hi(a[2])), s1 = (f16lo(a[1]) + f16hi(a[1])) + (f16lo(a[3]) + f16hi(a[3]));
            s0 += __shfl_xor_sync(0xffffffffu, s0, 1);
            s1 += __shfl_xor_sync(0xffffffffu, s1, 1);
            s0 += __shfl_xor_sync(0xffffffffu, s0, 2);
            s1 += __shfl_xor_sync(0xffffffffu, s1, 2);
            if (max(__float_as_uint(s0) - VAR_MIN, __float_as_uint(s1) - VAR_MIN) >= F32_INF - VAR_MIN) {
                const int rem = ((tile < TILES_A) ? NPIX - SEG_B - 64 * tile : SEG_B - 64 * (tile - TILES_A)) - warp * 16 - g;
                if ((__float_as_uint(s0) - VAR_MIN >= F32_INF - VAR_MIN && rem > 0) ||
                    (__float_as_uint(s1) - VAR_MIN >= F32_INF - VAR_MIN && rem > 8)) {
                    bad = true;
                    g_guard[1] = tag;
                }
            }
            const float rs0 = rsqrt_ftz(fmaf(s0, 1.f / 192.f, 1e-5f));
            const float rs1 = rsqrt_ftz(fmaf(s1, 1.f / 192.f, 1e-5f));
            const uint32_t rh[2] = {pack_f16(rs0, rs0), pack_f16(rs1, rs1)};
            auto Y = [&](int i) {
                const uint32_t t = hmul2_f16(acch[i], rh[i & 1]);
                return pack_bf16(f16lo(t), f16hi(t));
            };
            const uint32_t ya = yrel + (it & 1) * 3 * STAGE_BYTES;
            auto direct = [&]() {
                const int p0 = (tile < TILES_A) ? SEG_B + 64 * (tile & PWRAP) : 64 * (tile - TILES_A);
                const int lim = ((tile < TILES_A) ? NPIX : SEG_B) - p0;
                char* const po = reinterpret_cast<char*>(P.out) + (uint32_t)((p0 + warp * 16 + g) * 384 + c * 16);
                const bool v0 = warp * 16 + g < lim, v1 = warp * 16 + g + 8 < lim;
#pragma unroll
                for (int i = 2 * PSM; i < 6; i++) {
                    const int j = 8 * i;
                    stg128_if(v0, po + 64 * i, Y(j), Y(j + 2), Y(j + 4), Y(j + 6));
                    stg128_if(v1, po + 8 * 384 + 64 * i, Y(j + 1), Y(j + 3), Y(j + 5), Y(j + 7));
                }
            };
            if (PSM < 3 && PDF) direct();
#pragma unroll
            for (int p = 0; p < 4 * PSM; p++)
                stsm_x4((ya ^ (32 * (p & 3))) + (p >> 2) * 8192, Y(4 * p), Y(4 * p + 1), Y(4 * p + 2), Y(4 * p + 3));
            if (WFEN & 1) fence_async_smem();
            __syncwarp();
            if (lane == 0) mbar_arrive(bar + 104 + (it & 1) * 24);
            if (PSM < 3 && !PDF) direct();
            TR(29, it * 3 + wg);
            ST(16 + wg);
        }
        __syncwarp();
        if (lane == 0) mbar_arrive(sbase + SM_PBAR + 56);
    }

    {
        uint32_t any;
        asm volatile("{\n.reg .pred p, q;\nsetp.ne.u32 q, %1, 0;\nbarrier.cta.red.or.pred.aligned p, %2, 128, q;\nselp.u32 %0, 1, 0, p;\n}\n"
                     : "=r"(any) : "r"((uint32_t)bad), "r"(12 + wg) : "memory");
        if (!any) return;
    }
    redo(P, smem + wg * FB_BYTES, tag, 12 + wg);
}

}

typedef CUresult (*PFN_encodeTiled)(CUtensorMap*, CUtensorMapDataType, cuuint32_t, void*, const cuuint64_t*,
                                    const cuuint64_t*, const cuuint32_t*, const cuuint32_t*, CUtensorMapInterleave,
                                    CUtensorMapSwizzle, CUtensorMapL2promotion, CUtensorMapFloatOOBfill);

extern "C" void kernel_launch(void* const* d_in, const int* in_sizes, int n_in, void* d_out, int out_size) {
    swin::Params P;
    P.x           = (const __nv_bfloat16*)d_in[0];
    P.wqkv        = (const __nv_bfloat16*)d_in[1];
    P.wo          = (const __nv_bfloat16*)d_in[2];
    P.logit_scale = (const __nv_bfloat16*)d_in[3];
    P.cpb_w1      = (const __nv_bfloat16*)d_in[4];
    P.cpb_w2      = (const __nv_bfloat16*)d_in[5];
    P.rel_coords  = (const __nv_bfloat16*)d_in[6];
    P.rel_idx     = (const int*)d_in[7];
    P.mask        = (const __nv_bfloat16*)d_in[8];
    P.out         = (__nv_bfloat16*)d_out;
    P.z1 = 0;
    static PFN_encodeTiled encode = nullptr;
    if (!encode) {
        cudaFuncSetAttribute(swin::swin_window_attn_kernel, cudaFuncAttributeMaxDynamicSharedMemorySize, swin::SM_TOTAL);
        cudaDriverEntryPointQueryResult qr;
        cudaGetDriverEntryPoint("cuTensorMapEncodeTiled", (void**)&encode, cudaEnableDefault, &qr);
    }
    CUtensorMap xmap, xmap4, xmap3, omap, wmap, smap, omapb, xmapa, xmapb, smap3, wraw, smapw;
    const cuuint32_t estr[4] = {1, 1, 1, 1};
    auto make = [&](CUtensorMap* m, const void* base, int rank, const cuuint64_t* gdim, const cuuint64_t* gstr,
                    const cuuint32_t* box, CUtensorMapSwizzle swz = CU_TENSOR_MAP_SWIZZLE_128B) {
        CUresult r = encode(m, CU_TENSOR_MAP_DATA_TYPE_BFLOAT16, rank, const_cast<void*>(base), gdim, gstr, box, estr,
               CU_TENSOR_MAP_INTERLEAVE_NONE, swz, CU_TENSOR_MAP_L2_PROMOTION_L2_128B,
               CU_TENSOR_MAP_FLOAT_OOB_FILL_NONE);
        (void)r;
    };
    {
        const cuuint64_t gdim[3] = {192, swin::IMG, swin::IMG}, gstr[2] = {384, swin::IMG * 384};
        const cuuint32_t box[3] = {64, 7, 7}, box4[3] = {64, 4, 1}, box3[3] = {64, 3, 1};
        make(&xmap, P.x, 3, gdim, gstr, box);
        make(&xmap4, P.x, 3, gdim, gstr, box4);
        make(&xmap3, P.x, 3, gdim, gstr, box3);
        const cuuint32_t boxa[3] = {64, 7, 3}, boxb[3] = {64, 7, 4};
        make(&xmapa, P.x, 3, gdim, gstr, boxa);
        make(&xmapb, P.x, 3, gdim, gstr, boxb);
    }
    {
        const cuuint64_t gdim[2] = {192, (cuuint64_t)swin::NPIX}, gstr[1] = {384};
        const cuuint32_t box64[2] = {64, 64};
        make(&omap, d_out, 2, gdim, gstr, box64);
        const cuuint64_t gdimb[2] = {192, (cuuint64_t)swin::SEG_B};
        make(&omapb, d_out, 2, gdimb, gstr, box64);
    }
    {
        const cuuint64_t gdim[2] = {576, 192}, gstr[1] = {1152};
        const cuuint32_t box[2] = {32, 192}, box2[2] = {64, 192};
        make(&wmap, P.wqkv, 2, gdim, gstr, box, CU_TENSOR_MAP_SWIZZLE_64B);
        make(&wraw, P.wqkv, 2, gdim, gstr, box2);
    }
    {
        const cuuint64_t gdim[4] = {32, 6, swin::IMG, swin::IMG}, gstr[3] = {64, 384, swin::IMG * 384};
        const cuuint32_t box7[4] = {32, 3, 7, 7}, box3[4] = {32, 3, 7, 3}, boxw[4] = {32, 3, 4, 1};
        make(&smap, d_out, 4, gdim, gstr, box7, CU_TENSOR_MAP_SWIZZLE_64B);
        make(&smap3, d_out, 4, gdim, gstr, box3, CU_TENSOR_MAP_SWIZZLE_64B);
        const cuuint64_t gdimw[4] = {32, 6, 4, swin::IMG};
        make(&smapw, (char*)d_out - 384, 4, gdimw, gstr, boxw, CU_TENSOR_MAP_SWIZZLE_64B);
    }
    P.npair = NPAIR; P.need = swin::ROW_DONE;
    P.t1 = swin::TILES - (NTAIL - NOLD);
    P.spread = ((132 - 2 * NPAIR) * 65536 + 131) / 132;
    swin::swin_window_attn_kernel<<<132, swin::NTHREADS, swin::SM_TOTAL>>>(P, xmap, xmap4, xmap3, omap, wmap, smap, omapb, xmapa, xmapb, smap3, wraw, smapw);
}
```

```cpp
#include <cuda_runtime.h>
#include <cuda.h>
#include <cuda_bf16.h>
#include <stdint.h>
#include <type_traits>

namespace swin {

#define NPAIR 53
#define QFP32 0
#define PF_DIST 3
#define EXP 0
#define QSPLIT 3
#define SSPLIT 0
#define LATEMASK 0
#define CLUSTER 0
#define NOPF 0
#define NTAIL 250
#define PSTORE 1
#define PORDER 1
#define GORD 0
#define GMERGE 0
#define XSPLIT 1
#define EARLYW 1
#define NEARLY 4
#define W1 1
#define W2 2
#define W3 2
#define T_ONEBUF 0
#define T_NOWV 0
#define MPF 3
#define MRND 5
#define PX_L 3
#define PX_S 3
#define PX_W 0
#define PCHUNK 1
#define SPREAD 2
#define PSM 2
#define PDF 0
#define PWRAP -1
#define POLLER 1
#define PUBN 2
#define PUBT 4
#define NSTATIC 92
#define RSLEEP 800
#define AROLL 0
#define WOSPLIT 4
#define PADZ 1
#define MPRE 14
#define MEND 92
#define HOUT 1
#define HX 0
#define HM 2
#define OONE 1
#define VSTR 10256
#define MALIGN 128
#define MBUFS 2
#define FREL 1
#define RPOLL 1
#define NOCC 0
#define WFEN 0
#define ENDX 0
#define EW 1
#define EWT 480
#define GLATE 2
#define MDELAY 0
#define OSW 1
#define XPF 2
#define NOLD 0
#define OPF 1
#define WPOLL 1
#define EDELAY 200
#define PH 1
#define MBG 0
#define BGB 2
#define BGS 0
#define MLIM (MBG ? MBG : MEND)
#define PFALT 0
#define LATEW 0
#define SRS 0
#define MRAMP 0
#define NOONES 0
#define ADELAY 0
#define ADPOS 0
#define ADEL(pos) do { if (ADELAY && ADPOS == pos) { uint32_t t0_, t1_; asm volatile("mov.u32 %0, %%clock;" : "=r"(t0_) :: "memory"); do { asm volatile("mov.u32 %0, %%clock;" : "=r"(t1_) :: "memory"); } while (t1_ - t0_ < (uint32_t)ADELAY); } } while (0)
#define PVLATE 0
#define QDEP 0
#define BINIT 0
#define ABAR 0
#define ABARRIER() asm volatile("{\n.reg .pred p;\nsetp.eq.u32 p, %0, 1;\n@p bar.sync 4, 128;\n@!p bar.sync 5, 128;\n}\n" :: "r"(wg) : "memory")
#define SINT 0
#define GD 0
#define ASHFL 0
#define AMAX 0
#define SPIPE 0
#define SPORD 0
#define PVFINE 1
#define NOVW 1
#define OSTG 0
#define VLATE 0
#define GSP 5
#define LEARLY 1
#define NRM 1
#define GS0 0
#define GSF 0
#define WOE 0
#define PROG 0
#define MC CLUSTER
#define PV3 0
#define OMASK 0
#define WMASK 0
#define HOIST 0
#define HINT 0
#define HINT_A ""
#define HINT_B ""
#define REG_G 232
#define REG_A 120
#define REG_H 32
constexpr int IMG      = 511;
constexpr int NWS      = 73;
constexpr int NWINDOWS = NWS * NWS;
constexpr int TOK      = 49;
constexpr int NPIX     = IMG * IMG;
constexpr int NTHREADS = 512;

constexpr int W_ATOM = 6144;
constexpr int SM_WA = 0, SM_WB = 6 * W_ATOM, SM_WV = 12 * W_ATOM;
constexpr int GRP   = TOK * 16;
constexpr int XCH   = TOK * 128;
constexpr int SM_V  = 18 * W_ATOM, V_STRIDE = VSTR, O_STRIDE = 10240, O_PITCH = 208;
constexpr int SM_QK = SM_V + 4 * O_STRIDE, QK_CHUNK = 4 * XCH;
constexpr int SM_MASK = SM_QK + 3 * QK_CHUNK;
constexpr int SM_TAB  = SM_V + 3 * V_STRIDE + 256;
constexpr int SM_DUMP = SM_MASK + 4816;
constexpr int SM_BAR  = SM_DUMP + 320;
constexpr int B_XFULL = 0, B_WRAW = 32, B_XCONS = 40, B_NTILES = 48, B_GDONE = 56, B_DYN = 192, B_ROWS = 384, B_QKRAW = 64, B_QKFREE = 96, B_VFREE = 128, B_ODONE = 160,
              B_VRAW = 224, B_MFULL = 256, B_MSTATE = 264, B_MCONS = 272, B_WFULL = 280, B_STORED = 288, B_PUBD = 304;
constexpr int SM_A_END = SM_BAR + 320;
static_assert(SM_QK % 1024 == 0 && TOK * O_PITCH + 64 - 16 <= O_STRIDE && (28 * O_PITCH + 64) % 128 == 0, "layout");
static_assert(3 * V_STRIDE + 13 * GRP <= 4 * O_STRIDE && V_STRIDE >= O_STRIDE && SM_DUMP % 128 == 80, "layout");
constexpr int SM_WO    = 0;
constexpr int SM_STAGE = 73728;
constexpr int STAGE_BYTES = 24576;
constexpr int SM_MBAR  = SM_STAGE + 6 * STAGE_BYTES, M_BUF = 4992;
constexpr int SM_PBAR  = SM_A_END;
constexpr int SM_TOTAL = SM_PBAR + 152;
static_assert(!WOE || 12 * MBUFS * M_BUF <= 6 * STAGE_BYTES, "smem");
static_assert(SM_STAGE + 6 * STAGE_BYTES <= SM_BAR && SM_MBAR + 256 + BGB * M_BUF <= SM_BAR && (!MBG || MBUFS <= 2), "smem");
static_assert(SM_TOTAL <= 232448, "smem");
static_assert(SM_BAR % 8 == 0, "barrier alignment");

constexpr int SEG_B   = 3 * IMG;
constexpr int TILES_A = (NPIX - SEG_B + 63) / 64;
constexpr int TILES   = TILES_A + (SEG_B + 63) / 64;
constexpr uint32_t ROW_DONE = NWS * 2;

__device__ uint32_t g_cnt[NWS + 7];
__device__ __align__(128) uint8_t g_wo[SM_STAGE];
__device__ uint32_t g_mz[64 * 128];
__device__ uint32_t g_next[2];
__device__ uint32_t g_done;
__device__ __align__(16) uint32_t g_guard[4];
constexpr uint32_t F32_INF = 0x7F800000u;
constexpr uint32_t SS_MIN  = 0x3B800000u;
constexpr uint32_t VAR_MIN = 0x3D400000u;

#define TR(ev, idx)
#define ST(i)
#define SC(i)
#define CK(k)
constexpr uint64_t EVICT_FIRST = 0x12F0000000000000ull;
constexpr float LOG2E = 1.4426950408889634f;

__device__ __forceinline__ uint32_t smem_u32(const void* p) {
    return (uint32_t)__cvta_generic_to_shared(p);
}
__device__ __forceinline__ uint64_t make_desc(uint32_t saddr, uint32_t lbo, uint32_t sbo, uint32_t swz = 0) {
    return (uint64_t)((saddr & 0x3FFFF) >> 4) | ((uint64_t)(lbo >> 4) << 16) | ((uint64_t)(sbo >> 4) << 32) |
           ((uint64_t)swz << 62);
}
__host__ __device__ constexpr uint64_t make_desc_c(uint32_t saddr, uint32_t lbo, uint32_t sbo, uint32_t swz) {
    return (uint64_t)(saddr >> 4) | ((uint64_t)(lbo >> 4) << 16) | ((uint64_t)(sbo >> 4) << 32) | ((uint64_t)swz << 62);
}
__device__ __forceinline__ void wgmma_fence()  { asm volatile("wgmma.fence.sync.aligned;\n" ::: "memory"); }
__device__ __forceinline__ void wgmma_commit() { asm volatile("wgmma.commit_group.sync.aligned;\n" ::: "memory"); }
template <int N> __device__ __forceinline__ void wgmma_wait() {
    asm volatile("wgmma.wait_group.sync.aligned %0;\n" :: "n"(N) : "memory");
}
__device__ __forceinline__ void fence_async_smem() { asm volatile("fence.proxy.async.shared::cta;\n" ::: "memory"); }
__device__ __forceinline__ void wg_bar(int id) { asm volatile("bar.sync %0, 128;\n" :: "r"(id) : "memory"); }

template <int N> __device__ __forceinline__ void reg_fence(float (&v)[N]) {
#pragma unroll
    for (int i = 0; i < N; i++) asm volatile("" : "+f"(v[i]) :: "memory");
}
template <int N> __device__ __forceinline__ void reg_fence(uint32_t (&v)[N]) {
#pragma unroll
    for (int i = 0; i < N; i++) asm volatile("" : "+r"(v[i]) :: "memory");
}
template <int N, int M> __device__ __forceinline__ void reg_fence(uint32_t (&v)[N][M]) {
#pragma unroll
    for (int i = 0; i < N; i++) reg_fence(v[i]);
}

__device__ __forceinline__ uint32_t pack_bf16(float lo, float hi) {
    uint32_t r;
    asm("cvt.rn.bf16x2.f32 %0, %1, %2;\n" : "=r"(r) : "f"(hi), "f"(lo));
    return r;
}
__device__ __forceinline__ uint32_t pack_f16(float lo, float hi) {
    uint32_t r;
    asm("cvt.rn.f16x2.f32 %0, %1, %2;\n" : "=r"(r) : "f"(hi), "f"(lo));
    return r;
}
__device__ __forceinline__ uint32_t pack_f16_sat(float lo, float hi) {
    uint32_t r;
    asm("cvt.rn.satfinite.f16x2.f32 %0, %1, %2;\n" : "=r"(r) : "f"(hi), "f"(lo));
    return r;
}
__device__ __forceinline__ uint32_t hmul2_f16(uint32_t a, uint32_t b) {
    uint32_t r;
    asm("mul.rn.f16x2 %0, %1, %2;\n" : "=r"(r) : "r"(a), "r"(b));
    return r;
}
__device__ __forceinline__ uint32_t hadd2_f16(uint32_t a, uint32_t b) {
    uint32_t r;
    asm("add.rn.f16x2 %0, %1, %2;\n" : "=r"(r) : "r"(a), "r"(b));
    return r;
}
__device__ __forceinline__ uint32_t hfma2_f16(uint32_t a, uint32_t b, uint32_t c) {
    uint32_t r;
    asm("fma.rn.f16x2 %0, %1, %2, %3;\n" : "=r"(r) : "r"(a), "r"(b), "r"(c));
    return r;
}
__device__ __forceinline__ uint32_t hmax2_f16(uint32_t a, uint32_t b) {
    uint32_t r;
    asm("max.f16x2 %0, %1, %2;\n" : "=r"(r) : "r"(a), "r"(b));
    return r;
}
template <int H> __device__ __forceinline__ uint32_t hsub2_bc(uint32_t a, uint32_t b) {
    uint32_t r;
    if (H == 0) asm("{\n.reg .b16 l, h;\n.reg .b32 t;\nmov.b32 {l, h}, %2;\nmov.b32 t, {l, l};\nsub.rn.f16x2 %0, %1, t;\n}\n" : "=r"(r) : "r"(a), "r"(b));
    else        asm("{\n.reg .b16 l, h;\n.reg .b32 t;\nmov.b32 {l, h}, %2;\nmov.b32 t, {h, h};\nsub.rn.f16x2 %0, %1, t;\n}\n" : "=r"(r) : "r"(a), "r"(b));
    return r;
}
template <int H> __device__ __forceinline__ uint32_t hmul2_bc(uint32_t a, uint32_t b) {
    uint32_t r;
    if (H == 0) asm("{\n.reg .b16 l, h;\n.reg .b32 t;\nmov.b32 {l, h}, %2;\nmov.b32 t, {l, l};\nmul.rn.f16x2 %0, %1, t;\n}\n" : "=r"(r) : "r"(a), "r"(b));
    else        asm("{\n.reg .b16 l, h;\n.reg .b32 t;\nmov.b32 {l, h}, %2;\nmov.b32 t, {h, h};\nmul.rn.f16x2 %0, %1, t;\n}\n" : "=r"(r) : "r"(a), "r"(b));
    return r;
}
__device__ __forceinline__ uint32_t hsub2_f16(uint32_t a, uint32_t b) {
    uint32_t r;
    asm("sub.rn.f16x2 %0, %1, %2;\n" : "=r"(r) : "r"(a), "r"(b));
    return r;
}
__device__ __forceinline__ uint32_t ex2_f16x2(uint32_t a) {
    uint32_t r;
    asm("ex2.approx.f16x2 %0, %1;\n" : "=r"(r) : "r"(a));
    return r;
}
__device__ __forceinline__ uint32_t ex2_f16lo(uint32_t a) {
    uint32_t r;
    asm("{\n.reg .b16 l, h;\nmov.b32 {l, h}, %1;\nex2.approx.f16 l, l;\nmov.b32 %0, {l, h};\n}\n" : "=r"(r) : "r"(a));
    return r;
}
__device__ __forceinline__ uint32_t lds16(uint32_t addr) {
    uint32_t v;
    asm volatile("ld.shared.u16 %0, [%1];\n" : "=r"(v) : "r"(addr) : "memory");
    return v;
}
__device__ __forceinline__ uint32_t lds16v(uint32_t addr) {
    uint32_t v;
    asm volatile("ld.volatile.shared.u16 %0, [%1];\n" : "=r"(v) : "r"(addr) : "memory");
    return v;
}
__device__ __forceinline__ void sts16(uint32_t addr, uint32_t v) {
    asm volatile("st.volatile.shared.u16 [%0], %1;\n" :: "r"(addr), "r"(v) : "memory");
}
__device__ __forceinline__ float f16lo(uint32_t v) {
    float r;
    asm("{\n.reg .b16 l, h;\nmov.b32 {l, h}, %1;\ncvt.f32.f16 %0, l;\n}\n" : "=f"(r) : "r"(v));
    return r;
}
__device__ __forceinline__ float f16hi(uint32_t v) {
    float r;
    asm("{\n.reg .b16 l, h;\nmov.b32 {l, h}, %1;\ncvt.f32.f16 %0, h;\n}\n" : "=f"(r) : "r"(v));
    return r;
}
__device__ __forceinline__ uint32_t bf2h(uint32_t v) {
    return pack_f16(__uint_as_float(v << 16), __uint_as_float(v & 0xFFFF0000u));
}
__device__ __forceinline__ float bf16lo(uint32_t v) { return __uint_as_float(v << 16); }
__device__ __forceinline__ float bf16hi(uint32_t v) { return __uint_as_float(v & 0xFFFF0000u); }
__device__ __forceinline__ uint32_t hadd2_bf16(uint32_t a, uint32_t b) {
    uint32_t r;
    asm("add.rn.bf16x2 %0, %1, %2;\n" : "=r"(r) : "r"(a), "r"(b));
    return r;
}
__device__ __forceinline__ uint32_t hmul2_bf16(uint32_t a, uint32_t b) {
    uint32_t r;
    asm("mul.rn.bf16x2 %0, %1, %2;\n" : "=r"(r) : "r"(a), "r"(b));
    return r;
}
__device__ __forceinline__ uint32_t hsub2_bf16(uint32_t a, uint32_t b) {
    uint32_t r;
    asm("sub.rn.bf16x2 %0, %1, %2;\n" : "=r"(r) : "r"(a), "r"(b));
    return r;
}
__device__ __forceinline__ uint32_t hfma2_bf16(uint32_t a, uint32_t b, uint32_t c) {
    uint32_t r;
    asm("fma.rn.bf16x2 %0, %1, %2, %3;\n" : "=r"(r) : "r"(a), "r"(b), "r"(c));
    return r;
}
__device__ __forceinline__ uint32_t hmax2_bf16(uint32_t a, uint32_t b) {
    uint32_t r;
    asm("max.bf16x2 %0, %1, %2;\n" : "=r"(r) : "r"(a), "r"(b));
    return r;
}
__device__ __forceinline__ uint32_t ex2_bf16x2(uint32_t a) {
    uint32_t r;
    asm("ex2.approx.ftz.bf16x2 %0, %1;\n" : "=r"(r) : "r"(a));
    return r;
}
__device__ __forceinline__ uint32_t ex2_bf16lo(uint32_t a) {
    uint32_t r;
    asm("{\n.reg .b16 l, h;\nmov.b32 {l, h}, %1;\nex2.approx.ftz.bf16 l, l;\ncvt.u32.u16 %0, l;\n}\n" : "=r"(r) : "r"(a));
    return r;
}
__device__ __forceinline__ uint32_t mbar_test(uint32_t bar, uint32_t parity) {
    uint32_t ok;
    asm volatile("{\n.reg .pred p;\nmbarrier.test_wait.parity.shared::cta.b64 p, [%1], %2;\nselp.u32 %0, 1, 0, p;\n}\n"
                 : "=r"(ok) : "r"(bar), "r"(parity) : "memory");
    return ok;
}
__device__ __forceinline__ uint32_t prmt(uint32_t a, uint32_t b, uint32_t sel) {
    uint32_t r;
    asm("prmt.b32 %0, %1, %2, %3;\n" : "=r"(r) : "r"(a), "r"(b), "r"(sel));
    return r;
}
__device__ __forceinline__ float round_bf16(float x) { return __bfloat162float(__float2bfloat16_rn(x)); }

__device__ __forceinline__ void mbar_init(uint32_t bar, uint32_t count) {
    asm volatile("mbarrier.init.shared::cta.b64 [%0], %1;\n" :: "r"(bar), "r"(count) : "memory");
}
__device__ __forceinline__ void mbar_wait(uint32_t bar, uint32_t parity) {
    asm volatile(
        "{\n"
        ".reg .pred p;\n"
        ".reg .u32 n;\n"
        "mov.u32 n, 0;\n"
        "WAIT_%=:\n"
        "mbarrier.try_wait.parity.shared::cta.b64 p, [%0], %1" HINT_A ";\n"
        "@p bra DONE_%=;\n"
        "add.u32 n, n, 1;\n"
        "setp.lt.u32 p, n, 4194304;\n"
        "@p bra WAIT_%=;\n"
        "exit;\n"
        "DONE_%=:\n"
        "}\n" :: "r"(bar), "r"(parity) : "memory");
}
__device__ __forceinline__ void mbar_wait_cl(uint32_t bar, uint32_t parity) {
    asm volatile(
        "{\n"
        ".reg .pred p;\n"
        ".reg .u32 n;\n"
        "mov.u32 n, 0;\n"
        "WAIT_%=:\n"
        "mbarrier.try_wait.parity.acquire.cluster.shared::cta.b64 p, [%0], %1" HINT_A ";\n"
        "@p bra DONE_%=;\n"
        "add.u32 n, n, 1;\n"
        "setp.lt.u32 p, n, 4194304;\n"
        "@p bra WAIT_%=;\n"
        "exit;\n"
        "DONE_%=:\n"
        "}\n" :: "r"(bar), "r"(parity) : "memory");
}
__device__ __forceinline__ void mbar_wait4(uint32_t b0, uint32_t p0, uint32_t b1, uint32_t p1, uint32_t b2, uint32_t p2,
                                           uint32_t b3, uint32_t p3) {
    asm volatile(
        "{\n"
        ".reg .pred p, q, r, s;\n"
        ".reg .u32 n;\n"
        "mov.u32 n, 0;\n"
        "WAIT_%=:\n"
        "mbarrier.try_wait.parity.shared::cta.b64 p, [%0], %1;\n"
        "mbarrier.try_wait.parity.shared::cta.b64 q, [%2], %3;\n"
        "mbarrier.try_wait.parity.shared::cta.b64 r, [%4], %5;\n"
        "mbarrier.try_wait.parity.shared::cta.b64 s, [%6], %7;\n"
        "and.pred p, p, q;\n"
        "and.pred r, r, s;\n"
        "and.pred p, p, r;\n"
        "@p bra DONE_%=;\n"
        "add.u32 n, n, 1;\n"
        "setp.lt.u32 p, n, 4194304;\n"
        "@p bra WAIT_%=;\n"
        "exit;\n"
        "DONE_%=:\n"
        "}\n" :: "r"(b0), "r"(p0), "r"(b1), "r"(p1), "r"(b2), "r"(p2), "r"(b3), "r"(p3) : "memory");
}
__device__ __forceinline__ void mbar_wait2(uint32_t b0, uint32_t p0, uint32_t b1, uint32_t p1) {
    asm volatile(
        "{\n"
        ".reg .pred p, q;\n"
        ".reg .u32 n;\n"
        "mov.u32 n, 0;\n"
        "WAIT_%=:\n"
        "mbarrier.try_wait.parity.shared::cta.b64 p, [%0], %1;\n"
        "mbarrier.try_wait.parity.shared::cta.b64 q, [%2], %3;\n"
        "and.pred p, p, q;\n"
        "@p bra DONE_%=;\n"
        "add.u32 n, n, 1;\n"
        "setp.lt.u32 p, n, 4194304;\n"
        "@p bra WAIT_%=;\n"
        "exit;\n"
        "DONE_%=:\n"
        "}\n" :: "r"(b0), "r"(p0), "r"(b1), "r"(p1) : "memory");
}
__device__ __forceinline__ void mbar_wait_unless(uint32_t ok, uint32_t bar, uint32_t parity) {
    asm volatile(
        "{\n"
        ".reg .pred p;\n"
        ".reg .u32 n;\n"
        "setp.ne.u32 p, %2, 0;\n"
        "vote.sync.all.pred p, p, 0xffffffff;\n"
        "@p bra DONE_%=;\n"
        "mov.u32 n, 0;\n"
        "WAIT_%=:\n"
        "mbarrier.try_wait.parity.shared::cta.b64 p, [%0], %1" HINT_B ";\n"
        "@p bra DONE_%=;\n"
        "add.u32 n, n, 1;\n"
        "setp.lt.u32 p, n, 4194304;\n"
        "@p bra WAIT_%=;\n"
        "exit;\n"
        "DONE_%=:\n"
        "}\n" :: "r"(bar), "r"(parity), "r"(ok) : "memory");
}
__device__ __forceinline__ void mbar_wait_unless_dep(uint32_t ok, uint32_t bar, uint32_t parity, uint32_t zero, uint32_t& a,
                                                     uint32_t& b, uint32_t& c, uint32_t& d) {
    asm volatile(
        "{\n"
        ".reg .pred p;\n"
        ".reg .u32 n;\n"
        "setp.ne.u32 p, %6, 0;\n"
        "vote.sync.all.pred p, p, 0xffffffff;\n"
        "@p bra DONE_%=;\n"
        "mov.u32 n, 0;\n"
        "WAIT_%=:\n"
        "setp.ne.u32 p, %7, 0;\n"
        "@p ld.shared.v4.b32 {%0, %1, %2, %3}, [%7];\n"
        "mbarrier.try_wait.parity.shared::cta.b64 p, [%4], %5;\n"
        "@p bra DONE_%=;\n"
        "add.u32 n, n, 1;\n"
        "setp.lt.u32 p, n, 4194304;\n"
        "@p bra WAIT_%=;\n"
        "exit;\n"
        "DONE_%=:\n"
        "}\n" : "+r"(a), "+r"(b), "+r"(c), "+r"(d) : "r"(bar), "r"(parity), "r"(ok), "r"(zero) : "memory");
}
__device__ __forceinline__ void mbar_wait2_unless(uint32_t ok, uint32_t b0, uint32_t p0, uint32_t b1, uint32_t p1) {
    asm volatile(
        "{\n"
        ".reg .pred p, q;\n"
        ".reg .u32 n;\n"
        "setp.ne.u32 p, %4, 0;\n"
        "vote.sync.all.pred p, p, 0xffffffff;\n"
        "@p bra DONE_%=;\n"
        "mov.u32 n, 0;\n"
        "WAIT_%=:\n"
        "mbarrier.try_wait.parity.shared::cta.b64 p, [%0], %1" HINT_B ";\n"
        "mbarrier.try_wait.parity.shared::cta.b64 q, [%2], %3" HINT_B ";\n"
        "and.pred p, p, q;\n"
        "@p bra DONE_%=;\n"
        "add.u32 n, n, 1;\n"
        "setp.lt.u32 p, n, 4194304;\n"
        "@p bra WAIT_%=;\n"
        "exit;\n"
        "DONE_%=:\n"
        "}\n" :: "r"(b0), "r"(p0), "r"(b1), "r"(p1), "r"(ok) : "memory");
}
__device__ __forceinline__ void mbar_wait4_unless(uint32_t ok, uint32_t b0, uint32_t p0, uint32_t b1, uint32_t p1, uint32_t b2,
                                                  uint32_t p2, uint32_t b3, uint32_t p3) {
    asm volatile(
        "{\n"
        ".reg .pred p, q, r, s;\n"
        ".reg .u32 n;\n"
        "setp.ne.u32 p, %8, 0;\n"
        "vote.sync.all.pred p, p, 0xffffffff;\n"
        "@p bra DONE_%=;\n"
        "mov.u32 n, 0;\n"
        "WAIT_%=:\n"
        "mbarrier.try_wait.parity.shared::cta.b64 p, [%0], %1;\n"
        "mbarrier.try_wait.parity.shared::cta.b64 q, [%2], %3;\n"
        "mbarrier.try_wait.parity.shared::cta.b64 r, [%4], %5;\n"
        "mbarrier.try_wait.parity.shared::cta.b64 s, [%6], %7;\n"
        "and.pred p, p, q;\n"
        "and.pred r, r, s;\n"
        "and.pred p, p, r;\n"
        "@p bra DONE_%=;\n"
        "add.u32 n, n, 1;\n"
        "setp.lt.u32 p, n, 4194304;\n"
        "@p bra WAIT_%=;\n"
        "exit;\n"
        "DONE_%=:\n"
        "}\n" :: "r"(b0), "r"(p0), "r"(b1), "r"(p1), "r"(b2), "r"(p2), "r"(b3), "r"(p3), "r"(ok) : "memory");
}
__device__ __forceinline__ void sched_fence(uint32_t zero, uint32_t a, uint32_t b, uint32_t c, uint32_t d, uint32_t e = 0,
                                            uint32_t f = 0, uint32_t g = 0, uint32_t h = 0, uint32_t i = 0, uint32_t j = 0,
                                            uint32_t k = 0) {
    asm volatile("{\n.reg .pred p;\n.reg .u32 n;\nsetp.eq.u32 p, %0, 0;\n@p bra.uni DONE_%=;\nmov.u32 n, %0;\nSPIN_%=:\n"
                 "nanosleep.u32 %1;\nnanosleep.u32 %2;\nnanosleep.u32 %3;\nnanosleep.u32 %4;\nnanosleep.u32 %5;\n"
                 "nanosleep.u32 %6;\nnanosleep.u32 %7;\nnanosleep.u32 %8;\nnanosleep.u32 %9;\nnanosleep.u32 %10;\n"
                 "nanosleep.u32 %11;\nsub.u32 n, n, 1;\nsetp.ne.u32 p, n, 0;\n@p bra.uni SPIN_%=;\nDONE_%=:\n}\n"
                 :: "r"(zero), "r"(a), "r"(b), "r"(c), "r"(d), "r"(e), "r"(f), "r"(g), "r"(h), "r"(i), "r"(j), "r"(k) : "memory");
}
__device__ __forceinline__ void mma1688(uint32_t (&d)[2], const uint32_t (&a)[2], uint32_t b) {
    asm volatile("mma.sync.aligned.m16n8k8.row.col.f16.f16.f16.f16 {%0, %1}, {%2, %3}, {%4}, {%5, %5};\n"
                 : "=r"(d[0]), "=r"(d[1]) : "r"(a[0]), "r"(a[1]), "r"(b), "r"(0u));
}
__device__ __forceinline__ void sched_fence16(uint32_t zero, const uint32_t (&v)[4][4], uint32_t a = 0, uint32_t b = 0) {
    asm volatile("{\n.reg .pred p;\n.reg .u32 n;\nsetp.eq.u32 p, %0, 0;\n@p bra.uni DONE_%=;\nmov.u32 n, %0;\nSPIN_%=:\n"
                 "nanosleep.u32 %17;\nnanosleep.u32 %18;\n"
                 "st.shared.v4.b32 [n], {%1, %2, %3, %4};\nst.shared.v4.b32 [n + 16], {%5, %6, %7, %8};\n"
                 "st.shared.v4.b32 [n + 32], {%9, %10, %11, %12};\nst.shared.v4.b32 [n + 48], {%13, %14, %15, %16};\n"
                 "sub.u32 n, n, 1;\nsetp.ne.u32 p, n, 0;\n@p bra.uni SPIN_%=;\nDONE_%=:\n}\n"
                 :: "r"(zero), "r"(v[0][0]), "r"(v[0][1]), "r"(v[0][2]), "r"(v[0][3]), "r"(v[1][0]), "r"(v[1][1]), "r"(v[1][2]), "r"(v[1][3]),
                    "r"(v[2][0]), "r"(v[2][1]), "r"(v[2][2]), "r"(v[2][3]), "r"(v[3][0]), "r"(v[3][1]), "r"(v[3][2]), "r"(v[3][3]),
                    "r"(a), "r"(b) : "memory");
}
__device__ __forceinline__ void sched_dep(uint32_t zero, uint32_t& a, uint32_t& b, uint32_t& c, uint32_t& d) {
    asm volatile("{\n.reg .pred p;\n.reg .u32 n;\nsetp.eq.u32 p, %4, 0;\n@p bra.uni DONE_%=;\nmov.u32 n, %4;\nSPIN_%=:\n"
                 "ld.shared.v4.b32 {%0, %1, %2, %3}, [n];\n"
                 "sub.u32 n, n, 1;\nsetp.ne.u32 p, n, 0;\n@p bra.uni SPIN_%=;\nDONE_%=:\n}\n"
                 : "+r"(a), "+r"(b), "+r"(c), "+r"(d) : "r"(zero) : "memory");
}
__device__ __forceinline__ void mbar_arrive(uint32_t bar) {
    asm volatile("mbarrier.arrive.shared::cta.b64 _, [%0];\n" :: "r"(bar) : "memory");
}
__device__ __forceinline__ void mbar_arrive_n(uint32_t bar, uint32_t n) {
    asm volatile("mbarrier.arrive.shared::cta.b64 _, [%0], %1;\n" :: "r"(bar), "r"(n) : "memory");
}
__device__ __forceinline__ void mbar_arrive_expect_tx(uint32_t bar, uint32_t bytes) {
    asm volatile("mbarrier.arrive.expect_tx.shared::cta.b64 _, [%0], %1;\n" :: "r"(bar), "r"(bytes) : "memory");
}
__device__ __forceinline__ void stg128_if(bool p, void* addr, uint32_t x, uint32_t y, uint32_t z, uint32_t w) {
    asm volatile("{\n.reg .pred q;\nsetp.ne.b32 q, %5, 0;\n@q st.global.L1::no_allocate.L2::cache_hint.v4.b32 [%0], {%1, %2, %3, %4}, %6;\n}\n"
                 :: "l"(addr), "r"(x), "r"(y), "r"(z), "r"(w), "r"((uint32_t)p), "l"(EVICT_FIRST) : "memory");
}
__device__ __forceinline__ void stg128o_if(bool p, void* addr, uint32_t x, uint32_t y, uint32_t z, uint32_t w) {
    asm volatile("{\n.reg .pred q;\nsetp.ne.b32 q, %5, 0;\n@q st.global.L1::no_allocate.v4.b32 [%0], {%1, %2, %3, %4};\n}\n"
                 :: "l"(addr), "r"(x), "r"(y), "r"(z), "r"(w), "r"((uint32_t)p) : "memory");
}
__device__ __forceinline__ void stsm_x4(uint32_t addr, uint32_t r0, uint32_t r1, uint32_t r2, uint32_t r3) {
    asm volatile("stmatrix.sync.aligned.m8n8.x4.shared.b16 [%0], {%1, %2, %3, %4};\n"
                 :: "r"(addr), "r"(r0), "r"(r1), "r"(r2), "r"(r3) : "memory");
}
__device__ __forceinline__ void stsm_x4_if(bool p, uint32_t addr, uint32_t r0, uint32_t r1, uint32_t r2, uint32_t r3) {
    asm volatile("{\n.reg .pred q;\nsetp.ne.b32 q, %5, 0;\n@q stmatrix.sync.aligned.m8n8.x4.shared.b16 [%0], {%1, %2, %3, %4};\n}\n"
                 :: "r"(addr), "r"(r0), "r"(r1), "r"(r2), "r"(r3), "r"((uint32_t)p) : "memory");
}
__device__ __forceinline__ void stsm_x2(uint32_t addr, uint32_t r0, uint32_t r1) {
    asm volatile("stmatrix.sync.aligned.m8n8.x2.shared.b16 [%0], {%1, %2};\n" :: "r"(addr), "r"(r0), "r"(r1) : "memory");
}
__device__ __forceinline__ void sts128(uint32_t addr, uint32_t r0, uint32_t r1, uint32_t r2, uint32_t r3) {
    asm volatile("st.shared.v4.b32 [%0], {%1, %2, %3, %4};\n" :: "r"(addr), "r"(r0), "r"(r1), "r"(r2), "r"(r3) : "memory");
}
__device__ __forceinline__ void sts32(uint32_t addr, uint32_t v) {
    asm volatile("st.shared.b32 [%0], %1;\n" :: "r"(addr), "r"(v) : "memory");
}
__device__ __forceinline__ uint32_t lds32(uint32_t addr) {
    uint32_t v;
    asm volatile("ld.shared.b32 %0, [%1];\n" : "=r"(v) : "r"(addr) : "memory");
    return v;
}
__device__ __forceinline__ void lds128(uint32_t (&r)[4], uint32_t addr) {
    asm volatile("ld.shared.v4.b32 {%0, %1, %2, %3}, [%4];\n" : "=r"(r[0]), "=r"(r[1]), "=r"(r[2]), "=r"(r[3]) : "r"(addr) : "memory");
}
__device__ __forceinline__ uint32_t lds32v(uint32_t addr) {
    uint32_t v;
    asm volatile("ld.volatile.shared.b32 %0, [%1];\n" : "=r"(v) : "r"(addr) : "memory");
    return v;
}
__device__ __forceinline__ void ldg_nc_v4(uint32_t (&r)[4], const void* p) {
    asm volatile("ld.global.nc.L1::no_allocate.v4.u32 {%0, %1, %2, %3}, [%4];\n"
                 : "=r"(r[0]), "=r"(r[1]), "=r"(r[2]), "=r"(r[3]) : "l"(p));
}
__device__ __forceinline__ uint32_t ldg_u32(const void* p) {
    uint32_t v;
    asm volatile("ld.global.nc.L1::evict_first.u32 %0, [%1];\n" : "=r"(v) : "l"(p));
    return v;
}
__device__ __forceinline__ void ldg_u64(const void* p, uint32_t& a, uint32_t& b) {
    asm volatile("ld.global.nc.L1::evict_first.v2.u32 {%0, %1}, [%2];\n" : "=r"(a), "=r"(b) : "l"(p));
}
__device__ __forceinline__ void prefetch_l2(const void* p) {
    asm volatile("prefetch.global.L2 [%0];\n" :: "l"(p));
}
__device__ __forceinline__ void cp_async16(uint32_t dst, const void* src) {
    asm volatile("cp.async.cg.shared.global [%0], [%1], 16;\n" :: "r"(dst), "l"(src) : "memory");
}
__device__ __forceinline__ float ex2_ftz(float x) {
    float y;
    asm("ex2.approx.ftz.f32 %0, %1;\n" : "=f"(y) : "f"(x));
    return y;
}
__device__ __forceinline__ float rcp_ftz(float x) {
    float y;
    asm("rcp.approx.ftz.f32 %0, %1;\n" : "=f"(y) : "f"(x));
    return y;
}
__device__ __forceinline__ float rsqrt_ftz(float x) {
    float y;
    asm("rsqrt.approx.ftz.f32 %0, %1;\n" : "=f"(y) : "f"(x));
    return y;
}

__device__ __forceinline__ bool elect_one() {
    uint32_t p;
    asm volatile("{\n.reg .pred q;\nelect.sync _|q, 0xffffffff;\nselp.u32 %0, 1, 0, q;\n}\n" : "=r"(p));
    return p != 0;
}
__device__ __forceinline__ void ldsm_x4(uint32_t (&r)[4], uint32_t addr) {
    asm volatile("ldmatrix.sync.aligned.m8n8.x4.shared.b16 {%0, %1, %2, %3}, [%4];\n"
                 : "=r"(r[0]), "=r"(r[1]), "=r"(r[2]), "=r"(r[3]) : "r"(addr) : "memory");
}
__device__ __forceinline__ void ldsm_x2(uint32_t& r0, uint32_t& r1, uint32_t addr) {
    asm volatile("ldmatrix.sync.aligned.m8n8.x2.shared.b16 {%0, %1}, [%2];\n" : "=r"(r0), "=r"(r1) : "r"(addr) : "memory");
}
__device__ __forceinline__ uint32_t cl(uint32_t a) { return a; }
__device__ __forceinline__ void tma_3d_mc(uint32_t dst, const CUtensorMap* map, uint32_t bar, int c0, int c1, int c2, uint16_t mask) {
    asm volatile("cp.async.bulk.tensor.3d.shared::cluster.global.mbarrier::complete_tx::bytes.multicast::cluster [%0], [%1, {%3, %4, %5}], [%2], %6;\n"
                 :: "r"(cl(dst)), "l"(reinterpret_cast<uint64_t>(map)), "r"(cl(bar)), "r"(c0), "r"(c1), "r"(c2), "h"(mask) : "memory");
}
__device__ __forceinline__ void tma_3d_p(uint32_t dst, const CUtensorMap* map, uint32_t bar, int c0, int c1, int c2, uint64_t pol) {
    asm volatile("cp.async.bulk.tensor.3d.shared::cluster.global.mbarrier::complete_tx::bytes.L2::cache_hint [%0], [%1, {%3, %4, %5}], [%2], %6;\n"
                 :: "r"(dst), "l"(reinterpret_cast<uint64_t>(map)), "r"(bar), "r"(c0), "r"(c1), "r"(c2), "l"(pol) : "memory");
}
__device__ __forceinline__ void wait_tma3(uint32_t wbar, uint32_t parity, uint32_t dst, const CUtensorMap* map, uint32_t bar, int c1, int c2) {
    uint32_t d[3] = {dst, dst + QK_CHUNK, dst + 2 * QK_CHUNK}, b[3] = {bar, bar, bar}, c0[3] = {0, 64, 128};
    uint32_t x[3] = {(uint32_t)c1, (uint32_t)c1, (uint32_t)c1}, y[3] = {(uint32_t)c2, (uint32_t)c2, (uint32_t)c2};
    uint64_t m = reinterpret_cast<uint64_t>(map);
    reg_fence(d); reg_fence(b); reg_fence(c0); reg_fence(x); reg_fence(y);
    asm volatile("" : "+l"(m) :: "memory");
    mbar_wait(wbar, parity);
#pragma unroll
    for (int i = 0; i < 3; i++)
        asm volatile("cp.async.bulk.tensor.3d.shared::cluster.global.mbarrier::complete_tx::bytes [%0], [%1, {%3, %4, %5}], [%2];\n"
                     :: "r"(d[i]), "l"(m), "r"(b[i]), "r"(c0[i]), "r"(x[i]), "r"(y[i]) : "memory");
}
__device__ __forceinline__ void mbar_arrive_cl_if(uint32_t bar, uint32_t p) {
    asm volatile("{\n.reg .pred q;\nsetp.ne.b32 q, %1, 0;\n@q mbarrier.arrive.relaxed.cluster.shared::cluster.b64 _, [%0];\n}\n"
                 :: "r"(bar), "r"(p) : "memory");
}
__device__ __forceinline__ void tma_2d(uint32_t dst, const CUtensorMap* map, uint32_t bar, int c0, int c1) {
    asm volatile("cp.async.bulk.tensor.2d.shared::cluster.global.mbarrier::complete_tx::bytes [%0], [%1, {%3, %4}], [%2];\n"
                 :: "r"(cl(dst)), "l"(reinterpret_cast<uint64_t>(map)), "r"(cl(bar)), "r"(c0), "r"(c1) : "memory");
}
__device__ __forceinline__ void tma_3d(uint32_t dst, const CUtensorMap* map, uint32_t bar, int c0, int c1, int c2) {
    asm volatile("cp.async.bulk.tensor.3d.shared::cluster.global.mbarrier::complete_tx::bytes [%0], [%1, {%3, %4, %5}], [%2];\n"
                 :: "r"(cl(dst)), "l"(reinterpret_cast<uint64_t>(map)), "r"(cl(bar)), "r"(c0), "r"(c1), "r"(c2) : "memory");
}
__device__ __forceinline__ void tma_store_4d(const CUtensorMap* map, uint32_t src, int c0, int c1, int c2, int c3) {
    asm volatile("cp.async.bulk.tensor.4d.global.shared::cta.tile.bulk_group [%0, {%2, %3, %4, %5}], [%1];\n"
                 :: "l"(reinterpret_cast<uint64_t>(map)), "r"(cl(src)), "r"(c0), "r"(c1), "r"(c2), "r"(c3) : "memory");
}
__device__ __forceinline__ void mbar_arrive_if(uint32_t bar, uint32_t cnt) {
    asm volatile("{\n.reg .pred q;\nsetp.ne.b32 q, %1, 0;\n@q mbarrier.arrive.shared::cta.b64 _, [%0], %1;\n}\n"
                 :: "r"(bar), "r"(cnt) : "memory");
}

template <int BOFF, int AOFF, int NA>
__device__ __forceinline__ void mma_qk_first(uint32_t (&d)[48], const uint32_t (&a)[NA][4], uint64_t descB) {
    asm volatile(
        "{\n"
        ".reg .pred p0, p1;\n"
        ".reg .b64 ta, ta0, tb, tb0;\n"
        "setp.ne.b32 p0, 0, 0;\n"
        "setp.eq.b32 p1, 0, 0;\n"
        "add.s64 tb0, %64, %65;\n"
        "add.s64 tb, tb0, 0;\n"
        "wgmma.mma_async.sync.aligned.m64n192k16.f16.f16.f16 {%0, %1, %2, %3, %4, %5, %6, %7, %8, %9, %10, %11, %12, %13, %14, %15, %16, %17, %18, %19, %20, %21, %22, %23, %24, %25, %26, %27, %28, %29, %30, %31, %32, %33, %34, %35, %36, %37, %38, %39, %40, %41, %42, %43, %44, %45, %46, %47}, {%48, %49, %50, %51}, tb, p0, 1, 1, 1;\n"
        "add.s64 tb, tb0, 32;\n"
        "wgmma.mma_async.sync.aligned.m64n192k16.f16.f16.f16 {%0, %1, %2, %3, %4, %5, %6, %7, %8, %9, %10, %11, %12, %13, %14, %15, %16, %17, %18, %19, %20, %21, %22, %23, %24, %25, %26, %27, %28, %29, %30, %31, %32, %33, %34, %35, %36, %37, %38, %39, %40, %41, %42, %43, %44, %45, %46, %47}, {%52, %53, %54, %55}, tb, p1, 1, 1, 1;\n"
        "add.s64 tb, tb0, 64;\n"
        "wgmma.mma_async.sync.aligned.m64n192k16.f16.f16.f16 {%0, %1, %2, %3, %4, %5, %6, %7, %8, %9, %10, %11, %12, %13, %14, %15, %16, %17, %18, %19, %20, %21, %22, %23, %24, %25, %26, %27, %28, %29, %30, %31, %32, %33, %34, %35, %36, %37, %38, %39, %40, %41, %42, %43, %44, %45, %46, %47}, {%56, %57, %58, %59}, tb, p1, 1, 1, 1;\n"
        "add.s64 tb, tb0, 96;\n"
        "wgmma.mma_async.sync.aligned.m64n192k16.f16.f16.f16 {%0, %1, %2, %3, %4, %5, %6, %7, %8, %9, %10, %11, %12, %13, %14, %15, %16, %17, %18, %19, %20, %21, %22, %23, %24, %25, %26, %27, %28, %29, %30, %31, %32, %33, %34, %35, %36, %37, %38, %39, %40, %41, %42, %43, %44, %45, %46, %47}, {%60, %61, %62, %63}, tb, p1, 1, 1, 1;\n"
        "}\n"
        : "=r"(d[0]), "=r"(d[1]), "=r"(d[2]), "=r"(d[3]), "=r"(d[4]), "=r"(d[5]), "=r"(d[6]), "=r"(d[7]), "=r"(d[8]), "=r"(d[9]), "=r"(d[10]), "=r"(d[11]), "=r"(d[12]), "=r"(d[13]), "=r"(d[14]), "=r"(d[15]), "=r"(d[16]), "=r"(d[17]), "=r"(d[18]), "=r"(d[19]), "=r"(d[20]), "=r"(d[21]), "=r"(d[22]), "=r"(d[23]), "=r"(d[24]), "=r"(d[25]), "=r"(d[26]), "=r"(d[27]), "=r"(d[28]), "=r"(d[29]), "=r"(d[30]), "=r"(d[31]), "=r"(d[32]), "=r"(d[33]), "=r"(d[34]), "=r"(d[35]), "=r"(d[36]), "=r"(d[37]), "=r"(d[38]), "=r"(d[39]), "=r"(d[40]), "=r"(d[41]), "=r"(d[42]), "=r"(d[43]), "=r"(d[44]), "=r"(d[45]), "=r"(d[46]), "=r"(d[47])
        : "r"(a[AOFF + 0][0]), "r"(a[AOFF + 0][1]), "r"(a[AOFF + 0][2]), "r"(a[AOFF + 0][3]), "r"(a[AOFF + 1][0]), "r"(a[AOFF + 1][1]), "r"(a[AOFF + 1][2]), "r"(a[AOFF + 1][3]), "r"(a[AOFF + 2][0]), "r"(a[AOFF + 2][1]), "r"(a[AOFF + 2][2]), "r"(a[AOFF + 2][3]), "r"(a[AOFF + 3][0]), "r"(a[AOFF + 3][1]), "r"(a[AOFF + 3][2]), "r"(a[AOFF + 3][3]), "l"(descB), "n"(BOFF >> 4));
}

template <int BOFF, int AOFF, int NA>
__device__ __forceinline__ void mma_qk_next(uint32_t (&d)[48], const uint32_t (&a)[NA][4], uint64_t descB) {
    asm volatile(
        "{\n"
        ".reg .pred p0, p1;\n"
        ".reg .b64 ta, ta0, tb, tb0;\n"
        "setp.ne.b32 p0, 0, 0;\n"
        "setp.eq.b32 p1, 0, 0;\n"
        "add.s64 tb0, %64, %65;\n"
        "add.s64 tb, tb0, 0;\n"
        "wgmma.mma_async.sync.aligned.m64n192k16.f16.f16.f16 {%0, %1, %2, %3, %4, %5, %6, %7, %8, %9, %10, %11, %12, %13, %14, %15, %16, %17, %18, %19, %20, %21, %22, %23, %24, %25, %26, %27, %28, %29, %30, %31, %32, %33, %34, %35, %36, %37, %38, %39, %40, %41, %42, %43, %44, %45, %46, %47}, {%48, %49, %50, %51}, tb, p1, 1, 1, 1;\n"
        "add.s64 tb, tb0, 32;\n"
        "wgmma.mma_async.sync.aligned.m64n192k16.f16.f16.f16 {%0, %1, %2, %3, %4, %5, %6, %7, %8, %9, %10, %11, %12, %13, %14, %15, %16, %17, %18, %19, %20, %21, %22, %23, %24, %25, %26, %27, %28, %29, %30, %31, %32, %33, %34, %35, %36, %37, %38, %39, %40, %41, %42, %43, %44, %45, %46, %47}, {%52, %53, %54, %55}, tb, p1, 1, 1, 1;\n"
        "add.s64 tb, tb0, 64;\n"
        "wgmma.mma_async.sync.aligned.m64n192k16.f16.f16.f16 {%0, %1, %2, %3, %4, %5, %6, %7, %8, %9, %10, %11, %12, %13, %14, %15, %16, %17, %18, %19, %20, %21, %22, %23, %24, %25, %26, %27, %28, %29, %30, %31, %32, %33, %34, %35, %36, %37, %38, %39, %40, %41, %42, %43, %44, %45, %46, %47}, {%56, %57, %58, %59}, tb, p1, 1, 1, 1;\n"
        "add.s64 tb, tb0, 96;\n"
        "wgmma.mma_async.sync.aligned.m64n192k16.f16.f16.f16 {%0, %1, %2, %3, %4, %5, %6, %7, %8, %9, %10, %11, %12, %13, %14, %15, %16, %17, %18, %19, %20, %21, %22, %23, %24, %25, %26, %27, %28, %29, %30, %31, %32, %33, %34, %35, %36, %37, %38, %39, %40, %41, %42, %43, %44, %45, %46, %47}, {%60, %61, %62, %63}, tb, p1, 1, 1, 1;\n"
        "}\n"
        : "+r"(d[0]), "+r"(d[1]), "+r"(d[2]), "+r"(d[3]), "+r"(d[4]), "+r"(d[5]), "+r"(d[6]), "+r"(d[7]), "+r"(d[8]), "+r"(d[9]), "+r"(d[10]), "+r"(d[11]), "+r"(d[12]), "+r"(d[13]), "+r"(d[14]), "+r"(d[15]), "+r"(d[16]), "+r"(d[17]), "+r"(d[18]), "+r"(d[19]), "+r"(d[20]), "+r"(d[21]), "+r"(d[22]), "+r"(d[23]), "+r"(d[24]), "+r"(d[25]), "+r"(d[26]), "+r"(d[27]), "+r"(d[28]), "+r"(d[29]), "+r"(d[30]), "+r"(d[31]), "+r"(d[32]), "+r"(d[33]), "+r"(d[34]), "+r"(d[35]), "+r"(d[36]), "+r"(d[37]), "+r"(d[38]), "+r"(d[39]), "+r"(d[40]), "+r"(d[41]), "+r"(d[42]), "+r"(d[43]), "+r"(d[44]), "+r"(d[45]), "+r"(d[46]), "+r"(d[47])
        : "r"(a[AOFF + 0][0]), "r"(a[AOFF + 0][1]), "r"(a[AOFF + 0][2]), "r"(a[AOFF + 0][3]), "r"(a[AOFF + 1][0]), "r"(a[AOFF + 1][1]), "r"(a[AOFF + 1][2]), "r"(a[AOFF + 1][3]), "r"(a[AOFF + 2][0]), "r"(a[AOFF + 2][1]), "r"(a[AOFF + 2][2]), "r"(a[AOFF + 2][3]), "r"(a[AOFF + 3][0]), "r"(a[AOFF + 3][1]), "r"(a[AOFF + 3][2]), "r"(a[AOFF + 3][3]), "l"(descB), "n"(BOFF >> 4));
}

template <int BOFF, int AOFF, int NA>
__device__ __forceinline__ void mma_v_first(uint32_t (&d)[24], const uint32_t (&a)[NA][4], uint64_t descB) {
    asm volatile(
        "{\n"
        ".reg .pred p0, p1;\n"
        ".reg .b64 ta, ta0, tb, tb0;\n"
        "setp.ne.b32 p0, 0, 0;\n"
        "setp.eq.b32 p1, 0, 0;\n"
        "add.s64 tb0, %40, %41;\n"
        "add.s64 tb, tb0, 0;\n"
        "wgmma.mma_async.sync.aligned.m64n96k16.f16.f16.f16 {%0, %1, %2, %3, %4, %5, %6, %7, %8, %9, %10, %11, %12, %13, %14, %15, %16, %17, %18, %19, %20, %21, %22, %23}, {%24, %25, %26, %27}, tb, p0, 1, 1, 1;\n"
        "add.s64 tb, tb0, 32;\n"
        "wgmma.mma_async.sync.aligned.m64n96k16.f16.f16.f16 {%0, %1, %2, %3, %4, %5, %6, %7, %8, %9, %10, %11, %12, %13, %14, %15, %16, %17, %18, %19, %20, %21, %22, %23}, {%28, %29, %30, %31}, tb, p1, 1, 1, 1;\n"
        "add.s64 tb, tb0, 64;\n"
        "wgmma.mma_async.sync.aligned.m64n96k16.f16.f16.f16 {%0, %1, %2, %3, %4, %5, %6, %7, %8, %9, %10, %11, %12, %13, %14, %15, %16, %17, %18, %19, %20, %21, %22, %23}, {%32, %33, %34, %35}, tb, p1, 1, 1, 1;\n"
        "add.s64 tb, tb0, 96;\n"
        "wgmma.mma_async.sync.aligned.m64n96k16.f16.f16.f16 {%0, %1, %2, %3, %4, %5, %6, %7, %8, %9, %10, %11, %12, %13, %14, %15, %16, %17, %18, %19, %20, %21, %22, %23}, {%36, %37, %38, %39}, tb, p1, 1, 1, 1;\n"
        "}\n"
        : "=r"(d[0]), "=r"(d[1]), "=r"(d[2]), "=r"(d[3]), "=r"(d[4]), "=r"(d[5]), "=r"(d[6]), "=r"(d[7]), "=r"(d[8]), "=r"(d[9]), "=r"(d[10]), "=r"(d[11]), "=r"(d[12]), "=r"(d[13]), "=r"(d[14]), "=r"(d[15]), "=r"(d[16]), "=r"(d[17]), "=r"(d[18]), "=r"(d[19]), "=r"(d[20]), "=r"(d[21]), "=r"(d[22]), "=r"(d[23])
        : "r"(a[AOFF + 0][0]), "r"(a[AOFF + 0][1]), "r"(a[AOFF + 0][2]), "r"(a[AOFF + 0][3]), "r"(a[AOFF + 1][0]), "r"(a[AOFF + 1][1]), "r"(a[AOFF + 1][2]), "r"(a[AOFF + 1][3]), "r"(a[AOFF + 2][0]), "r"(a[AOFF + 2][1]), "r"(a[AOFF + 2][2]), "r"(a[AOFF + 2][3]), "r"(a[AOFF + 3][0]), "r"(a[AOFF + 3][1]), "r"(a[AOFF + 3][2]), "r"(a[AOFF + 3][3]), "l"(descB), "n"(BOFF >> 4));
}

template <int BOFF, int AOFF, int NA>
__device__ __forceinline__ void mma_v_next(uint32_t (&d)[24], const uint32_t (&a)[NA][4], uint64_t descB) {
    asm volatile(
        "{\n"
        ".reg .pred p0, p1;\n"
        ".reg .b64 ta, ta0, tb, tb0;\n"
        "setp.ne.b32 p0, 0, 0;\n"
        "setp.eq.b32 p1, 0, 0;\n"
        "add.s64 tb0, %40, %41;\n"
        "add.s64 tb, tb0, 0;\n"
        "wgmma.mma_async.sync.aligned.m64n96k16.f16.f16.f16 {%0, %1, %2, %3, %4, %5, %6, %7, %8, %9, %10, %11, %12, %13, %14, %15, %16, %17, %18, %19, %20, %21, %22, %23}, {%24, %25, %26, %27}, tb, p1, 1, 1, 1;\n"
        "add.s64 tb, tb0, 32;\n"
        "wgmma.mma_async.sync.aligned.m64n96k16.f16.f16.f16 {%0, %1, %2, %3, %4, %5, %6, %7, %8, %9, %10, %11, %12, %13, %14, %15, %16, %17, %18, %19, %20, %21, %22, %23}, {%28, %29, %30, %31}, tb, p1, 1, 1, 1;\n"
        "add.s64 tb, tb0, 64;\n"
        "wgmma.mma_async.sync.aligned.m64n96k16.f16.f16.f16 {%0, %1, %2, %3, %4, %5, %6, %7, %8, %9, %10, %11, %12, %13, %14, %15, %16, %17, %18, %19, %20, %21, %22, %23}, {%32, %33, %34, %35}, tb, p1, 1, 1, 1;\n"
        "add.s64 tb, tb0, 96;\n"
        "wgmma.mma_async.sync.aligned.m64n96k16.f16.f16.f16 {%0, %1, %2, %3, %4, %5, %6, %7, %8, %9, %10, %11, %12, %13, %14, %15, %16, %17, %18, %19, %20, %21, %22, %23}, {%36, %37, %38, %39}, tb, p1, 1, 1, 1;\n"
        "}\n"
        : "+r"(d[0]), "+r"(d[1]), "+r"(d[2]), "+r"(d[3]), "+r"(d[4]), "+r"(d[5]), "+r"(d[6]), "+r"(d[7]), "+r"(d[8]), "+r"(d[9]), "+r"(d[10]), "+r"(d[11]), "+r"(d[12]), "+r"(d[13]), "+r"(d[14]), "+r"(d[15]), "+r"(d[16]), "+r"(d[17]), "+r"(d[18]), "+r"(d[19]), "+r"(d[20]), "+r"(d[21]), "+r"(d[22]), "+r"(d[23])
        : "r"(a[AOFF + 0][0]), "r"(a[AOFF + 0][1]), "r"(a[AOFF + 0][2]), "r"(a[AOFF + 0][3]), "r"(a[AOFF + 1][0]), "r"(a[AOFF + 1][1]), "r"(a[AOFF + 1][2]), "r"(a[AOFF + 1][3]), "r"(a[AOFF + 2][0]), "r"(a[AOFF + 2][1]), "r"(a[AOFF + 2][2]), "r"(a[AOFF + 2][3]), "r"(a[AOFF + 3][0]), "r"(a[AOFF + 3][1]), "r"(a[AOFF + 3][2]), "r"(a[AOFF + 3][3]), "l"(descB), "n"(BOFF >> 4));
}

template <int AOFF, int BOFF>
__device__ __forceinline__ void mma_s0_f32(float (&d)[28], uint64_t descA, uint64_t descB) {
    asm volatile(
        "{\n"
        ".reg .pred p0, p1;\n"
        ".reg .b64 ta, ta0, tb, tb0;\n"
        "setp.ne.b32 p0, 0, 0;\n"
        "setp.eq.b32 p1, 0, 0;\n"
        "add.s64 tb0, %30, %31;\n"
        "add.s64 ta0, %28, %29;\n"
        "add.s64 tb, tb0, 4;\n"
        "add.s64 ta, ta0, 0;\n"
        "wgmma.mma_async.sync.aligned.m64n56k16.f32.f16.f16 {%0, %1, %2, %3, %4, %5, %6, %7, %8, %9, %10, %11, %12, %13, %14, %15, %16, %17, %18, %19, %20, %21, %22, %23, %24, %25, %26, %27}, ta, tb, p1, 1, 1, 0, 0;\n"
        "add.s64 tb, tb0, 1572;\n"
        "add.s64 ta, ta0, 1568;\n"
        "wgmma.mma_async.sync.aligned.m64n56k16.f32.f16.f16 {%0, %1, %2, %3, %4, %5, %6, %7, %8, %9, %10, %11, %12, %13, %14, %15, %16, %17, %18, %19, %20, %21, %22, %23, %24, %25, %26, %27}, ta, tb, p1, 1, 1, 0, 0;\n"
        "add.s64 tb, tb0, 3140;\n"
        "add.s64 ta, ta0, 3136;\n"
        "wgmma.mma_async.sync.aligned.m64n56k16.f32.f16.f16 {%0, %1, %2, %3, %4, %5, %6, %7, %8, %9, %10, %11, %12, %13, %14, %15, %16, %17, %18, %19, %20, %21, %22, %23, %24, %25, %26, %27}, ta, tb, p1, 1, 1, 0, 0;\n"
        "}\n"
        : "+f"(d[0]), "+f"(d[1]), "+f"(d[2]), "+f"(d[3]), "+f"(d[4]), "+f"(d[5]), "+f"(d[6]), "+f"(d[7]), "+f"(d[8]), "+f"(d[9]), "+f"(d[10]), "+f"(d[11]), "+f"(d[12]), "+f"(d[13]), "+f"(d[14]), "+f"(d[15]), "+f"(d[16]), "+f"(d[17]), "+f"(d[18]), "+f"(d[19]), "+f"(d[20]), "+f"(d[21]), "+f"(d[22]), "+f"(d[23]), "+f"(d[24]), "+f"(d[25]), "+f"(d[26]), "+f"(d[27])
        : "l"(descA), "n"(AOFF >> 4), "l"(descB), "n"(BOFF >> 4));
}

template <int AOFF, int BOFF>
__device__ __forceinline__ void mma_s0_f16(uint32_t (&d)[14], uint64_t descA, uint64_t descB) {
    asm volatile(
        "{\n"
        ".reg .pred p0, p1;\n"
        ".reg .b64 ta, ta0, tb, tb0;\n"
        "setp.ne.b32 p0, 0, 0;\n"
        "setp.eq.b32 p1, 0, 0;\n"
        "add.s64 tb0, %16, %17;\n"
        "add.s64 ta0, %14, %15;\n"
        "add.s64 tb, tb0, 4;\n"
        "add.s64 ta, ta0, 0;\n"
        "wgmma.mma_async.sync.aligned.m64n56k16.f16.f16.f16 {%0, %1, %2, %3, %4, %5, %6, %7, %8, %9, %10, %11, %12, %13}, ta, tb, p1, 1, 1, 0, 0;\n"
        "add.s64 tb, tb0, 1572;\n"
        "add.s64 ta, ta0, 1568;\n"
        "wgmma.mma_async.sync.aligned.m64n56k16.f16.f16.f16 {%0, %1, %2, %3, %4, %5, %6, %7, %8, %9, %10, %11, %12, %13}, ta, tb, p1, 1, 1, 0, 0;\n"
        "add.s64 tb, tb0, 3140;\n"
        "add.s64 ta, ta0, 3136;\n"
        "wgmma.mma_async.sync.aligned.m64n56k16.f16.f16.f16 {%0, %1, %2, %3, %4, %5, %6, %7, %8, %9, %10, %11, %12, %13}, ta, tb, p1, 1, 1, 0, 0;\n"
        "}\n"
        : "+r"(d[0]), "+r"(d[1]), "+r"(d[2]), "+r"(d[3]), "+r"(d[4]), "+r"(d[5]), "+r"(d[6]), "+r"(d[7]), "+r"(d[8]), "+r"(d[9]), "+r"(d[10]), "+r"(d[11]), "+r"(d[12]), "+r"(d[13])
        : "l"(descA), "n"(AOFF >> 4), "l"(descB), "n"(BOFF >> 4));
}

template <int AOFF, int BOFF>
__device__ __forceinline__ void mma_s1_f32(float (&d)[28], uint64_t descA, uint64_t descB) {
    asm volatile(
        "{\n"
        ".reg .pred p0, p1;\n"
        ".reg .b64 ta, ta0, tb, tb0;\n"
        "setp.ne.b32 p0, 0, 0;\n"
        "setp.eq.b32 p1, 0, 0;\n"
        "add.s64 tb0, %30, %31;\n"
        "add.s64 ta0, %28, %29;\n"
        "add.s64 tb, tb0, 6;\n"
        "add.s64 ta, ta0, 2;\n"
        "wgmma.mma_async.sync.aligned.m64n56k16.f32.f16.f16 {%0, %1, %2, %3, %4, %5, %6, %7, %8, %9, %10, %11, %12, %13, %14, %15, %16, %17, %18, %19, %20, %21, %22, %23, %24, %25, %26, %27}, ta, tb, p1, 1, 1, 0, 0;\n"
        "add.s64 tb, tb0, 1574;\n"
        "add.s64 ta, ta0, 1570;\n"
        "wgmma.mma_async.sync.aligned.m64n56k16.f32.f16.f16 {%0, %1, %2, %3, %4, %5, %6, %7, %8, %9, %10, %11, %12, %13, %14, %15, %16, %17, %18, %19, %20, %21, %22, %23, %24, %25, %26, %27}, ta, tb, p1, 1, 1, 0, 0;\n"
        "add.s64 tb, tb0, 3142;\n"
        "add.s64 ta, ta0, 3138;\n"
        "wgmma.mma_async.sync.aligned.m64n56k16.f32.f16.f16 {%0, %1, %2, %3, %4, %5, %6, %7, %8, %9, %10, %11, %12, %13, %14, %15, %16, %17, %18, %19, %20, %21, %22, %23, %24, %25, %26, %27}, ta, tb, p1, 1, 1, 0, 0;\n"
        "}\n"
        : "+f"(d[0]), "+f"(d[1]), "+f"(d[2]), "+f"(d[3]), "+f"(d[4]), "+f"(d[5]), "+f"(d[6]), "+f"(d[7]), "+f"(d[8]), "+f"(d[9]), "+f"(d[10]), "+f"(d[11]), "+f"(d[12]), "+f"(d[13]), "+f"(d[14]), "+f"(d[15]), "+f"(d[16]), "+f"(d[17]), "+f"(d[18]), "+f"(d[19]), "+f"(d[20]), "+f"(d[21]), "+f"(d[22]), "+f"(d[23]), "+f"(d[24]), "+f"(d[25]), "+f"(d[26]), "+f"(d[27])
        : "l"(descA), "n"(AOFF >> 4), "l"(descB), "n"(BOFF >> 4));
}

template <int AOFF, int BOFF>
__device__ __forceinline__ void mma_s1_f16(uint32_t (&d)[14], uint64_t descA, uint64_t descB) {
    asm volatile(
        "{\n"
        ".reg .pred p0, p1;\n"
        ".reg .b64 ta, ta0, tb, tb0;\n"
        "setp.ne.b32 p0, 0, 0;\n"
        "setp.eq.b32 p1, 0, 0;\n"
        "add.s64 tb0, %16, %17;\n"
        "add.s64 ta0, %14, %15;\n"
        "add.s64 tb, tb0, 6;\n"
        "add.s64 ta, ta0, 2;\n"
        "wgmma.mma_async.sync.aligned.m64n56k16.f16.f16.f16 {%0, %1, %2, %3, %4, %5, %6, %7, %8, %9, %10, %11, %12, %13}, ta, tb, p1, 1, 1, 0, 0;\n"
        "add.s64 tb, tb0, 1574;\n"
        "add.s64 ta, ta0, 1570;\n"
        "wgmma.mma_async.sync.aligned.m64n56k16.f16.f16.f16 {%0, %1, %2, %3, %4, %5, %6, %7, %8, %9, %10, %11, %12, %13}, ta, tb, p1, 1, 1, 0, 0;\n"
        "add.s64 tb, tb0, 3142;\n"
        "add.s64 ta, ta0, 3138;\n"
        "wgmma.mma_async.sync.aligned.m64n56k16.f16.f16.f16 {%0, %1, %2, %3, %4, %5, %6, %7, %8, %9, %10, %11, %12, %13}, ta, tb, p1, 1, 1, 0, 0;\n"
        "}\n"
        : "+r"(d[0]), "+r"(d[1]), "+r"(d[2]), "+r"(d[3]), "+r"(d[4]), "+r"(d[5]), "+r"(d[6]), "+r"(d[7]), "+r"(d[8]), "+r"(d[9]), "+r"(d[10]), "+r"(d[11]), "+r"(d[12]), "+r"(d[13])
        : "l"(descA), "n"(AOFF >> 4), "l"(descB), "n"(BOFF >> 4));
}

template <int BOFF, int AOFF, int NA>
__device__ __forceinline__ void mma_sr0(uint32_t (&d)[14], const uint32_t (&a)[NA][4], uint64_t descB) {
    asm volatile(
        "{\n"
        ".reg .pred p0, p1;\n"
        ".reg .b64 ta, ta0, tb, tb0;\n"
        "setp.ne.b32 p0, 0, 0;\n"
        "setp.eq.b32 p1, 0, 0;\n"
        "add.s64 tb0, %26, %27;\n"
        "add.s64 tb, tb0, 4;\n"
        "wgmma.mma_async.sync.aligned.m64n56k16.f16.f16.f16 {%0, %1, %2, %3, %4, %5, %6, %7, %8, %9, %10, %11, %12, %13}, {%14, %15, %16, %17}, tb, p1, 1, 1, 0;\n"
        "add.s64 tb, tb0, 1572;\n"
        "wgmma.mma_async.sync.aligned.m64n56k16.f16.f16.f16 {%0, %1, %2, %3, %4, %5, %6, %7, %8, %9, %10, %11, %12, %13}, {%18, %19, %20, %21}, tb, p1, 1, 1, 0;\n"
        "add.s64 tb, tb0, 3140;\n"
        "wgmma.mma_async.sync.aligned.m64n56k16.f16.f16.f16 {%0, %1, %2, %3, %4, %5, %6, %7, %8, %9, %10, %11, %12, %13}, {%22, %23, %24, %25}, tb, p1, 1, 1, 0;\n"
        "}\n"
        : "+r"(d[0]), "+r"(d[1]), "+r"(d[2]), "+r"(d[3]), "+r"(d[4]), "+r"(d[5]), "+r"(d[6]), "+r"(d[7]), "+r"(d[8]), "+r"(d[9]), "+r"(d[10]), "+r"(d[11]), "+r"(d[12]), "+r"(d[13])
        : "r"(a[AOFF + 0][0]), "r"(a[AOFF + 0][1]), "r"(a[AOFF + 0][2]), "r"(a[AOFF + 0][3]), "r"(a[AOFF + 1][0]), "r"(a[AOFF + 1][1]), "r"(a[AOFF + 1][2]), "r"(a[AOFF + 1][3]), "r"(a[AOFF + 2][0]), "r"(a[AOFF + 2][1]), "r"(a[AOFF + 2][2]), "r"(a[AOFF + 2][3]), "l"(descB), "n"(BOFF >> 4));
}

template <int BOFF, int AOFF, int NA>
__device__ __forceinline__ void mma_sr1(uint32_t (&d)[14], const uint32_t (&a)[NA][4], uint64_t descB) {
    asm volatile(
        "{\n"
        ".reg .pred p0, p1;\n"
        ".reg .b64 ta, ta0, tb, tb0;\n"
        "setp.ne.b32 p0, 0, 0;\n"
        "setp.eq.b32 p1, 0, 0;\n"
        "add.s64 tb0, %26, %27;\n"
        "add.s64 tb, tb0, 6;\n"
        "wgmma.mma_async.sync.aligned.m64n56k16.f16.f16.f16 {%0, %1, %2, %3, %4, %5, %6, %7, %8, %9, %10, %11, %12, %13}, {%14, %15, %16, %17}, tb, p1, 1, 1, 0;\n"
        "add.s64 tb, tb0, 1574;\n"
        "wgmma.mma_async.sync.aligned.m64n56k16.f16.f16.f16 {%0, %1, %2, %3, %4, %5, %6, %7, %8, %9, %10, %11, %12, %13}, {%18, %19, %20, %21}, tb, p1, 1, 1, 0;\n"
        "add.s64 tb, tb0, 3142;\n"
        "wgmma.mma_async.sync.aligned.m64n56k16.f16.f16.f16 {%0, %1, %2, %3, %4, %5, %6, %7, %8, %9, %10, %11, %12, %13}, {%22, %23, %24, %25}, tb, p1, 1, 1, 0;\n"
        "}\n"
        : "+r"(d[0]), "+r"(d[1]), "+r"(d[2]), "+r"(d[3]), "+r"(d[4]), "+r"(d[5]), "+r"(d[6]), "+r"(d[7]), "+r"(d[8]), "+r"(d[9]), "+r"(d[10]), "+r"(d[11]), "+r"(d[12]), "+r"(d[13])
        : "r"(a[AOFF + 0][0]), "r"(a[AOFF + 0][1]), "r"(a[AOFF + 0][2]), "r"(a[AOFF + 0][3]), "r"(a[AOFF + 1][0]), "r"(a[AOFF + 1][1]), "r"(a[AOFF + 1][2]), "r"(a[AOFF + 1][3]), "r"(a[AOFF + 2][0]), "r"(a[AOFF + 2][1]), "r"(a[AOFF + 2][2]), "r"(a[AOFF + 2][3]), "l"(descB), "n"(BOFF >> 4));
}

template <int BOFF, int AOFF, int NA>
__device__ __forceinline__ void mma_pv(uint32_t (&d)[14], const uint32_t (&a)[NA][4], uint64_t descB) {
    asm volatile(
        "{\n"
        ".reg .pred p0, p1;\n"
        ".reg .b64 ta, ta0, tb, tb0;\n"
        "setp.ne.b32 p0, 0, 0;\n"
        "setp.eq.b32 p1, 0, 0;\n"
        "add.s64 tb0, %30, %31;\n"
        "add.s64 tb, tb0, 0;\n"
        "wgmma.mma_async.sync.aligned.m64n56k16.f16.f16.f16 {%0, %1, %2, %3, %4, %5, %6, %7, %8, %9, %10, %11, %12, %13}, {%14, %15, %16, %17}, tb, p0, 1, 1, 1;\n"
        "add.s64 tb, tb0, 16;\n"
        "wgmma.mma_async.sync.aligned.m64n56k16.f16.f16.f16 {%0, %1, %2, %3, %4, %5, %6, %7, %8, %9, %10, %11, %12, %13}, {%18, %19, %20, %21}, tb, p1, 1, 1, 1;\n"
        "add.s64 tb, tb0, 32;\n"
        "wgmma.mma_async.sync.aligned.m64n56k16.f16.f16.f16 {%0, %1, %2, %3, %4, %5, %6, %7, %8, %9, %10, %11, %12, %13}, {%22, %23, %24, %25}, tb, p1, 1, 1, 1;\n"
        "add.s64 tb, tb0, 48;\n"
        "wgmma.mma_async.sync.aligned.m64n56k16.f16.f16.f16 {%0, %1, %2, %3, %4, %5, %6, %7, %8, %9, %10, %11, %12, %13}, {%26, %27, %28, %29}, tb, p1, 1, 1, 1;\n"
        "}\n"
        : "=r"(d[0]), "=r"(d[1]), "=r"(d[2]), "=r"(d[3]), "=r"(d[4]), "=r"(d[5]), "=r"(d[6]), "=r"(d[7]), "=r"(d[8]), "=r"(d[9]), "=r"(d[10]), "=r"(d[11]), "=r"(d[12]), "=r"(d[13])
        : "r"(a[AOFF + 0][0]), "r"(a[AOFF + 0][1]), "r"(a[AOFF + 0][2]), "r"(a[AOFF + 0][3]), "r"(a[AOFF + 1][0]), "r"(a[AOFF + 1][1]), "r"(a[AOFF + 1][2]), "r"(a[AOFF + 1][3]), "r"(a[AOFF + 2][0]), "r"(a[AOFF + 2][1]), "r"(a[AOFF + 2][2]), "r"(a[AOFF + 2][3]), "r"(a[AOFF + 3][0]), "r"(a[AOFF + 3][1]), "r"(a[AOFF + 3][2]), "r"(a[AOFF + 3][3]), "l"(descB), "n"(BOFF >> 4));
}

template <int AOFF, int BOFF>
__device__ __forceinline__ void mma_s1step(uint32_t (&d)[14], uint64_t descA, uint64_t descB) {
    asm volatile(
        "{\n"
        ".reg .pred p0, p1;\n"
        ".reg .b64 ta, ta0, tb, tb0;\n"
        "setp.ne.b32 p0, 0, 0;\n"
        "setp.eq.b32 p1, 0, 0;\n"
        "add.s64 tb0, %16, %17;\n"
        "add.s64 ta0, %14, %15;\n"
        "add.s64 tb, tb0, 0;\n"
        "add.s64 ta, ta0, 0;\n"
        "wgmma.mma_async.sync.aligned.m64n56k16.f16.f16.f16 {%0, %1, %2, %3, %4, %5, %6, %7, %8, %9, %10, %11, %12, %13}, ta, tb, p1, 1, 1, 0, 0;\n"
        "}\n"
        : "+r"(d[0]), "+r"(d[1]), "+r"(d[2]), "+r"(d[3]), "+r"(d[4]), "+r"(d[5]), "+r"(d[6]), "+r"(d[7]), "+r"(d[8]), "+r"(d[9]), "+r"(d[10]), "+r"(d[11]), "+r"(d[12]), "+r"(d[13])
        : "l"(descA), "n"(AOFF >> 4), "l"(descB), "n"(BOFF >> 4));
}

template <int BOFF, int AOFF, int NA>
__device__ __forceinline__ void mma_pv1f(uint32_t (&d)[14], const uint32_t (&a)[NA][4], uint64_t descB) {
    asm volatile(
        "{\n"
        ".reg .pred p0, p1;\n"
        ".reg .b64 ta, ta0, tb, tb0;\n"
        "setp.ne.b32 p0, 0, 0;\n"
        "setp.eq.b32 p1, 0, 0;\n"
        "add.s64 tb0, %18, %19;\n"
        "add.s64 tb, tb0, 0;\n"
        "wgmma.mma_async.sync.aligned.m64n56k16.f16.f16.f16 {%0, %1, %2, %3, %4, %5, %6, %7, %8, %9, %10, %11, %12, %13}, {%14, %15, %16, %17}, tb, p0, 1, 1, 1;\n"
        "}\n"
        : "=r"(d[0]), "=r"(d[1]), "=r"(d[2]), "=r"(d[3]), "=r"(d[4]), "=r"(d[5]), "=r"(d[6]), "=r"(d[7]), "=r"(d[8]), "=r"(d[9]), "=r"(d[10]), "=r"(d[11]), "=r"(d[12]), "=r"(d[13])
        : "r"(a[AOFF + 0][0]), "r"(a[AOFF + 0][1]), "r"(a[AOFF + 0][2]), "r"(a[AOFF + 0][3]), "l"(descB), "n"(BOFF >> 4));
}

template <int BOFF, int AOFF, int NA>
__device__ __forceinline__ void mma_pv1n(uint32_t (&d)[14], const uint32_t (&a)[NA][4], uint64_t descB) {
    asm volatile(
        "{\n"
        ".reg .pred p0, p1;\n"
        ".reg .b64 ta, ta0, tb, tb0;\n"
        "setp.ne.b32 p0, 0, 0;\n"
        "setp.eq.b32 p1, 0, 0;\n"
        "add.s64 tb0, %18, %19;\n"
        "add.s64 tb, tb0, 0;\n"
        "wgmma.mma_async.sync.aligned.m64n56k16.f16.f16.f16 {%0, %1, %2, %3, %4, %5, %6, %7, %8, %9, %10, %11, %12, %13}, {%14, %15, %16, %17}, tb, p1, 1, 1, 1;\n"
        "}\n"
        : "+r"(d[0]), "+r"(d[1]), "+r"(d[2]), "+r"(d[3]), "+r"(d[4]), "+r"(d[5]), "+r"(d[6]), "+r"(d[7]), "+r"(d[8]), "+r"(d[9]), "+r"(d[10]), "+r"(d[11]), "+r"(d[12]), "+r"(d[13])
        : "r"(a[AOFF + 0][0]), "r"(a[AOFF + 0][1]), "r"(a[AOFF + 0][2]), "r"(a[AOFF + 0][3]), "l"(descB), "n"(BOFF >> 4));
}

template <int BOFF, int AOFF, int NA>
__device__ __forceinline__ void mma_pv1f(uint32_t (&d)[12], const uint32_t (&a)[NA][4], uint64_t descB) {
    asm volatile(
        "{\n"
        ".reg .pred p0, p1;\n"
        ".reg .b64 ta, ta0, tb, tb0;\n"
        "setp.ne.b32 p0, 0, 0;\n"
        "setp.eq.b32 p1, 0, 0;\n"
        "add.s64 tb0, %16, %17;\n"
        "add.s64 tb, tb0, 0;\n"
        "wgmma.mma_async.sync.aligned.m64n48k16.f16.f16.f16 {%0, %1, %2, %3, %4, %5, %6, %7, %8, %9, %10, %11}, {%12, %13, %14, %15}, tb, p0, 1, 1, 1;\n"
        "}\n"
        : "=r"(d[0]), "=r"(d[1]), "=r"(d[2]), "=r"(d[3]), "=r"(d[4]), "=r"(d[5]), "=r"(d[6]), "=r"(d[7]), "=r"(d[8]), "=r"(d[9]), "=r"(d[10]), "=r"(d[11])
        : "r"(a[AOFF + 0][0]), "r"(a[AOFF + 0][1]), "r"(a[AOFF + 0][2]), "r"(a[AOFF + 0][3]), "l"(descB), "n"(BOFF >> 4));
}

template <int BOFF, int AOFF, int NA>
__device__ __forceinline__ void mma_pv1n(uint32_t (&d)[12], const uint32_t (&a)[NA][4], uint64_t descB) {
    asm volatile(
        "{\n"
        ".reg .pred p0, p1;\n"
        ".reg .b64 ta, ta0, tb, tb0;\n"
        "setp.ne.b32 p0, 0, 0;\n"
        "setp.eq.b32 p1, 0, 0;\n"
        "add.s64 tb0, %16, %17;\n"
        "add.s64 tb, tb0, 0;\n"
        "wgmma.mma_async.sync.aligned.m64n48k16.f16.f16.f16 {%0, %1, %2, %3, %4, %5, %6, %7, %8, %9, %10, %11}, {%12, %13, %14, %15}, tb, p1, 1, 1, 1;\n"
        "}\n"
        : "+r"(d[0]), "+r"(d[1]), "+r"(d[2]), "+r"(d[3]), "+r"(d[4]), "+r"(d[5]), "+r"(d[6]), "+r"(d[7]), "+r"(d[8]), "+r"(d[9]), "+r"(d[10]), "+r"(d[11])
        : "r"(a[AOFF + 0][0]), "r"(a[AOFF + 0][1]), "r"(a[AOFF + 0][2]), "r"(a[AOFF + 0][3]), "l"(descB), "n"(BOFF >> 4));
}

template <int BOFF, int AOFF, int NA>
__device__ __forceinline__ void mma_pvn(uint32_t (&d)[12], const uint32_t (&a)[NA][4], uint64_t descB) {
    asm volatile(
        "{\n"
        ".reg .pred p0, p1;\n"
        ".reg .b64 ta, ta0, tb, tb0;\n"
        "setp.ne.b32 p0, 0, 0;\n"
        "setp.eq.b32 p1, 0, 0;\n"
        "add.s64 tb0, %28, %29;\n"
        "add.s64 tb, tb0, 0;\n"
        "wgmma.mma_async.sync.aligned.m64n48k16.f16.f16.f16 {%0, %1, %2, %3, %4, %5, %6, %7, %8, %9, %10, %11}, {%12, %13, %14, %15}, tb, p0, 1, 1, 1;\n"
        "add.s64 tb, tb0, 16;\n"
        "wgmma.mma_async.sync.aligned.m64n48k16.f16.f16.f16 {%0, %1, %2, %3, %4, %5, %6, %7, %8, %9, %10, %11}, {%16, %17, %18, %19}, tb, p1, 1, 1, 1;\n"
        "add.s64 tb, tb0, 32;\n"
        "wgmma.mma_async.sync.aligned.m64n48k16.f16.f16.f16 {%0, %1, %2, %3, %4, %5, %6, %7, %8, %9, %10, %11}, {%20, %21, %22, %23}, tb, p1, 1, 1, 1;\n"
        "add.s64 tb, tb0, 48;\n"
        "wgmma.mma_async.sync.aligned.m64n48k16.f16.f16.f16 {%0, %1, %2, %3, %4, %5, %6, %7, %8, %9, %10, %11}, {%24, %25, %26, %27}, tb, p1, 1, 1, 1;\n"
        "}\n"
        : "=r"(d[0]), "=r"(d[1]), "=r"(d[2]), "=r"(d[3]), "=r"(d[4]), "=r"(d[5]), "=r"(d[6]), "=r"(d[7]), "=r"(d[8]), "=r"(d[9]), "=r"(d[10]), "=r"(d[11])
        : "r"(a[AOFF + 0][0]), "r"(a[AOFF + 0][1]), "r"(a[AOFF + 0][2]), "r"(a[AOFF + 0][3]), "r"(a[AOFF + 1][0]), "r"(a[AOFF + 1][1]), "r"(a[AOFF + 1][2]), "r"(a[AOFF + 1][3]), "r"(a[AOFF + 2][0]), "r"(a[AOFF + 2][1]), "r"(a[AOFF + 2][2]), "r"(a[AOFF + 2][3]), "r"(a[AOFF + 3][0]), "r"(a[AOFF + 3][1]), "r"(a[AOFF + 3][2]), "r"(a[AOFF + 3][3]), "l"(descB), "n"(BOFF >> 4));
}

template <int BOFF, int AOFF, int NA>
__device__ __forceinline__ void mma_pv3(uint32_t (&d)[14], const uint32_t (&a)[NA][4], uint64_t descB) {
    asm volatile(
        "{\n"
        ".reg .pred p0, p1;\n"
        ".reg .b64 ta, ta0, tb, tb0;\n"
        "setp.ne.b32 p0, 0, 0;\n"
        "setp.eq.b32 p1, 0, 0;\n"
        "add.s64 tb0, %26, %27;\n"
        "add.s64 tb, tb0, 0;\n"
        "wgmma.mma_async.sync.aligned.m64n56k16.f16.f16.f16 {%0, %1, %2, %3, %4, %5, %6, %7, %8, %9, %10, %11, %12, %13}, {%14, %15, %16, %17}, tb, p1, 1, 1, 1;\n"
        "add.s64 tb, tb0, 16;\n"
        "wgmma.mma_async.sync.aligned.m64n56k16.f16.f16.f16 {%0, %1, %2, %3, %4, %5, %6, %7, %8, %9, %10, %11, %12, %13}, {%18, %19, %20, %21}, tb, p1, 1, 1, 1;\n"
        "add.s64 tb, tb0, 32;\n"
        "wgmma.mma_async.sync.aligned.m64n56k16.f16.f16.f16 {%0, %1, %2, %3, %4, %5, %6, %7, %8, %9, %10, %11, %12, %13}, {%22, %23, %24, %25}, tb, p1, 1, 1, 1;\n"
        "}\n"
        : "+r"(d[0]), "+r"(d[1]), "+r"(d[2]), "+r"(d[3]), "+r"(d[4]), "+r"(d[5]), "+r"(d[6]), "+r"(d[7]), "+r"(d[8]), "+r"(d[9]), "+r"(d[10]), "+r"(d[11]), "+r"(d[12]), "+r"(d[13])
        : "r"(a[AOFF + 0][0]), "r"(a[AOFF + 0][1]), "r"(a[AOFF + 0][2]), "r"(a[AOFF + 0][3]), "r"(a[AOFF + 1][0]), "r"(a[AOFF + 1][1]), "r"(a[AOFF + 1][2]), "r"(a[AOFF + 1][3]), "r"(a[AOFF + 2][0]), "r"(a[AOFF + 2][1]), "r"(a[AOFF + 2][2]), "r"(a[AOFF + 2][3]), "l"(descB), "n"(BOFF >> 4));
}

template <int AOFF, int BOFF>
__device__ __forceinline__ void mma_proj(float (&d)[96], uint64_t descA, uint64_t descB) {
    asm volatile(
        "{\n"
        ".reg .pred p0, p1;\n"
        ".reg .b64 ta, ta0, tb, tb0;\n"
        "setp.ne.b32 p0, 0, 0;\n"
        "setp.eq.b32 p1, 0, 0;\n"
        "add.s64 tb0, %98, %99;\n"
        "add.s64 ta0, %96, %97;\n"
        "add.s64 tb, tb0, 0;\n"
        "add.s64 ta, ta0, 0;\n"
        "wgmma.mma_async.sync.aligned.m64n192k16.f32.f16.f16 {%0, %1, %2, %3, %4, %5, %6, %7, %8, %9, %10, %11, %12, %13, %14, %15, %16, %17, %18, %19, %20, %21, %22, %23, %24, %25, %26, %27, %28, %29, %30, %31, %32, %33, %34, %35, %36, %37, %38, %39, %40, %41, %42, %43, %44, %45, %46, %47, %48, %49, %50, %51, %52, %53, %54, %55, %56, %57, %58, %59, %60, %61, %62, %63, %64, %65, %66, %67, %68, %69, %70, %71, %72, %73, %74, %75, %76, %77, %78, %79, %80, %81, %82, %83, %84, %85, %86, %87, %88, %89, %90, %91, %92, %93, %94, %95}, ta, tb, p0, 1, 1, 0, 1;\n"
        "add.s64 tb, tb0, 64;\n"
        "add.s64 ta, ta0, 2;\n"
        "wgmma.mma_async.sync.aligned.m64n192k16.f32.f16.f16 {%0, %1, %2, %3, %4, %5, %6, %7, %8, %9, %10, %11, %12, %13, %14, %15, %16, %17, %18, %19, %20, %21, %22, %23, %24, %25, %26, %27, %28, %29, %30, %31, %32, %33, %34, %35, %36, %37, %38, %39, %40, %41, %42, %43, %44, %45, %46, %47, %48, %49, %50, %51, %52, %53, %54, %55, %56, %57, %58, %59, %60, %61, %62, %63, %64, %65, %66, %67, %68, %69, %70, %71, %72, %73, %74, %75, %76, %77, %78, %79, %80, %81, %82, %83, %84, %85, %86, %87, %88, %89, %90, %91, %92, %93, %94, %95}, ta, tb, p1, 1, 1, 0, 1;\n"
        "add.s64 tb, tb0, 128;\n"
        "add.s64 ta, ta0, 4;\n"
        "wgmma.mma_async.sync.aligned.m64n192k16.f32.f16.f16 {%0, %1, %2, %3, %4, %5, %6, %7, %8, %9, %10, %11, %12, %13, %14, %15, %16, %17, %18, %19, %20, %21, %22, %23, %24, %25, %26, %27, %28, %29, %30, %31, %32, %33, %34, %35, %36, %37, %38, %39, %40, %41, %42, %43, %44, %45, %46, %47, %48, %49, %50, %51, %52, %53, %54, %55, %56, %57, %58, %59, %60, %61, %62, %63, %64, %65, %66, %67, %68, %69, %70, %71, %72, %73, %74, %75, %76, %77, %78, %79, %80, %81, %82, %83, %84, %85, %86, %87, %88, %89, %90, %91, %92, %93, %94, %95}, ta, tb, p1, 1, 1, 0, 1;\n"
        "add.s64 tb, tb0, 192;\n"
        "add.s64 ta, ta0, 6;\n"
        "wgmma.mma_async.sync.aligned.m64n192k16.f32.f16.f16 {%0, %1, %2, %3, %4, %5, %6, %7, %8, %9, %10, %11, %12, %13, %14, %15, %16, %17, %18, %19, %20, %21, %22, %23, %24, %25, %26, %27, %28, %29, %30, %31, %32, %33, %34, %35, %36, %37, %38, %39, %40, %41, %42, %43, %44, %45, %46, %47, %48, %49, %50, %51, %52, %53, %54, %55, %56, %57, %58, %59, %60, %61, %62, %63, %64, %65, %66, %67, %68, %69, %70, %71, %72, %73, %74, %75, %76, %77, %78, %79, %80, %81, %82, %83, %84, %85, %86, %87, %88, %89, %90, %91, %92, %93, %94, %95}, ta, tb, p1, 1, 1, 0, 1;\n"
        "add.s64 tb, tb0, 256;\n"
        "add.s64 ta, ta0, 512;\n"
        "wgmma.mma_async.sync.aligned.m64n192k16.f32.f16.f16 {%0, %1, %2, %3, %4, %5, %6, %7, %8, %9, %10, %11, %12, %13, %14, %15, %16, %17, %18, %19, %20, %21, %22, %23, %24, %25, %26, %27, %28, %29, %30, %31, %32, %33, %34, %35, %36, %37, %38, %39, %40, %41, %42, %43, %44, %45, %46, %47, %48, %49, %50, %51, %52, %53, %54, %55, %56, %57, %58, %59, %60, %61, %62, %63, %64, %65, %66, %67, %68, %69, %70, %71, %72, %73, %74, %75, %76, %77, %78, %79, %80, %81, %82, %83, %84, %85, %86, %87, %88, %89, %90, %91, %92, %93, %94, %95}, ta, tb, p1, 1, 1, 0, 1;\n"
        "add.s64 tb, tb0, 320;\n"
        "add.s64 ta, ta0, 514;\n"
        "wgmma.mma_async.sync.aligned.m64n192k16.f32.f16.f16 {%0, %1, %2, %3, %4, %5, %6, %7, %8, %9, %10, %11, %12, %13, %14, %15, %16, %17, %18, %19, %20, %21, %22, %23, %24, %25, %26, %27, %28, %29, %30, %31, %32, %33, %34, %35, %36, %37, %38, %39, %40, %41, %42, %43, %44, %45, %46, %47, %48, %49, %50, %51, %52, %53, %54, %55, %56, %57, %58, %59, %60, %61, %62, %63, %64, %65, %66, %67, %68, %69, %70, %71, %72, %73, %74, %75, %76, %77, %78, %79, %80, %81, %82, %83, %84, %85, %86, %87, %88, %89, %90, %91, %92, %93, %94, %95}, ta, tb, p1, 1, 1, 0, 1;\n"
        "add.s64 tb, tb0, 384;\n"
        "add.s64 ta, ta0, 516;\n"
        "wgmma.mma_async.sync.aligned.m64n192k16.f32.f16.f16 {%0, %1, %2, %3, %4, %5, %6, %7, %8, %9, %10, %11, %12, %13, %14, %15, %16, %17, %18, %19, %20, %21, %22, %23, %24, %25, %26, %27, %28, %29, %30, %31, %32, %33, %34, %35, %36, %37, %38, %39, %40, %41, %42, %43, %44, %45, %46, %47, %48, %49, %50, %51, %52, %53, %54, %55, %56, %57, %58, %59, %60, %61, %62, %63, %64, %65, %66, %67, %68, %69, %70, %71, %72, %73, %74, %75, %76, %77, %78, %79, %80, %81, %82, %83, %84, %85, %86, %87, %88, %89, %90, %91, %92, %93, %94, %95}, ta, tb, p1, 1, 1, 0, 1;\n"
        "add.s64 tb, tb0, 448;\n"
        "add.s64 ta, ta0, 518;\n"
        "wgmma.mma_async.sync.aligned.m64n192k16.f32.f16.f16 {%0, %1, %2, %3, %4, %5, %6, %7, %8, %9, %10, %11, %12, %13, %14, %15, %16, %17, %18, %19, %20, %21, %22, %23, %24, %25, %26, %27, %28, %29, %30, %31, %32, %33, %34, %35, %36, %37, %38, %39, %40, %41, %42, %43, %44, %45, %46, %47, %48, %49, %50, %51, %52, %53, %54, %55, %56, %57, %58, %59, %60, %61, %62, %63, %64, %65, %66, %67, %68, %69, %70, %71, %72, %73, %74, %75, %76, %77, %78, %79, %80, %81, %82, %83, %84, %85, %86, %87, %88, %89, %90, %91, %92, %93, %94, %95}, ta, tb, p1, 1, 1, 0, 1;\n"
        "add.s64 tb, tb0, 512;\n"
        "add.s64 ta, ta0, 1024;\n"
        "wgmma.mma_async.sync.aligned.m64n192k16.f32.f16.f16 {%0, %1, %2, %3, %4, %5, %6, %7, %8, %9, %10, %11, %12, %13, %14, %15, %16, %17, %18, %19, %20, %21, %22, %23, %24, %25, %26, %27, %28, %29, %30, %31, %32, %33, %34, %35, %36, %37, %38, %39, %40, %41, %42, %43, %44, %45, %46, %47, %48, %49, %50, %51, %52, %53, %54, %55, %56, %57, %58, %59, %60, %61, %62, %63, %64, %65, %66, %67, %68, %69, %70, %71, %72, %73, %74, %75, %76, %77, %78, %79, %80, %81, %82, %83, %84, %85, %86, %87, %88, %89, %90, %91, %92, %93, %94, %95}, ta, tb, p1, 1, 1, 0, 1;\n"
        "add.s64 tb, tb0, 576;\n"
        "add.s64 ta, ta0, 1026;\n"
        "wgmma.mma_async.sync.aligned.m64n192k16.f32.f16.f16 {%0, %1, %2, %3, %4, %5, %6, %7, %8, %9, %10, %11, %12, %13, %14, %15, %16, %17, %18, %19, %20, %21, %22, %23, %24, %25, %26, %27, %28, %29, %30, %31, %32, %33, %34, %35, %36, %37, %38, %39, %40, %41, %42, %43, %44, %45, %46, %47, %48, %49, %50, %51, %52, %53, %54, %55, %56, %57, %58, %59, %60, %61, %62, %63, %64, %65, %66, %67, %68, %69, %70, %71, %72, %73, %74, %75, %76, %77, %78, %79, %80, %81, %82, %83, %84, %85, %86, %87, %88, %89, %90, %91, %92, %93, %94, %95}, ta, tb, p1, 1, 1, 0, 1;\n"
        "add.s64 tb, tb0, 640;\n"
        "add.s64 ta, ta0, 1028;\n"
        "wgmma.mma_async.sync.aligned.m64n192k16.f32.f16.f16 {%0, %1, %2, %3, %4, %5, %6, %7, %8, %9, %10, %11, %12, %13, %14, %15, %16, %17, %18, %19, %20, %21, %22, %23, %24, %25, %26, %27, %28, %29, %30, %31, %32, %33, %34, %35, %36, %37, %38, %39, %40, %41, %42, %43, %44, %45, %46, %47, %48, %49, %50, %51, %52, %53, %54, %55, %56, %57, %58, %59, %60, %61, %62, %63, %64, %65, %66, %67, %68, %69, %70, %71, %72, %73, %74, %75, %76, %77, %78, %79, %80, %81, %82, %83, %84, %85, %86, %87, %88, %89, %90, %91, %92, %93, %94, %95}, ta, tb, p1, 1, 1, 0, 1;\n"
        "add.s64 tb, tb0, 704;\n"
        "add.s64 ta, ta0, 1030;\n"
        "wgmma.mma_async.sync.aligned.m64n192k16.f32.f16.f16 {%0, %1, %2, %3, %4, %5, %6, %7, %8, %9, %10, %11, %12, %13, %14, %15, %16, %17, %18, %19, %20, %21, %22, %23, %24, %25, %26, %27, %28, %29, %30, %31, %32, %33, %34, %35, %36, %37, %38, %39, %40, %41, %42, %43, %44, %45, %46, %47, %48, %49, %50, %51, %52, %53, %54, %55, %56, %57, %58, %59, %60, %61, %62, %63, %64, %65, %66, %67, %68, %69, %70, %71, %72, %73, %74, %75, %76, %77, %78, %79, %80, %81, %82, %83, %84, %85, %86, %87, %88, %89, %90, %91, %92, %93, %94, %95}, ta, tb, p1, 1, 1, 0, 1;\n"
        "}\n"
        : "+f"(d[0]), "+f"(d[1]), "+f"(d[2]), "+f"(d[3]), "+f"(d[4]), "+f"(d[5]), "+f"(d[6]), "+f"(d[7]), "+f"(d[8]), "+f"(d[9]), "+f"(d[10]), "+f"(d[11]), "+f"(d[12]), "+f"(d[13]), "+f"(d[14]), "+f"(d[15]), "+f"(d[16]), "+f"(d[17]), "+f"(d[18]), "+f"(d[19]), "+f"(d[20]), "+f"(d[21]), "+f"(d[22]), "+f"(d[23]), "+f"(d[24]), "+f"(d[25]), "+f"(d[26]), "+f"(d[27]), "+f"(d[28]), "+f"(d[29]), "+f"(d[30]), "+f"(d[31]), "+f"(d[32]), "+f"(d[33]), "+f"(d[34]), "+f"(d[35]), "+f"(d[36]), "+f"(d[37]), "+f"(d[38]), "+f"(d[39]), "+f"(d[40]), "+f"(d[41]), "+f"(d[42]), "+f"(d[43]), "+f"(d[44]), "+f"(d[45]), "+f"(d[46]), "+f"(d[47]), "+f"(d[48]), "+f"(d[49]), "+f"(d[50]), "+f"(d[51]), "+f"(d[52]), "+f"(d[53]), "+f"(d[54]), "+f"(d[55]), "+f"(d[56]), "+f"(d[57]), "+f"(d[58]), "+f"(d[59]), "+f"(d[60]), "+f"(d[61]), "+f"(d[62]), "+f"(d[63]), "+f"(d[64]), "+f"(d[65]), "+f"(d[66]), "+f"(d[67]), "+f"(d[68]), "+f"(d[69]), "+f"(d[70]), "+f"(d[71]), "+f"(d[72]), "+f"(d[73]), "+f"(d[74]), "+f"(d[75]), "+f"(d[76]), "+f"(d[77]), "+f"(d[78]), "+f"(d[79]), "+f"(d[80]), "+f"(d[81]), "+f"(d[82]), "+f"(d[83]), "+f"(d[84]), "+f"(d[85]), "+f"(d[86]), "+f"(d[87]), "+f"(d[88]), "+f"(d[89]), "+f"(d[90]), "+f"(d[91]), "+f"(d[92]), "+f"(d[93]), "+f"(d[94]), "+f"(d[95])
        : "l"(descA), "n"(AOFF >> 4), "l"(descB), "n"(BOFF >> 4));
}

template <int AOFF, int BOFF>
__device__ __forceinline__ void mma_projh(uint32_t (&d)[48], uint64_t descA, uint64_t descB) {
    asm volatile(
        "{\n"
        ".reg .pred p0, p1;\n"
        ".reg .b64 ta, ta0, tb, tb0;\n"
        "setp.ne.b32 p0, 0, 0;\n"
        "setp.eq.b32 p1, 0, 0;\n"
        "add.s64 tb0, %50, %51;\n"
        "add.s64 ta0, %48, %49;\n"
        "add.s64 tb, tb0, 0;\n"
        "add.s64 ta, ta0, 0;\n"
        "wgmma.mma_async.sync.aligned.m64n192k16.f16.f16.f16 {%0, %1, %2, %3, %4, %5, %6, %7, %8, %9, %10, %11, %12, %13, %14, %15, %16, %17, %18, %19, %20, %21, %22, %23, %24, %25, %26, %27, %28, %29, %30, %31, %32, %33, %34, %35, %36, %37, %38, %39, %40, %41, %42, %43, %44, %45, %46, %47}, ta, tb, p0, 1, 1, 0, 1;\n"
        "add.s64 tb, tb0, 64;\n"
        "add.s64 ta, ta0, 2;\n"
        "wgmma.mma_async.sync.aligned.m64n192k16.f16.f16.f16 {%0, %1, %2, %3, %4, %5, %6, %7, %8, %9, %10, %11, %12, %13, %14, %15, %16, %17, %18, %19, %20, %21, %22, %23, %24, %25, %26, %27, %28, %29, %30, %31, %32, %33, %34, %35, %36, %37, %38, %39, %40, %41, %42, %43, %44, %45, %46, %47}, ta, tb, p1, 1, 1, 0, 1;\n"
        "add.s64 tb, tb0, 128;\n"
        "add.s64 ta, ta0, 4;\n"
        "wgmma.mma_async.sync.aligned.m64n192k16.f16.f16.f16 {%0, %1, %2, %3, %4, %5, %6, %7, %8, %9, %10, %11, %12, %13, %14, %15, %16, %17, %18, %19, %20, %21, %22, %23, %24, %25, %26, %27, %28, %29, %30, %31, %32, %33, %34, %35, %36, %37, %38, %39, %40, %41, %42, %43, %44, %45, %46, %47}, ta, tb, p1, 1, 1, 0, 1;\n"
        "add.s64 tb, tb0, 192;\n"
        "add.s64 ta, ta0, 6;\n"
        "wgmma.mma_async.sync.aligned.m64n192k16.f16.f16.f16 {%0, %1, %2, %3, %4, %5, %6, %7, %8, %9, %10, %11, %12, %13, %14, %15, %16, %17, %18, %19, %20, %21, %22, %23, %24, %25, %26, %27, %28, %29, %30, %31, %32, %33, %34, %35, %36, %37, %38, %39, %40, %41, %42, %43, %44, %45, %46, %47}, ta, tb, p1, 1, 1, 0, 1;\n"
        "add.s64 tb, tb0, 256;\n"
        "add.s64 ta, ta0, 512;\n"
        "wgmma.mma_async.sync.aligned.m64n192k16.f16.f16.f16 {%0, %1, %2, %3, %4, %5, %6, %7, %8, %9, %10, %11, %12, %13, %14, %15, %16, %17, %18, %19, %20, %21, %22, %23, %24, %25, %26, %27, %28, %29, %30, %31, %32, %33, %34, %35, %36, %37, %38, %39, %40, %41, %42, %43, %44, %45, %46, %47}, ta, tb, p1, 1, 1, 0, 1;\n"
        "add.s64 tb, tb0, 320;\n"
        "add.s64 ta, ta0, 514;\n"
        "wgmma.mma_async.sync.aligned.m64n192k16.f16.f16.f16 {%0, %1, %2, %3, %4, %5, %6, %7, %8, %9, %10, %11, %12, %13, %14, %15, %16, %17, %18, %19, %20, %21, %22, %23, %24, %25, %26, %27, %28, %29, %30, %31, %32, %33, %34, %35, %36, %37, %38, %39, %40, %41, %42, %43, %44, %45, %46, %47}, ta, tb, p1, 1, 1, 0, 1;\n"
        "add.s64 tb, tb0, 384;\n"
        "add.s64 ta, ta0, 516;\n"
        "wgmma.mma_async.sync.aligned.m64n192k16.f16.f16.f16 {%0, %1, %2, %3, %4, %5, %6, %7, %8, %9, %10, %11, %12, %13, %14, %15, %16, %17, %18, %19, %20, %21, %22, %23, %24, %25, %26, %27, %28, %29, %30, %31, %32, %33, %34, %35, %36, %37, %38, %39, %40, %41, %42, %43, %44, %45, %46, %47}, ta, tb, p1, 1, 1, 0, 1;\n"
        "add.s64 tb, tb0, 448;\n"
        "add.s64 ta, ta0, 518;\n"
        "wgmma.mma_async.sync.aligned.m64n192k16.f16.f16.f16 {%0, %1, %2, %3, %4, %5, %6, %7, %8, %9, %10, %11, %12, %13, %14, %15, %16, %17, %18, %19, %20, %21, %22, %23, %24, %25, %26, %27, %28, %29, %30, %31, %32, %33, %34, %35, %36, %37, %38, %39, %40, %41, %42, %43, %44, %45, %46, %47}, ta, tb, p1, 1, 1, 0, 1;\n"
        "add.s64 tb, tb0, 512;\n"
        "add.s64 ta, ta0, 1024;\n"
        "wgmma.mma_async.sync.aligned.m64n192k16.f16.f16.f16 {%0, %1, %2, %3, %4, %5, %6, %7, %8, %9, %10, %11, %12, %13, %14, %15, %16, %17, %18, %19, %20, %21, %22, %23, %24, %25, %26, %27, %28, %29, %30, %31, %32, %33, %34, %35, %36, %37, %38, %39, %40, %41, %42, %43, %44, %45, %46, %47}, ta, tb, p1, 1, 1, 0, 1;\n"
        "add.s64 tb, tb0, 576;\n"
        "add.s64 ta, ta0, 1026;\n"
        "wgmma.mma_async.sync.aligned.m64n192k16.f16.f16.f16 {%0, %1, %2, %3, %4, %5, %6, %7, %8, %9, %10, %11, %12, %13, %14, %15, %16, %17, %18, %19, %20, %21, %22, %23, %24, %25, %26, %27, %28, %29, %30, %31, %32, %33, %34, %35, %36, %37, %38, %39, %40, %41, %42, %43, %44, %45, %46, %47}, ta, tb, p1, 1, 1, 0, 1;\n"
        "add.s64 tb, tb0, 640;\n"
        "add.s64 ta, ta0, 1028;\n"
        "wgmma.mma_async.sync.aligned.m64n192k16.f16.f16.f16 {%0, %1, %2, %3, %4, %5, %6, %7, %8, %9, %10, %11, %12, %13, %14, %15, %16, %17, %18, %19, %20, %21, %22, %23, %24, %25, %26, %27, %28, %29, %30, %31, %32, %33, %34, %35, %36, %37, %38, %39, %40, %41, %42, %43, %44, %45, %46, %47}, ta, tb, p1, 1, 1, 0, 1;\n"
        "add.s64 tb, tb0, 704;\n"
        "add.s64 ta, ta0, 1030;\n"
        "wgmma.mma_async.sync.aligned.m64n192k16.f16.f16.f16 {%0, %1, %2, %3, %4, %5, %6, %7, %8, %9, %10, %11, %12, %13, %14, %15, %16, %17, %18, %19, %20, %21, %22, %23, %24, %25, %26, %27, %28, %29, %30, %31, %32, %33, %34, %35, %36, %37, %38, %39, %40, %41, %42, %43, %44, %45, %46, %47}, ta, tb, p1, 1, 1, 0, 1;\n"
        "}\n"
        : "=r"(d[0]), "=r"(d[1]), "=r"(d[2]), "=r"(d[3]), "=r"(d[4]), "=r"(d[5]), "=r"(d[6]), "=r"(d[7]), "=r"(d[8]), "=r"(d[9]), "=r"(d[10]), "=r"(d[11]), "=r"(d[12]), "=r"(d[13]), "=r"(d[14]), "=r"(d[15]), "=r"(d[16]), "=r"(d[17]), "=r"(d[18]), "=r"(d[19]), "=r"(d[20]), "=r"(d[21]), "=r"(d[22]), "=r"(d[23]), "=r"(d[24]), "=r"(d[25]), "=r"(d[26]), "=r"(d[27]), "=r"(d[28]), "=r"(d[29]), "=r"(d[30]), "=r"(d[31]), "=r"(d[32]), "=r"(d[33]), "=r"(d[34]), "=r"(d[35]), "=r"(d[36]), "=r"(d[37]), "=r"(d[38]), "=r"(d[39]), "=r"(d[40]), "=r"(d[41]), "=r"(d[42]), "=r"(d[43]), "=r"(d[44]), "=r"(d[45]), "=r"(d[46]), "=r"(d[47])
        : "l"(descA), "n"(AOFF >> 4), "l"(descB), "n"(BOFF >> 4));
}

struct Params {
    const __nv_bfloat16* x;
    const __nv_bfloat16* wqkv;
    const __nv_bfloat16* wo;
    const __nv_bfloat16* logit_scale;
    const __nv_bfloat16* cpb_w1;
    const __nv_bfloat16* cpb_w2;
    const __nv_bfloat16* rel_coords;
    const int*           rel_idx;
    const __nv_bfloat16* mask;
    __nv_bfloat16*       out;
    unsigned long long   z1;
    int                  npair;
    uint32_t             need;
    int                  spread;
    int                  t1;
};

constexpr uint32_t POS_END = 0x8000;
__device__ __forceinline__ uint32_t pos_add(uint32_t pos, int n) {
    pos += n;
    return (pos & 127) >= NWS ? pos + (128 - NWS) : pos;
}
__device__ __forceinline__ int role_of(const Params& P, int b) {
    const int n0 = ((b >> 1) * P.spread) >> 16, n1 = (((b >> 1) + 1) * P.spread) >> 16;
    return n1 != n0 ? 2 * P.npair + 2 * n0 + (b & 1) : b - 2 * n0;
}
__device__ __forceinline__ void finish(uint32_t total) {
    __threadfence();
    if (atomicAdd(&g_done, 1u) == total - 1) {
        for (int i = 0; i < NWS; i++) g_cnt[i] = 0;
        g_next[0] = 0; g_next[1] = 0;
        g_done = 0;
    }
}

constexpr int FB_PITCH = 584, FB_X = TOK * FB_PITCH * 2, FB_TAB = FB_X + TOK * 384, FB_BYTES = FB_TAB + 169 * 8 + 8;
static_assert(3 * FB_BYTES <= SM_PBAR && FB_BYTES % 16 == 0 && SM_BAR + B_ROWS == SM_PBAR + 64 && PCHUNK, "smem");
__device__ __forceinline__ void redo(const Params& P, uint8_t* sm, uint32_t tag, int barid) {
    typedef __nv_bfloat16 bf;
    const int t = threadIdx.x & 127, lane = t & 31;
    bf* const qkv = reinterpret_cast<bf*>(sm);
    bf* const xs = reinterpret_cast<bf*>(sm + FB_X);
    bf* const tab = reinterpret_cast<bf*>(sm + FB_TAB);
    volatile int* const next = reinterpret_cast<volatile int*>(sm + FB_TAB + 169 * 8);
#pragma unroll 1
    for (uint32_t n = 0; n < (1u << 22); n++) {
        uint32_t a;
        asm volatile("ld.acquire.gpu.global.u32 %0, [%1];\n" : "=r"(a) : "l"(g_guard) : "memory");
        if (a == tag + 1) break;
        __nanosleep(256);
    }
    asm volatile("fence.proxy.async;\n" ::: "memory");
#pragma unroll 1
    for (int i = t; i < 169 * 4; i += 128) {
        float a = 0.f;
#pragma unroll 1
        for (int u = 0; u < 16; u++) {
            const float h = round_bf16(__bfloat162float(P.rel_coords[(i >> 2) * 2]) * __bfloat162float(P.cpb_w1[u]) +
                                       __bfloat162float(P.rel_coords[(i >> 2) * 2 + 1]) * __bfloat162float(P.cpb_w1[16 + u]));
            a += (h > 0.f ? h : h * 0.f) * __bfloat162float(P.cpb_w2[u * 4 + (i & 3)]);
        }
        tab[i] = __float2bfloat16_rn(16.f * round_bf16(1.f / (1.f + expf(-round_bf16(a)))));
    }
#pragma unroll 1
    for (;;) {
        wg_bar(barid);
        if (t == 0) *next = (int)atomicAdd(g_guard + 2, 1u);
        wg_bar(barid);
        const int win = *next;
        if (win >= NWINDOWS) return;
        const int y0 = 7 * (win / NWS) + 3, x0 = 7 * (win % NWS) + 3;
        auto pixel = [&](int r) { return (size_t)(((y0 + r / 7) % IMG) * IMG + (x0 + r % 7) % IMG) * 192; };
#pragma unroll 1
        for (int i = t; i < TOK * 24; i += 128)
            reinterpret_cast<uint4*>(xs)[i] = reinterpret_cast<const uint4*>(P.x + pixel(i / 24))[i % 24];
#pragma unroll 1
        for (int ph = 0; ph < 2; ph++) {
            const bf* const a = ph ? qkv : xs;
            bf* const d = ph ? xs : qkv;
            const int n = ph ? 192 : 576, pa = ph ? FB_PITCH : 192, pd = ph ? 192 : FB_PITCH;
            wg_bar(barid);
#pragma unroll 1
            for (int col = t; col < n; col += 128) {
                const bf* w = (ph ? P.wo : P.wqkv) + col;
                float acc[TOK];
#pragma unroll
                for (int r = 0; r < TOK; r++) acc[r] = 0.f;
#pragma unroll 1
                for (int k = 0; k < 192; k += 2) {
                    const float w0 = __bfloat162float(w[k * n]), w1 = __bfloat162float(w[(k + 1) * n]);
#pragma unroll
                    for (int r = 0; r < TOK; r++) {
                        const uint32_t v = *reinterpret_cast<const uint32_t*>(a + r * pa + k);
                        acc[r] = fmaf(bf16hi(v), w1, fmaf(bf16lo(v), w0, acc[r]));
                    }
                }
#pragma unroll
                for (int r = 0; r < TOK; r++) d[r * pd + col] = __float2bfloat16_rn(acc[r]);
            }
            wg_bar(barid);
            if (ph) break;
#pragma unroll 1
            for (int i = t; i < TOK * 8; i += 128) {
                bf* const v = qkv + (i % TOK) * FB_PITCH + (i / TOK) * 48;
                float s = 0.f;
#pragma unroll 1
                for (int j = 0; j < 48; j++) s = fmaf(__bfloat162float(v[j]), __bfloat162float(v[j]), s);
                s = round_bf16(1.f / sqrtf(round_bf16(round_bf16(s) + 1e-12f)));
#pragma unroll 1
                for (int j = 0; j < 48; j++) v[j] = __float2bfloat16_rn(__bfloat162float(v[j]) * s);
            }
            wg_bar(barid);
#pragma unroll 1
            for (int i = t; i < TOK * 4; i += 128) {
                const int r = i % TOK, h = i / TOK;
                uint32_t* const q = reinterpret_cast<uint32_t*>(qkv + r * FB_PITCH + h * 48);
                const float tau = round_bf16(expf(round_bf16(fminf(fmaxf(__bfloat162float(P.logit_scale[h]), -100.f), 4.6052f))));
                float v[48], mx = -INFINITY, sum = 0.f;
#pragma unroll
                for (int j = 0; j < 24; j++) { v[2 * j] = bf16lo(q[j]); v[2 * j + 1] = bf16hi(q[j]); }
#pragma unroll 1
                for (int j = 0; j < TOK; j++) {
                    const uint32_t* kk = reinterpret_cast<const uint32_t*>(qkv + j * FB_PITCH + 192 + h * 48);
                    float s = 0.f;
#pragma unroll
                    for (int u = 0; u < 24; u++) s = fmaf(v[2 * u + 1], bf16hi(kk[u]), fmaf(v[2 * u], bf16lo(kk[u]), s));
                    s = round_bf16(round_bf16(s) * tau);
                    s = round_bf16(s + __bfloat162float(tab[min(max(P.rel_idx[r * TOK + j], 0), 168) * 4 + h]));
                    s = round_bf16(s + __bfloat162float(P.mask[(size_t)win * (TOK * TOK) + r * TOK + j]));
                    xs[j * 128 + t] = __float2bfloat16_rn(s);
                    mx = fmaxf(mx, s);
                }
#pragma unroll 1
                for (int j = 0; j < TOK; j++) sum += expf(__bfloat162float(xs[j * 128 + t]) - mx);
#pragma unroll
                for (int j = 0; j < 48; j++) v[j] = 0.f;
#pragma unroll 1
                for (int j = 0; j < TOK; j++) {
                    const uint32_t* vv = reinterpret_cast<const uint32_t*>(qkv + j * FB_PITCH + 384 + h * 48);
                    const float p = round_bf16(expf(__bfloat162float(xs[j * 128 + t]) - mx) / sum);
#pragma unroll
                    for (int u = 0; u < 24; u++) {
                        v[2 * u] = fmaf(p, bf16lo(vv[u]), v[2 * u]);
                        v[2 * u + 1] = fmaf(p, bf16hi(vv[u]), v[2 * u + 1]);
                    }
                }
#pragma unroll
                for (int j = 0; j < 24; j++) q[j] = pack_bf16(v[2 * j], v[2 * j + 1]);
            }
        }
#pragma unroll 1
        for (int r = t >> 5; r < TOK; r += 4) {
            float v[6], m = 0.f, s = 0.f;
#pragma unroll
            for (int j = 0; j < 6; j++) { v[j] = __bfloat162float(xs[r * 192 + j * 32 + lane]); m += v[j]; }
#pragma unroll
            for (int o = 16; o; o >>= 1) m += __shfl_xor_sync(0xffffffffu, m, o);
            m *= 1.f / 192.f;
#pragma unroll
            for (int j = 0; j < 6; j++) s = fmaf(v[j] - m, v[j] - m, s);
#pragma unroll
            for (int o = 16; o; o >>= 1) s += __shfl_xor_sync(0xffffffffu, s, o);
            s = round_bf16(sqrtf(round_bf16(round_bf16(s * (1.f / 192.f)) + 1e-5f)));
            m = round_bf16(m);
#pragma unroll
            for (int j = 0; j < 6; j++) P.out[pixel(r) + j * 32 + lane] = __float2bfloat16_rn(round_bf16(v[j] - m) / s);
        }
    }
}

__global__ void __launch_bounds__(NTHREADS, 1)
swin_window_attn_kernel(const Params P, const __grid_constant__ CUtensorMap xmap, const __grid_constant__ CUtensorMap xmap4,
                        const __grid_constant__ CUtensorMap xmap3,
                        const __grid_constant__ CUtensorMap omap, const __grid_constant__ CUtensorMap wmap,
                        const __grid_constant__ CUtensorMap smap, const __grid_constant__ CUtensorMap omapb,
                        const __grid_constant__ CUtensorMap xmapa, const __grid_constant__ CUtensorMap xmapb,
                        const __grid_constant__ CUtensorMap smap3, const __grid_constant__ CUtensorMap wraw,
                        const __grid_constant__ CUtensorMap smapw) {
    extern __shared__ __align__(1024) uint8_t smem[];
    constexpr uint32_t sb0 = 1024;
    constexpr uint32_t sbase = sb0;
    if (smem_u32(smem) != sbase) return;
    const int tid = threadIdx.x;
    const int wg = __shfl_sync(0xffffffffu, tid >> 7, 0);
    const int warp = __shfl_sync(0xffffffffu, (tid >> 5) & 3, 0);
    const int lane = tid & 31;
    const int g = lane >> 2, c = lane & 3;

    TR(26, wg);
    if (wg == 0) { ST(0); SC(27); }
    const int role = role_of(P, blockIdx.x);
    const bool attn = role < 2 * P.npair;
    const int pair = role >> 1, half = role & 1;
    const uint32_t bars = sbase + SM_BAR;
    const bool first = wg == 3 && warp == 3;
    if (first) {
        if (lane == 0) {
            mbar_init(bars + B_WRAW, 1);
            mbar_init(bars + B_WFULL, 1);
            mbar_init(bars + B_MFULL, 1);
            for (int b = 0; b < 4; b++) mbar_init(bars + B_XFULL + b * 8, 2);
            asm volatile("fence.mbarrier_init.release.cluster;\n" ::: "memory");
            fence_async_smem();
        }
        __syncwarp();
        asm volatile("bar.arrive 0, 512;\n" ::: "memory");
        if (attn && elect_one()) {
            mbar_arrive_expect_tx(bars + B_WRAW, 12 * W_ATOM);
            TR(26, 30);
            asm volatile("prefetch.tensormap [%0];\n" :: "l"(reinterpret_cast<uint64_t>(&wmap)) : "memory");
            asm volatile("prefetch.tensormap [%0];\n" :: "l"(reinterpret_cast<uint64_t>(XPF ? &wraw : &xmap)) : "memory");
            if (XPF == 1) {
                const uint32_t pos = half ? pos_add(pair, P.npair) : pair;
#pragma unroll
                for (int ch = 0; ch < 3; ch++)
                    asm volatile("cp.async.bulk.prefetch.tensor.3d.L2.global.tile [%0, {%1, %2, %3}];\n"
                                 :: "l"(reinterpret_cast<uint64_t>(&xmap)), "r"(ch * 64), "r"(7 * (pos & 127) + 3), "r"(7 * (pos >> 7) + 3)
                                 : "memory");
            }
            if (XPF == 2) {
                const uint32_t pos = half ? pos_add(pair, P.npair) : pair;
                const char* src = reinterpret_cast<const char*>(P.x) + ((7 * (pos >> 7) + 3) * IMG + 7 * (pos & 127) + 3) * 384;
#pragma unroll
                for (int r = 0; r < 7; r++)
                    asm volatile("cp.async.bulk.prefetch.L2.global [%0], 2688;\n" :: "l"(src + r * IMG * 384) : "memory");
                asm volatile("prefetch.tensormap [%0];\n" :: "l"(reinterpret_cast<uint64_t>(&xmap)) : "memory");
            }
#pragma unroll
            for (int i = 0; i < 2; i++) tma_2d(sbase + i * 6 * W_ATOM, &wraw, bars + B_WRAW, i * 192 + half * 128, 0);
            TR(26, 31);
#pragma unroll
            for (int i = 0; i < 2; i++) tma_2d(sbase + (i * 6 + 4) * W_ATOM, &wmap, bars + B_WRAW, i * 192 + 64 + half * 32, 0);
            TR(26, 33);
            int wh = 0, ww = pair;
#pragma unroll
            for (int j = 0; j < NEARLY; j++) {
                if (ww < NWS - 1) {
                    const uint32_t bar = bars + B_XFULL + (j ? j - 1 : 0) * 8;
                    if (j >= 2) mbar_arrive(bar);
                    mbar_arrive_expect_tx(bar, 3 * XCH);
#pragma unroll
                    for (int ch = 0; ch < 3; ch++)
                        tma_3d(sbase + SM_QK + ((j + 3) & 3) * XCH + ch * QK_CHUNK, &xmap, bar, ch * 64, 7 * ww + 3, 7 * wh + 3);
                }
                ww += P.npair; if (ww >= NWS) { ww -= NWS; wh++; }
                TR(26, 40 + j);
                if (j == 1) {
                    mbar_arrive_expect_tx(bars + B_WFULL, 6 * W_ATOM);
                    tma_2d(sbase + SM_WV, &wraw, bars + B_WFULL, 384 + half * 128, 0);
                    tma_2d(sbase + SM_WV + 4 * W_ATOM, &wmap, bars + B_WFULL, 384 + 64 + half * 32, 0);
                    mbar_arrive_expect_tx(bars + B_MFULL, 4816);
                    asm volatile("cp.async.bulk.shared::cluster.global.mbarrier::complete_tx::bytes [%0], [%1], 4816, [%2];\n"
                                 :: "r"(cl(sbase + SM_MASK)), "l"(reinterpret_cast<const char*>(P.mask) + (((uint32_t)pair * 4802u) & ~15u)),
                                    "r"(cl(bars + B_MFULL)) : "memory");
                    TR(26, 50);
                }
            }
        }
        __syncwarp();
    }
    const int t0 = min(warp * 16 + g, TOK - 1), t1 = min(warp * 16 + g + 8, TOK - 1);
    int ridx[26];
    uint32_t rc, w2[16];
    uint4 w1[4];
    if (attn && wg == 0) rc = reinterpret_cast<const uint32_t*>(P.logit_scale)[half];
    if (attn && (wg == 1 || wg == 2)) {
        rc = reinterpret_cast<const uint32_t*>(P.rel_coords)[min(tid - 128, 168)];
#pragma unroll
        for (int i = 0; i < 4; i++) w1[i] = reinterpret_cast<const uint4*>(P.cpb_w1)[i];
#pragma unroll
        for (int u = 0; u < 16; u++) w2[u] = reinterpret_cast<const uint32_t*>(P.cpb_w2)[2 * u + half];
#pragma unroll
        for (int rh = 0; rh < 2; rh++) {
            const int* ri = P.rel_idx + (rh ? t1 : t0) * TOK;
#pragma unroll
            for (int j = 0; j < 12; j++) ridx[13 * rh + j] = ri[8 * (j >> 1) + 2 * c + (j & 1)];
            ridx[13 * rh + 12] = ri[48];
        }
    }
    {
        if (tid == 416) {
            const CUtensorMap* maps[4] = {attn ? &smap : &omap, &smap3, &xmapa, &xmapb};
#pragma unroll
            for (int i = 0; i < 4; i++) asm volatile("prefetch.tensormap [%0];\n" :: "l"(reinterpret_cast<uint64_t>(maps[i])) : "memory");
        }
        if (tid == 384) {
            for (int b = 0; b < 4; b++) {
                mbar_init(bars + B_QKRAW + b * 8, 4);
                mbar_init(bars + B_VRAW + b * 8, 4);
                mbar_init(bars + B_VFREE + b * 8, 2);
                mbar_init(bars + B_QKFREE + b * 8, MC ? 8 : 4);
                mbar_init(bars + B_ODONE + b * 8, 4);
            }
            sts32(bars + B_MSTATE, 0);
            sts32(bars + B_MSTATE + 4, 0x7FFFFFFF);
            sts32(bars + B_NTILES, 0x7FFFFFFF);
            sts128(bars + B_DYN, ~0u, ~0u, ~0u, ~0u);
            sts128(bars + B_DYN + 16, ~0u, ~0u, ~0u, ~0u);
            mbar_init(bars + B_GDONE, 4);
            sts32(bars + B_ROWS, 0xFFFFFFFFu);
            if (WPOLL) sts32(bars + B_ROWS + 8, 0);
            if (PROG) sts32(bars + B_ROWS + 12, 0xFFFFFF00u);
            mbar_init(bars + B_MCONS, 4);
            mbar_init(bars + B_XCONS, 4);
            for (int b = 0; b < 4; b++) mbar_init(bars + B_STORED + b * 8, 1);
            for (int b = 0; b < 6; b++) {
                mbar_init(sbase + SM_PBAR + b * 8, 1);
                if (PCHUNK) sts32(sbase + SM_PBAR + 48, 0); else
                mbar_init(sbase + SM_PBAR + 48 + b * 8, PSTORE ? 1 : 4);
                mbar_init(sbase + SM_PBAR + 104 + b * 8, 4);
            }
            mbar_init(sbase + SM_PBAR + 96, attn ? 13 : 12);
            if (MPRE && !attn) for (int b = 0; b < (MBG ? 32 : 12 * MBUFS); b++) mbar_init(sbase + SM_MBAR + b * 8, 1);
            mbar_init(sbase + SM_PBAR + 56, 12);
            asm volatile("fence.mbarrier_init.release.cluster;\n" ::: "memory");
        }
        if (wg == 3) {
            static_assert(4 * O_STRIDE == 3 * V_STRIDE + 13 * GRP, "layout");
            if (attn && lane < 16 && warp < 3)
                *reinterpret_cast<uint4*>(smem + SM_V + warp * V_STRIDE + 13 * GRP + lane * 16) = make_uint4(0, 0, 0, 0);
            fence_async_smem();
        }
        if (MC || PROG) { __syncwarp(); asm volatile("barrier.cluster.arrive.relaxed.aligned;\n" ::: "memory"); }
        if (!first) asm volatile("bar.sync 0, 512;\n" ::: "memory");
        if (wg == 3 && warp == 0) asm volatile("bar.arrive 15, 64;\n" ::: "memory");
        if (first) asm volatile("bar.sync 15, 64;\n" ::: "memory");
        TR(26, 4 + wg);
        TR(26, 13);
    }

    auto raw_w = [&](int rg, int cc) {
        const uint32_t ca = cc - 4 * half, row = rg * 8 + (lane & 7);
        return ca < 8 ? row * 128 + ((ca ^ (lane & 7)) << 4) : 4 * W_ATOM + row * 64 + (((cc ^ (lane >> 1)) & 3) << 4);
    };
    auto permute_a = [&]() {
        uint2 w[9][4];
        uint32_t src[3][2], step[3][2];
        const int rg = ((tid >> 5) - 4) * 3;
#pragma unroll
        for (int i = 0; i < 6; i++) {
            const int cc = (i >> 1) * 2 + (i & 1) * 6;
            src[i >> 1][i & 1] = raw_w(rg, cc + (lane >> 4)) + (lane & 8);
            step[i >> 1][i & 1] = (uint32_t)(cc - 4 * half) < 8 ? 1024 : 512;
        }
        reg_fence(src);
        TR(26, 16 + wg);
        mbar_wait(bars + B_WRAW, 0);
        TR(26, 20 + wg);
#pragma unroll
        for (int i = 0; i < 9; i++)
#pragma unroll
            for (int m = 0; m < 4; m++)
                w[i][m] = *reinterpret_cast<const uint2*>(smem + (m >> 1) * 6 * W_ATOM + src[i % 3][m & 1] + (i / 3) * step[i % 3][m & 1]);
        asm volatile("bar.sync 2, 256;\n" ::: "memory");
        TR(26, 24 + wg);
        const uint32_t d = sbase + (lane >> 3) * W_ATOM + (rg * 8 + (lane & 7)) * 32 + ((lane >> 2) & 1) * 16;
#pragma unroll
        for (int i = 0; i < 9; i++) {
            sts128(d + (i % 3) * 4 * W_ATOM + (i / 3) * 256, bf2h(w[i][0].x), bf2h(w[i][1].x), bf2h(w[i][2].x), bf2h(w[i][3].x));
            sts128((d ^ 16) + (i % 3) * 4 * W_ATOM + (i / 3) * 256, bf2h(w[i][0].y), bf2h(w[i][1].y), bf2h(w[i][2].y), bf2h(w[i][3].y));
        }
    };
    auto permute_w = [&]() {
        uint4 w[3][4];
        uint32_t src[3][2];
#pragma unroll
        for (int it = 0; it < 3; it++) {
            const int o = ((tid >> 5) * 3 + it) * 4 + (lane >> 3);
            src[it][0] = raw_w(o / 6, o % 6);
            src[it][1] = raw_w(o / 6, o % 6 + 6);
        }
        reg_fence(src);
        TR(26, 16 + wg);
        mbar_wait(bars + B_WRAW, 0);
        TR(26, 20 + wg);
#pragma unroll
        for (int it = 0; it < 3; it++) {
#pragma unroll
            for (int m = 0; m < 4; m++)
                w[it][m] = *reinterpret_cast<const uint4*>(smem + (m >> 1) * 6 * W_ATOM + src[it][m & 1]);
        }
        asm volatile("bar.sync 2, 384;\n" ::: "memory");
        TR(26, 24 + wg);
#pragma unroll
        for (int it = 0; it < 3; it++) {
            const int o = ((tid >> 5) * 3 + it) * 4 + (lane >> 3);
            const uint32_t d = sbase + (o % 6) * 2 * W_ATOM + ((o / 6) * 8 + (lane & 7)) * 32 + ((lane >> 2) & 1) * 16;
            sts128(d, bf2h(w[it][0].x), bf2h(w[it][1].x), bf2h(w[it][2].x), bf2h(w[it][3].x));
            sts128(d ^ 16, bf2h(w[it][0].y), bf2h(w[it][1].y), bf2h(w[it][2].y), bf2h(w[it][3].y));
            sts128(d + W_ATOM, bf2h(w[it][0].z), bf2h(w[it][1].z), bf2h(w[it][2].z), bf2h(w[it][3].z));
            sts128((d ^ 16) + W_ATOM, bf2h(w[it][0].w), bf2h(w[it][1].w), bf2h(w[it][2].w), bf2h(w[it][3].w));
        }
    };
    const uint32_t nfinish = gridDim.x + (POLLER ? 0 : 2 * P.npair);
#define PROJ_SCHEDULE                                                                                   \
    int bid = blockIdx.x;                                                                               \
    asm volatile("" : "+r"(bid));                      \
    bid = role_of(P, bid);                                                                              \
    const bool at = bid < 2 * P.npair;                                                                  \
    const int tile0 = at ? P.t1 - NOLD + bid : NOLD + bid - 2 * P.npair;                                \
    const int told = at ? P.t1 - NOLD : 0;                                                              \
    const int tstep = at ? 2 * P.npair : (int)gridDim.x - 2 * P.npair;                                  \
    const int tend = at ? TILES : P.t1;
    if (wg == 3) {
        TR(26, 60 + warp);
        asm volatile("setmaxnreg.dec.sync.aligned.u32 %0;\n" :: "n"(REG_H));
        TR(26, 64 + warp);
#define MST_OFF 0
        if (warp == 1 && attn) {
            const uint16_t mlast = reinterpret_cast<const uint16_t*>(P.mask)[NWINDOWS * TOK * TOK - 1];
            const uint32_t ma = sbase + SM_MASK + 16 + lane * 16, mb = sbase + SM_MASK + min(289 + lane, 299) * 16;
            const uint32_t mc = sbase + SM_MASK + (lane & 7) * 2 + (lane & 8) * 600;
            uint32_t ph = 0, win = pair, fp = 0, nzl = 0;
#pragma unroll 1
            for (int k = 0;; k++) {
                mbar_wait(bars + B_MFULL, fp);
                uint32_t acc = lds16(mc);
                if ((lane & 15) - (win & 7) > 8u) acc = 0;
#pragma unroll
                for (int i = 0; i < 10; i += MRND) {
                    uint32_t w[MRND][4];
#pragma unroll
                    for (int j = 0; j < MRND; j++) if (i + j < 10) lds128(w[j], i + j < 9 ? ma + (i + j) * 512 : mb);
#pragma unroll
                    for (int j = 0; j < MRND; j++) if (i + j < 10) acc |= w[j][0] | w[j][1] | w[j][2] | w[j][3];
                    asm volatile("" : "+r"(acc) :: "memory");
                }
                uint32_t nz = __any_sync(0xffffffffu, (acc & 0x7FFF7FFFu) != 0) ? 1 : 0;
                if (lane == 0) asm volatile("st.volatile.shared.b32 [%0], %1;\n" :: "r"(MST_OFF ? sbase + SM_DUMP : bars + B_MSTATE), "r"(32 * k + 32 - 16 * nz + (2 * win & 14) + fp) : "memory");
                fp ^= 1;
                if (k + 1 == MPRE) {
                    uint32_t tag;
                    asm volatile("ld.relaxed.gpu.global.u32 %0, [%1];\n" : "=r"(tag) : "l"(g_guard) : "memory");
#pragma unroll 1
                    for (uint32_t n = 0; n < (1u << 20); n++) {
                        bool ok = true;
                        nzl = 0;
#pragma unroll
                        for (int j = 0; j < 3; j++) {
                            uint32_t f;
                            asm volatile("ld.relaxed.gpu.global.u32 %0, [%1];\n" : "=r"(f) : "l"(g_mz + pair * 128 + 32 * j + lane) : "memory");
                            ok = ok && ((f | 1) == (tag | 255) || 32 * j + lane < MPRE || 32 * j + lane >= MEND);
                            nzl |= (~f & 1) << j;
                        }
                        if (__all_sync(0xffffffffu, ok)) break;
                        nzl = 7;
                        __nanosleep(RSLEEP);
                    }
                }
                if (k + 1 >= MPRE && k + 1 < MEND) {
                    uint32_t kn = MEND;
#pragma unroll
                    for (int j = 0; j < 3; j++) if ((nzl >> j & 1) && 32 * j + lane > k) kn = min(kn, 32 * j + lane);
                    kn = __reduce_min_sync(0xffffffffu, kn);
                    if (kn > k + 1) {
                        if (nz) { mbar_wait(bars + B_MCONS, ph); ph ^= 1; fence_async_smem(); nz = 0; }
                        if (lane == 0) asm volatile("st.volatile.shared.b32 [%0], %1;\n" :: "r"(bars + B_MSTATE), "r"(32 * kn) : "memory");
                        k = kn - 1;
                        win = pair + k * P.npair;
                    }
                }
                win += P.npair;
                if (k + 1 >= NSTATIC) {
                    uint32_t e = 0xFFFF;
#pragma unroll 1
                    for (uint32_t n = 0; n < (1u << 20); n++) {
                        e = lds16v(bars + B_DYN + (k + 1 - NSTATIC) * 2);
                        if (__all_sync(0xffffffffu, e != 0xFFFF)) break;
                        __nanosleep(RSLEEP);
                    }
                    if (__any_sync(0xffffffffu, e >= POS_END)) break;
                    win = e - (e >> 7) * (128 - NWS);
                }
                if (nz && !MST_OFF) { mbar_wait(bars + B_MCONS, ph); ph ^= 1; fence_async_smem(); }
                if (elect_one()) {
                    uint32_t bytes = 4816;
                    if (win == NWINDOWS - 1) {
                        bytes = 4800;
                        asm volatile("st.shared.u16 [%0], %1;\n" :: "r"(sbase + SM_MASK + 4800), "h"(mlast) : "memory");
                    }
                    TR(25, k + 1);
                    mbar_arrive_expect_tx(bars + B_MFULL, bytes);
                    asm volatile("cp.async.bulk.shared::cluster.global.mbarrier::complete_tx::bytes [%0], [%1], %2, [%3];\n"
                                 :: "r"(cl(sbase + SM_MASK)),
                                    "l"(reinterpret_cast<const char*>(P.mask) + (((uint32_t)win * 4802u) & ~15u)),
                                    "r"(bytes), "r"(cl(bars + B_MFULL)) : "memory");
                    if (MPF && half == (win & 1) && win + MPF * P.npair < NWINDOWS && (!MPRE || k + 1 + MPF < MPRE || k + 1 >= MLIM))
                        asm volatile("cp.async.bulk.prefetch.L2.global [%0], %1;\n"
                                     :: "l"(reinterpret_cast<const char*>(P.mask) + (((uint32_t)(win + MPF * P.npair) * 4802u) & ~15u)),
                                        "r"(4800) : "memory");
                }
                __syncwarp();
            }
            {
                const int r0 = min(64 * P.t1 / (7 * IMG), NWS - 1);
                int ready = -1;
#pragma unroll 1
                for (uint32_t n = 0; n < (1u << 20); n++) {
                    const uint32_t over = mbar_test(sbase + SM_PBAR + 96, 0);
                    uint32_t a;
                    asm volatile("ld.relaxed.gpu.global.u32 %0, [%1];\n" : "=r"(a) : "l"(g_cnt + min(r0 + lane, NWS)) : "memory");
                    const int r = r0 - 2 + __ffs(__ballot_sync(0xffffffffu, a < P.need));
                    if (r > ready && r >= r0) {
                        ready = r;
                        asm volatile("fence.acquire.gpu;\n" ::: "memory");
                        asm volatile("fence.proxy.async.global;\n" ::: "memory");
                        __syncwarp();
                        if (lane == 0) asm volatile("st.volatile.shared.b32 [%0], %1;\n" :: "r"(bars + B_ROWS), "r"(r) : "memory");
                    }
                    if (__any_sync(0xffffffffu, over)) break;
                    __nanosleep(WPOLL * 100);
                }
                __syncwarp();
                if (lane == 0) asm volatile("st.volatile.shared.b32 [%0], %1;\n" :: "r"(bars + B_ROWS + 8), "r"(1) : "memory");
            }
        }
        if (!elect_one()) return;
        TR(26, 68 + warp);
        if (warp == 0) {
          if (attn) {
            int kmax = 1 << 20, rows = 1 << 30;
            uint32_t cur = pair, pos1 = pos_add(cur, P.npair), pos2 = pos_add(pos1, P.npair);
            if (MC || PROG) asm volatile("barrier.cluster.wait;\n" ::: "memory");
#pragma unroll 1
            for (int k = -4; k + 4 <= kmax; k++) {
                const int row0 = (k + 4) * TOK;
                const uint32_t dst = sbase + SM_QK + ((k + 3) & 3) * XCH, bar = bars + B_XFULL + ((row0 >> 6) & 3) * 8;
                const bool alone = (row0 & 63) >= 64 - TOK && (row0 & 63) < TOK;
                const int wh = cur >> 7, ww = cur & 127;
                uint32_t claim = NWINDOWS;
                if (k + 7 >= NSTATIC && k + 7 < NSTATIC + 15 && pos2 < POS_END && !(MC && half))
                    asm volatile("atom.relaxed.gpu.global.add.u32 %0, [%1], 1;\n" : "=r"(claim) : "l"(g_next + half) : "memory");
                const int x0 = 7 * ww + 3, y0 = 7 * wh + 3;
                const bool done = k < NEARLY - 4 && ww < NWS - 1;
#define TMA_Y tma_3d
#define QW do { if (k >= 0) mbar_wait(bars + B_QKFREE + ((k + 3) & 3) * 8, (k >> 2) & 1); } while (0)
#define QW2 mbar_wait(bars + B_QKFREE + ((k + 3) & 3) * 8, (k >> 2) & 1)
#define TMA_X tma_3d
                if (!LATEW) QW;
                if (alone && !done) mbar_arrive(bar);
                if (row0 >= rows || ((EXP & 32) && k >= 0)) {
                    mbar_arrive(bar);
                    if (LATEW) QW2;
                    continue;
                }
                TR(20, k + 4);
                const bool inner = wh < NWS - 1 && ww < NWS - 1;
                if (done) {
                } else if (XSPLIT && inner && (row0 & 63) >= 64 - 21) {
                    const uint32_t bar2 = bars + B_XFULL + (((row0 >> 6) + 1) & 3) * 8;
                    mbar_arrive_expect_tx(bar, 3 * 21 * 128);
                    asm volatile("mbarrier.expect_tx.relaxed.cta.shared::cta.b64 [%0], %1;\n" :: "r"(bar2), "r"(3 * 28 * 128) : "memory");
                    if (LATEW) QW2;
#pragma unroll
                    for (int ch = 0; ch < 3; ch++) TMA_X(dst + ch * QK_CHUNK, &xmapa, bar, ch * 64, x0, y0);
#pragma unroll
                    for (int ch = 0; ch < 3; ch++) TMA_X(dst + ch * QK_CHUNK + 21 * 128, &xmapb, bar2, ch * 64, x0, y0 + 3);
                } else if (inner) {
                    mbar_arrive_expect_tx(bar, 3 * XCH);
                    if (LATEW) QW2;
#pragma unroll
                    for (int ch = 0; ch < 3; ch++) TMA_X(dst + ch * QK_CHUNK, &xmap, bar, ch * 64, x0, y0);
                } else if (ww < NWS - 1) {
                    mbar_arrive_expect_tx(bar, 3 * XCH);
                    if (LATEW) QW2;
#pragma unroll
                    for (int ch = 0; ch < 3; ch++) {
                        TMA_X(dst + ch * QK_CHUNK, &xmapb, bar, ch * 64, x0, y0);
                        TMA_X(dst + ch * QK_CHUNK + 28 * 128, &xmapa, bar, ch * 64, x0, 0);
                    }
                } else {
                    mbar_arrive_expect_tx(bar, 3 * XCH);
                    if (LATEW) QW;
                    const int x1 = (ww == NWS - 1) ? 0 : x0 + 4;
#pragma unroll 1
                    for (int i = 0; i < 7; i++) {
                        const int y = (y0 + i >= IMG) ? y0 + i - IMG : y0 + i;
#pragma unroll
                        for (int ch = 0; ch < 3; ch++) {
                            TMA_Y(dst + ch * QK_CHUNK + i * 896, &xmap4, bar, ch * 64, x0, y);
                            TMA_X(dst + ch * QK_CHUNK + i * 896 + 512, &xmap3, bar, ch * 64, x1, y);
                        }
                    }
                }
                if (pos1 < POS_END) cur = pos1;
                pos1 = pos2;
                if (k + 7 < NSTATIC) {
                    pos2 = pos_add(pos2, P.npair);
                } else if (pos2 < POS_END) {
                    if (MC && half) {
                        pos2 = 0xFFFF;
#pragma unroll 1
                        for (uint32_t n = 0; n < (1u << 22) && pos2 == 0xFFFF; n++) pos2 = lds16v(bars + B_DYN + (k + 7 - NSTATIC) * 2);
                        pos2 = min(pos2, POS_END);
                    } else {
                    sts32(bars + B_NTILES + 4, claim);
                    const uint32_t w = lds32v(bars + B_NTILES + 4) + NSTATIC * P.npair;
                    pos2 = w < NWINDOWS ? w + __umulhi(w, 58835169u) * (128 - NWS) : POS_END;
                    sts16(bars + B_DYN + (k + 7 - NSTATIC) * 2, pos2);
                    if (MC) asm volatile("st.relaxed.cluster.shared::cluster.u16 [%0], %1;\n" :: "r"(bars + B_DYN + (k + 7 - NSTATIC) * 2 + (1 << 24)), "h"((uint16_t)pos2) : "memory");
                    }
                    if (pos2 == POS_END) {
                        rows = (row0 + 3 * TOK + 63) & ~63;
                        kmax = (rows + 63) / TOK;
                        sts32(bars + B_MSTATE + 4, k + 7);
                        sts32(bars + B_NTILES, rows >> 6);
                        if (role < SM_STAGE / 1024)
                            asm volatile("cp.async.bulk.prefetch.L2.global [%0], 1024;\n" :: "l"(g_wo + role * 1024) : "memory");
                    }
                }
                if (!NOPF && half == (PFALT ? (k & 1) : 0) && pos2 < POS_END) {
#pragma unroll
                    for (int ch = 0; ch < 3; ch++)
                        asm volatile("cp.async.bulk.prefetch.tensor.3d.L2.global.tile [%0, {%1, %2, %3}];\n"
                                     :: "l"(reinterpret_cast<uint64_t>(&xmap)), "r"(ch * 64), "r"(7 * (pos2 & 127) + 3), "r"(7 * (pos2 >> 7) + 3)
                                     : "memory");
                }
            }
            {
#pragma unroll 1
                for (uint32_t n = 0; n < (1u << 22); n++) {
                    uint32_t a, b;
                    asm volatile("ld.relaxed.gpu.global.u32 %0, [%1];\n" : "=r"(b) : "l"(g_guard) : "memory");
                    asm volatile("ld.acquire.gpu.global.u32 %0, [%1];\n" : "=r"(a) : "l"(g_guard + 3) : "memory");
                    if (a == (b | 255)) break;
                }
                asm volatile("fence.proxy.async.global;\n" ::: "memory");
                mbar_arrive_expect_tx(bars + B_WRAW, SM_STAGE);
                mbar_wait(bars + B_GDONE, 0);
#pragma unroll
                for (int i = 0; i < WOSPLIT; i++)
                    asm volatile("cp.async.bulk.shared::cluster.global.mbarrier::complete_tx::bytes [%0], [%1], %2, [%3];\n"
                                 :: "r"(cl(sbase + SM_WO + i * (SM_STAGE / WOSPLIT))), "l"(g_wo + i * (SM_STAGE / WOSPLIT)),
                                    "n"(SM_STAGE / WOSPLIT), "r"(cl(bars + B_WRAW)) : "memory");
            }
          }
            mbar_wait(sbase + SM_PBAR + 96, 0);
            ST(15);
            if (EDELAY && attn) {
                const uint32_t c0 = clock();
#pragma unroll 1
                while ((uint32_t)clock() - c0 < EDELAY) {}
            }
            fence_async_smem();
            PROJ_SCHEDULE
            int st = 0, ready = -1, want = -6 * PSM, freed = 0;
            uint32_t ph = 1;
#pragma unroll 1
            for (int u = tile0; u < tend; u += tstep) {
                const int t = (NOLD && u < P.t1) ? u - told : u;
                const int p0 = (t < TILES_A) ? SEG_B + 64 * (t & PWRAP) : 64 * (t - TILES_A);
                const int w1 = (t < TILES_A) ? min((64 * t + 63) / (7 * IMG), NWS - 1) : NWS - 1;
#pragma unroll 1
                for (uint32_t n = 0; n < (1u << 24) && ready < w1; n++) ready = (int)lds32v(bars + B_ROWS);
#pragma unroll
                for (int ch = 0; ch < PSM; ch++) {
                    want++;
#pragma unroll 1
                    for (uint32_t n = 0; n < (1u << 22) && freed < want; n++) freed = (int)lds32v(sbase + SM_PBAR + 48);
                    if (ch == 0) mbar_arrive_expect_tx(sbase + SM_PBAR + st * 8, STAGE_BYTES);
                    tma_2d(sbase + SM_STAGE + st * STAGE_BYTES + ch * 8192, &omap, sbase + SM_PBAR + st * 8, ch * 64, p0);
                    if (ch == 0) {
#pragma unroll
                        for (int c2 = PSM; c2 < 3; c2++)
                            tma_2d(sbase + SM_STAGE + st * STAGE_BYTES + c2 * 8192, &omap, sbase + SM_PBAR + st * 8, c2 * 64, p0);
                    }
                }
                if (++st == 6) st = 0;
            }
            if (!POLLER) finish(nfinish);
        } else if (warp == 2 && (POLLER || attn)) {
            CK(0);
            uint32_t rows = 0, cur = attn ? pair : POS_END;
#pragma unroll 1
            for (int k = 0; cur < POS_END; k++) {
                const uint32_t wh = cur >> 7;
                mbar_wait(bars + B_STORED + (k & 1) * 8, (k >> 1) & 1);
                mbar_arrive(bars + B_PUBD + (k & 1) * 8);
                rows = rows * 128 + wh + 1;
                cur = k + 1 < NSTATIC ? pos_add(cur, P.npair) : lds16v(bars + B_DYN + (k + 1 - NSTATIC) * 2);
                if (rows >= (1u << (7 * PUBN - 7)) || k < 2 || cur >= (NWS - PUBT) * 128) {
                    asm volatile("fence.release.gpu;\n" ::: "memory");
#pragma unroll 1
                    for (; rows; rows >>= 7)
                        asm volatile("red.relaxed.gpu.global.add.u32 [%0], 1;\n" :: "l"(g_cnt + ((rows & 127) - 1)) : "memory");
                }
                TR(24, k);
                CK(k + 1);
                if (k == 30) { ST(9); SC(29); }
                if (k == 60) { ST(10); SC(30); }
                if (k == 90) { ST(11); SC(31); }
            }
            ST(14);
            const int r1 = attn ? NWS - 1 : min((64 * P.t1 - 1) / (7 * IMG), NWS - 1);
            if (NOLD && attn) {
#pragma unroll 1
                for (uint32_t n = 0; n < (1u << 24) && (int)lds32v(bars + B_ROWS) < 0; n++) {}
            }
            int rs = attn ? min(64 * P.t1 / (7 * IMG), NWS - 1) : 64 * NOLD / (7 * IMG);
            if (WPOLL && attn) {
#pragma unroll 1
                for (uint32_t n = 0; n < (1u << 24) && lds32v(bars + B_ROWS + 8) == 0; n++) {}
                rs = max(rs, (int)lds32v(bars + B_ROWS) + 1);
            }
#pragma unroll 1
            for (int r = rs; r <= r1; r++) {
#pragma unroll 1
                for (uint32_t n = 0; n < (1u << 22); n++) {
                    uint32_t a;
                    asm volatile("ld.relaxed.gpu.global.u32 %0, [%1];\n" : "=r"(a) : "l"(g_cnt + r) : "memory");
                    if (a >= P.need) break;
                    __nanosleep(64);
                }
                asm volatile("fence.acquire.gpu;\n" ::: "memory");
                asm volatile("fence.proxy.async.global;\n" ::: "memory");
                asm volatile("st.volatile.shared.b32 [%0], %1;\n" :: "r"(bars + B_ROWS), "r"(r) : "memory");
                if (r >= 66) ST(20 + r - 66);
            }
            finish(nfinish);
        } else if (warp == 3 && attn) {
            for (int t = 0; t < 3; t++) mbar_arrive_n(bars + B_VFREE + t * 8, 2);
            uint32_t cur = pair;
            auto stored = [&](int k) {
                if (!OSTG) asm volatile("fence.proxy.async.global;\n" ::: "memory");
                mbar_wait(bars + B_PUBD + (k & 1) * 8, ((k >> 1) + 1) & 1);
                mbar_arrive(bars + B_STORED + (k & 1) * 8);
            };
            bool pend = false;
#pragma unroll 1
            for (int k = 0; cur < POS_END; k++) {
                const int wh = cur >> 7, ww = cur & 127;
                const uint32_t src = sbase + SM_V + (k & 3) * O_STRIDE;
                const int x0 = 7 * ww + 3, y0 = 7 * wh + 3;
                mbar_wait(bars + B_ODONE + (k & 3) * 8, (k >> 2) & 1);
                if (!(WFEN & 2) && !OSTG) fence_async_smem();
                TR(22, k);
                if (ww == NWS - 1) {
#pragma unroll 1
                    for (int i = 0; i < 7; i++)
                        tma_store_4d(&smapw, src + ((7 * i + 4) & ~1) * 192, 0, 3 * half, ~i & 1, y0 + i >= IMG ? y0 + i - IMG : y0 + i);
                    asm volatile("cp.async.bulk.commit_group;\n" ::: "memory");
                    asm volatile("cp.async.bulk.wait_group 0;\n" ::: "memory");
                }
                tma_store_4d(&smap, src, 0, 3 * half, x0, y0);
                if (wh == NWS - 1) tma_store_4d(&smap3, src + 28 * 192, 0, 3 * half, x0, 0);
                if (!OSTG) asm volatile("cp.async.bulk.commit_group;\n" ::: "memory");
                if (SPIPE && !SPORD && pend) {
                    asm volatile("cp.async.bulk.wait_group 1;\n" ::: "memory");
                    stored(k - 1);
                }
                if (!OSTG) asm volatile("cp.async.bulk.wait_group.read 0;\n" ::: "memory");
                {
                    const int row0 = (k + 4) * TOK;
                    mbar_arrive_n(bars + B_VFREE + ((row0 >> 6) & 3) * 8, ((row0 & 63) >= 64 - TOK && (row0 & 63) < TOK) ? 2 : 1);
                }
                TR(23, k);
                cur = k + 1 < NSTATIC ? pos_add(cur, P.npair) : lds16v(bars + B_DYN + (k + 1 - NSTATIC) * 2);
                if (SPIPE && SPORD && pend) {
                    asm volatile("cp.async.bulk.wait_group 1;\n" ::: "memory");
                    stored(k - 1);
                }
                pend = false;
                if (SPIPE && cur < POS_END) {
                    uint32_t c0, c1;
                    asm volatile("mov.u32 %0, %%clock;\n" : "=r"(c0) :: "memory");
                    do {
                        pend = mbar_test(bars + B_ODONE + ((k + 1) & 3) * 8, ((k + 1) >> 2) & 1);
                        asm volatile("mov.u32 %0, %%clock;\n" : "=r"(c1) :: "memory");
                    } while (!pend && c1 - c0 < (uint32_t)SPIPE);
                }
                if (!pend) {
                    if (!OSTG) asm volatile("cp.async.bulk.wait_group 0;\n" ::: "memory");
                    stored(k);
                }
            }
            mbar_arrive(sbase + SM_PBAR + 96);
        }
        if (PSTORE && warp == 1) {
            PROJ_SCHEDULE
            int st = 0, prev = -1, done = 0;
            uint32_t ph = 0;
            if (bid == gridDim.x - 1) { g_guard[2] = 0; __threadfence(); }
#pragma unroll 1
            for (int u = tile0; u < tend; u += tstep) {
                const int t = (NOLD && u < P.t1) ? u - told : u;
                const int p0 = (t < TILES_A) ? SEG_B + 64 * (t & PWRAP) : 64 * (t - TILES_A);
                mbar_wait(sbase + SM_PBAR + 104 + st * 8, ph);
                if (!(WFEN & 1)) fence_async_smem();
                if (!at) TR(22, (t - tile0) / tstep);
                if (!at && done == 40 * PSM) ST(9);
                if (!at && done == 90 * PSM) ST(10);
                if (!at && done == 130 * PSM) ST(11);
                if (!at && done == 140 * PSM) ST(12);
#pragma unroll
                for (int ch = 0; ch < PSM; ch++) {
                    asm volatile("cp.async.bulk.tensor.2d.global.shared::cta.tile.bulk_group.L2::cache_hint [%0, {%2, %3}], [%1], %4;\n"
                                 :: "l"(reinterpret_cast<uint64_t>(t < TILES_A ? &omap : &omapb)),
                                    "r"(cl(sbase + SM_STAGE + st * STAGE_BYTES + ch * 8192)), "r"(ch * 64), "r"(p0), "l"(EVICT_FIRST) : "memory");
                    asm volatile("cp.async.bulk.commit_group;\n" ::: "memory");
                    asm volatile("cp.async.bulk.wait_group.read %0;\n" :: "n"(PCHUNK) : "memory");
                    asm volatile("st.volatile.shared.b32 [%0], %1;\n" :: "r"(sbase + SM_PBAR + 48), "r"(max(done + ch + 1 - PCHUNK, 0)) : "memory");
                }
                done += PSM;
                if (!mbar_test(sbase + SM_PBAR + 104 + (st == 5 ? 0 : st + 1) * 8, st == 5 ? ph ^ 1 : ph)) {
                    if (PCHUNK > 1) {
                        asm volatile("cp.async.bulk.wait_group.read 1;\n" ::: "memory");
                        asm volatile("st.volatile.shared.b32 [%0], %1;\n" :: "r"(sbase + SM_PBAR + 48), "r"(done - 1) : "memory");
                    }
                    asm volatile("cp.async.bulk.wait_group.read 0;\n" ::: "memory");
                    asm volatile("st.volatile.shared.b32 [%0], %1;\n" :: "r"(sbase + SM_PBAR + 48), "r"(done) : "memory");
                }
                prev = st;
                if (++st == 6) { st = 0; ph ^= 1; }
            }
            mbar_wait(sbase + SM_PBAR + 56, 0);
            asm volatile("fence.release.gpu;\n" ::: "memory");
            asm volatile("cp.async.bulk.wait_group 0;\n" ::: "memory");
            asm volatile("red.relaxed.gpu.global.add.u32 [%0], %1;\n" :: "l"(g_guard), "r"(bid == 0 ? 257 - gridDim.x : 1) : "memory");
            TR(30, 0);
            ST(13);
        }
        return;
    }
    bool bad = false;
    if (!attn) {
        asm volatile("setmaxnreg.inc.sync.aligned.u32 160;\n");
        uint32_t lo = 0x7F807F80u, hi = 0;
#pragma unroll 1
        for (int i = (role - 2 * P.npair) * 384 + tid; i < 192 * 96; i += (gridDim.x - 2 * P.npair) * 384) {
            const bool o = i >= 192 * 72;
            const uint4 w = o ? reinterpret_cast<const uint4*>(P.wo)[i - 192 * 72] : reinterpret_cast<const uint4*>(P.wqkv)[i];
            const uint32_t m = __vmaxu2(__vmaxu2(w.x & 0x7FFF7FFFu, w.y & 0x7FFF7FFFu), __vmaxu2(w.z & 0x7FFF7FFFu, w.w & 0x7FFF7FFFu));
            lo = __vminu2(lo, m);
            hi = __vmaxu2(hi, m + (o ? 0x02000200u : 0u));
        }
        bad = __vminu2(lo, 0x38803880u) != 0x38803880u || __vmaxu2(hi, 0x42004200u) != 0x42004200u;
    } else if (wg == 0) {
        float qs = 1.f;
        if (c < 2) qs = round_bf16(expf(round_bf16(fminf(fmaxf(c ? bf16hi(rc) : bf16lo(rc), -100.f), 4.6052f)))) * LOG2E;
        asm volatile("" : "+f"(qs) :: "memory");
        if (GLATE == 1) permute_w();
        TR(26, 28);
        asm volatile("setmaxnreg.inc.sync.aligned.u32 %0;\n" :: "n"(REG_G));
        TR(26, 29);
        uint32_t xa[8][4];
        uint32_t qk[2][48], vv[24];
        uint32_t rho = warp * 16 + (lane & 15), rq = warp * 16 + g;
        uint32_t rx = rho + 3 * TOK - (rho >= TOK ? 4 * TOK : 0);
        uint32_t hi = lane >> 4, lane0 = lane == 0, c2 = 2 * c;
        asm volatile("" : "+r"(hi), "+r"(lane0), "+r"(c2));
        auto row_addr = [&](uint32_t (&ax)[4], uint32_t r) {
            ax[0] = sbase + SM_QK + r * 128 + (((r & 7) ^ hi) << 4);
#pragma unroll
            for (int i = 1; i < 4; i++) ax[i] = ax[0] ^ (32 * i);
        };
#define XADDR(ax, s) ((ax)[((s) & 3) ^ (((s) >> 1) & 2)] + ((s) >> 2) * QK_CHUNK)
        uint64_t descW = make_desc(sb0, W_ATOM, 256, 3);
        const uint32_t zero = (uint32_t)P.z1;
        const uint32_t vbase = sbase + SM_V + (lane >> 4) * GRP;
        uint32_t ones = 0x3C003C00u | zero, ones2 = ones | (zero >> 1);
        asm volatile("" : "+r"(ones), "+r"(ones2));
        const uint32_t mh[2] = {0xFFFF0000u, 0xFFFF0000u}, ml[2] = {0x10000u, 0x10000u};
        uint32_t raw[48], xb[4][4];
        auto cvt = [&](auto& dst, int d0, const uint32_t (&raw)[48], int s0) {
#pragma unroll
            for (int s = 0; s < 4; s++) {
#pragma unroll
                for (int i = 0; i < 4; i++)
                    dst[d0 + s][i] = pack_f16(__uint_as_float(raw[4 * (s0 + s) + i] * ml[i & 1]), __uint_as_float(raw[4 * (s0 + s) + i] & mh[i & 1]));
                reg_fence(dst[d0 + s]);
            }
        };
        uint32_t ax[4];
        auto load_x = [&](int s0) {
#pragma unroll
            for (int s = s0; s < s0 + 4; s++) ldsm_x4(reinterpret_cast<uint32_t (&)[4]>(raw[4 * s]), XADDR(ax, s));
        };
        auto next_x = [&]() {
            row_addr(ax, rx);
            rx += 64;
            if (rx >= 4 * TOK) rx -= 4 * TOK;
        };
        if (!GLATE) permute_w();
        TR(26, 10);
        mbar_wait(bars + B_XFULL, 0);
        next_x();
        load_x(0); load_x(4); load_x(8);
        cvt(xa, 0, raw, 0); cvt(xa, 4, raw, 4); cvt(xb, 0, raw, 8);
        __syncwarp();
        mbar_arrive_if(bars + B_QKFREE + 24, lane0);
        TR(26, 8);
        asm volatile("bar.sync 7, 384;\n" ::: "memory");
        fence_async_smem();
        TR(26, 9);
        wgmma_fence();
        mma_qk_first<SM_WA, 0>(qk[0], xa, descW);
        mma_qk_next<SM_WA + 2048, 4>(qk[0], xa, descW);
        mma_qk_next<SM_WA + 4096, 0>(qk[0], xb, descW);
        wgmma_commit();
        TR(26, 11);
        asm volatile("bar.sync 11, 384;\n" ::: "memory");
        fence_async_smem();
        TR(26, 12);
        wgmma_fence();
        mma_v_first<SM_WV, 0>(vv, xa, descW);
        mma_v_next<SM_WV + 2048, 4>(vv, xa, descW);
        wgmma_commit();
        wgmma_wait<0>();
        ST(1); SC(28);
        uint32_t xok = 0, range = 0;
        int ntiles;
        auto body = [&](auto U_, int t) {
            constexpr int U = decltype(U_)::value;
            uint32_t (&cur)[48] = qk[U];
            uint32_t (&nxt)[48] = qk[U ^ 1];
            descW += P.z1;
            const uint32_t bt = bars + (t & 3) * 8, pt = (t >> 2) & 1;
            TR(1, t);
            next_x();
            mbar_wait_unless(xok, bars + ((t + 1) & 3) * 8 + B_XFULL, ((t + 1) >> 2) & 1);
            TR(2, t);
            load_x(0);
            wgmma_fence();
            mma_v_next<SM_WV + 4096, 0>(vv, xb, descW);
            wgmma_commit();
            load_x(4);
            uint32_t av = vbase + rho * 16 + ((rho * 1338) >> 16) * (V_STRIDE - GRP);
            uint32_t aq[2];
            aq[0] = sbase + SM_QK + rq * 128 + (((rq & 7) ^ c2) << 4);
            aq[1] = aq[0] + 1024;
            if (rq >= 4 * TOK - 8) aq[1] = (aq[1] - QK_CHUNK) ^ 64;
            rho += 64;
            if (rho >= 4 * TOK) rho -= 4 * TOK;
            rq += 64;
            if (rq >= 4 * TOK) rq -= 4 * TOK;
            asm volatile("" : "+r"(av), "+r"(aq[0]), "+r"(aq[1]), "+r"(rho), "+r"(rq));
            cvt(xa, 0, raw, 0);
            wgmma_fence();
            mma_qk_first<SM_WA, 0>(nxt, xa, descW);
            wgmma_commit();
            load_x(8);
            __syncwarp();
            mbar_arrive_if(bars + B_XCONS, lane0);
            const uint32_t vok = VLATE ? 0 : mbar_test(bt + B_VFREE, pt);
            ntiles = lds32v(bars + B_NTILES);
            cvt(xa, 4, raw, 4);
            wgmma_wait<2>();
            reg_fence(cur);
            uint32_t ss[4];
#pragma unroll
            for (int i = 0; i < 4; i++) ss[i] = hmul2_f16(cur[i], cur[i]);
#pragma unroll
            for (int i = 4; i < ((EXP & 16) ? 4 : 48); i++) ss[i & 3] = hfma2_f16(cur[i], cur[i], ss[i & 3]);
            ss[0] = hadd2_f16(ss[0], ss[2]);
            ss[1] = hadd2_f16(ss[1], ss[3]);
            const float s0 = f16lo(ss[0]) + f16hi(ss[0]) + 1e-12f, s1 = f16lo(ss[1]) + f16hi(ss[1]) + 1e-12f;
            range = __viaddmax_u32(__float_as_uint(s0), 0u - SS_MIN, __viaddmax_u32(__float_as_uint(s1), 0u - SS_MIN, range));
            const float f0 = rsqrt_ftz(s0) * qs, f1 = rsqrt_ftz(s1) * qs;
            uint32_t f2[2] = {pack_f16_sat(f0, f0), pack_f16_sat(f1, f1)};
            reg_fence(f2);
            if (NRM == 2) sched_fence16(zero, reinterpret_cast<const uint32_t (&)[4][4]>(xa[4]), f2[0], f2[1]);
            TR(5, t);
            wgmma_fence();
            mma_qk_next<SM_WA + 2048, 4>(nxt, xa, descW);
            wgmma_commit();
            wgmma_wait<2>();
            reg_fence(cur);
            reg_fence(vv);
            TR(6, t);
            mbar_wait_unless(vok, bt + B_VFREE, pt);
            if (U == 0 && t == 2) asm volatile("bar.sync 3, 384;\n" ::: "memory");
#pragma unroll
            for (int p = 0; p < 6; p++)
                stsm_x4(av + (p < 3 ? 2 * p : 2 * p + 1) * GRP, vv[4 * p], vv[4 * p + 1], vv[4 * p + 2], vv[4 * p + 3]);
            if (!NOONES && (OSTG < 2 || t < 4)) stsm_x2(av + 6 * GRP, ones, ones2);
            const uint32_t cok = mbar_test(bars + B_XCONS, U);
            TR(4, t);
            cvt(xb, 0, raw, 8);
            if (GSF) sched_fence16(zero, xb, f2[0], f2[1]);
            if (!GS0) wgmma_fence();
            mma_v_first<SM_WV, 0>(vv, xa, descW);
            wgmma_commit();
            mbar_wait_unless_dep(cok, bars + B_XCONS, U, zero, f2[0], f2[1], aq[0], aq[1]);
            TR(7, t);
#pragma unroll
            for (int u = 0; u < 6; u++) {
                if (GS0 && u == GS0) {
                    wgmma_fence();
                    mma_v_first<SM_WV, 0>(vv, xa, descW);
                    wgmma_commit();
                }
                if (GSP && u == GSP) {
                    wgmma_fence();
                    mma_v_next<SM_WV + 2048, 4>(vv, xa, descW);
                    wgmma_commit();
                }
#pragma unroll
                for (int r = 0; r < 2; r++)
                    sts128((aq[r] ^ ((u & 1) * 16 + (u & 2) * 32)) + (u >> 1) * QK_CHUNK,
                           hmul2_f16(cur[8 * u + r], f2[r]), hmul2_f16(cur[8 * u + 2 + r], f2[r]),
                           hmul2_f16(cur[8 * u + 4 + r], f2[r]), hmul2_f16(cur[8 * u + 6 + r], f2[r]));
            }
            __syncwarp();
            mbar_arrive_if(bt + B_QKRAW, lane0);
            TR(3, t);
            wgmma_fence();
            xok = mbar_test(bars + ((t + 2) & 3) * 8 + B_XFULL, ((t + 2) >> 2) & 1);
            mma_qk_next<SM_WA + 4096, 0>(nxt, xb, descW);
            wgmma_commit();
            TR(0, t + 1);
            wgmma_wait<GORD == 4 ? 2 : 1>();
        };
        for (int t = 0;; t += 2) {
            body(std::integral_constant<int, 0>(), t);
            if (__any_sync(0xffffffffu, t + 1 >= ntiles)) { wgmma_wait<0>(); reg_fence(qk[1]); break; }
            body(std::integral_constant<int, 1>(), t + 1);
            if (__any_sync(0xffffffffu, t + 2 >= ntiles)) { wgmma_wait<0>(); reg_fence(qk[0]); break; }
        }
        reg_fence(vv);
        bad = range >= F32_INF - SS_MIN;
        __syncwarp();
        mbar_arrive_if(bars + B_GDONE, lane0);
        asm volatile("setmaxnreg.dec.sync.aligned.u32 160;\n");
    } else {
        if (REG_A > 128) asm volatile("setmaxnreg.inc.sync.aligned.u32 %0;\n" :: "n"(REG_A));
        if (REG_A < 128) asm volatile("setmaxnreg.dec.sync.aligned.u32 %0;\n" :: "n"(REG_A));
        {
            const float c0 = bf16lo(rc), c1 = bf16hi(rc);
            float a0 = 0.f, a1 = 0.f;
#pragma unroll
            for (int u = 0; u < 16; u++) {
                const uint32_t p = reinterpret_cast<const uint32_t*>(w1)[u >> 1], q = reinterpret_cast<const uint32_t*>(w1)[8 + (u >> 1)];
                float h = round_bf16(c0 * ((u & 1) ? bf16hi(p) : bf16lo(p)) + c1 * ((u & 1) ? bf16hi(q) : bf16lo(q)));
                h = fmaxf(h, 0.f);
                a0 += h * bf16lo(w2[u]);
                a1 += h * bf16hi(w2[u]);
            }
            const float s0 = round_bf16(__fdividef(1.f, 1.f + expf(-round_bf16(a0))));
            const float s1 = round_bf16(__fdividef(1.f, 1.f + expf(-round_bf16(a1))));
            if (tid - 128 < 169) sts32(sbase + SM_TAB + (tid - 128) * 4, pack_f16(16.f * LOG2E * s0, 16.f * LOG2E * s1));
        }
        if (GLATE == 2) permute_a(); else permute_w();
        asm volatile("bar.arrive 7, 384;\n" ::: "memory");
        TR(26, 72 + wg);
        {
            uint4 w[9];
            const int rg = ((tid >> 5) - 4) * 3;
            mbar_wait(bars + B_WFULL, 0);
#pragma unroll
            for (int i = 0; i < 9; i++) w[i] = *reinterpret_cast<const uint4*>(smem + SM_WV + raw_w(rg + i / 3, (i % 3) * 4 + (lane >> 3)));
            asm volatile("bar.sync 1, 256;\n" ::: "memory");
            const uint32_t d = sbase + SM_WV + (lane >> 4) * W_ATOM + (rg * 8 + (lane & 7)) * 32 + (((lane >> 2) ^ (lane >> 3)) & 1) * 16;
#pragma unroll
            for (int i = 0; i < 9; i++)
                sts128(d + (i % 3) * 2 * W_ATOM + (i / 3) * 256, bf2h(w[i].x), bf2h(w[i].y), bf2h(w[i].z), bf2h(w[i].w));
            asm volatile("bar.arrive 11, 384;\n" ::: "memory");
            TR(26, 76 + wg);
        }
        uint32_t bias[28];
        {
            const uint32_t* tab = reinterpret_cast<const uint32_t*>(smem + SM_TAB);
#pragma unroll
            for (int rh = 0; rh < 2; rh++) {
#pragma unroll
                for (int j = 0; j < 6; j++) {
                    const uint32_t lo = tab[min(max(ridx[13 * rh + 2 * j], 0), 168)];
                    const uint32_t hi = tab[min(max(ridx[13 * rh + 2 * j + 1], 0), 168)];
                    bias[2 * j + rh]      = prmt(lo, hi, 0x5410);
                    bias[14 + 2 * j + rh] = prmt(lo, hi, 0x7632);
                }
                const uint32_t l = (c == 0) ? tab[min(max(ridx[13 * rh + 12], 0), 168)] : 0xFC00FC00u;
                bias[12 + rh] = (l & 0xFFFFu) | 0xFC000000u;
                bias[26 + rh] = (l >> 16) | 0xFC000000u;
            }
        }
#pragma unroll
        for (int i = 0; i < 28; i++)
            if (warp * 16 + g + (i & 1) * 8 >= TOK && i % 14 < 12) bias[i] = 0xFC00FC00u;
        reg_fence(bias);
        asm volatile("bar.arrive 3, 384;\n" ::: "memory");
        uint32_t os[3];
#pragma unroll
        for (int p = 0; p < 3; p++) {
            const int orow = warp * 16 + (lane & 7);
            uint32_t a = orow * 192 + p * 64;
            a += (((lane >> 3) ^ (a >> 7)) & 3) << 4;
            os[p] = sbase + SM_V + (wg - 1) * O_STRIDE + (orow < TOK ? a : 74 * 128 + (a & 127));
        }
        reg_fence(os);
        const int orow = warp * 16 + (lane & 7);
        const bool ov = orow < TOK;
        const uint32_t orel = sbase + (ov ? SM_V + orow * O_PITCH + (OONE == 2 && orow >= 28 ? 64 : 0) : SM_DUMP + ((lane + (OONE == 2 ? 7 : 3)) & 7) * 16) + (lane >> 3) * 16;
        const uint32_t oup = (OONE == 2 && warp == 1) ? (lane & 4) * 16 : 0;
        const uint32_t omul = ov ? O_STRIDE : 0;
        const uint64_t descK0 = make_desc(sb0 + SM_QK, 16, 1024, 1);
        const uint64_t descV0 = make_desc(sb0 + SM_V, 128, GRP, 0);
        const uint32_t mrel = sbase + SM_MASK + t0 * 98 + c * 4;
        const uint32_t mrow = (warp < 3) ? 784 : 0;
        const uint32_t pmask = (c == 0) ? 0xFFFFu : 0u;

        uint32_t mstate = 0;
        int nwin;
        const uint32_t barw = bars + (wg - 1) * 8;
        const uint64_t descKw = descK0 + (uint64_t)((wg - 1) * (XCH >> 4)), descVw = descV0 + (uint64_t)((wg - 1) * (V_STRIDE >> 4));
        uint32_t oa = orel + (wg - 1) * omul;
        const uint32_t oflip = oa ^ (oa + 2 * omul);
        uint32_t qok = 0;
        const uint32_t zero = (uint32_t)P.z1;
        auto window = [&](auto IT_, int k) {
            constexpr int IT = decltype(IT_)::value;
            const uint32_t bar = barw + 16 * IT;
            const int tl = (k * TOK + TOK - 1) >> 6, tn = ((k + 2) * TOK + TOK - 1) >> 6;
            const uint32_t bt = bars + (tl & 3) * 8, pt = (tl >> 2) & 1;
            TR(8, k);
            uint32_t sc0[14], sc1[14];
#pragma unroll
            for (int i = 0; i < 14; i++) { sc0[i] = bias[i]; sc1[i] = bias[14 + i]; }
            if (mstate < 32 * k + 32) {
#pragma unroll 1
                for (uint32_t n = 0; n < (1u << 22) && mstate < 32 * k + 16; n++) mstate = lds32v(bars + B_MSTATE);
                if (mstate < 32 * k + 32) {
                    mbar_wait(bars + B_MFULL, mstate & 1);
                    const uint32_t ma = mrel + (mstate & 14);
#pragma unroll
                    for (int i = 0; i < 14; i++) {
                        const uint32_t lo = lds16(ma + (i & 1) * mrow + (i >> 1) * 16);
                        const uint32_t hi = i < 12 ? lds16(ma + (i & 1) * mrow + (i >> 1) * 16 + 2) : 0u;
                        const uint32_t mk = pack_f16(__uint_as_float(lo << 16), __uint_as_float(hi << 16));
                        sc0[i] = hfma2_f16(mk, 0x3DC53DC5u, sc0[i]);
                        sc1[i] = hfma2_f16(mk, 0x3DC53DC5u, sc1[i]);
                    }
                    __syncwarp();
                    if (lane == 0) mbar_arrive(bars + B_MCONS);
                }
            }
            reg_fence(sc0);
            reg_fence(sc1);
            TR(10, k);
            mbar_wait_unless(qok, bt + B_QKRAW, pt);
            ADEL(3);
            fence_async_smem();
            TR(11, k);
            if (ABAR & 1) ABARRIER();
            wgmma_fence();
#if !(EXP & 128)
            mma_s0_f16<2 * IT * XCH, 2 * IT * XCH>(sc0, descKw, descKw);
            mma_s1_f16<2 * IT * XCH, 2 * IT * XCH>(sc1, descKw, descKw);
#endif
            wgmma_commit();
            uint32_t m[2];
            auto rowmax = [&](const uint32_t (&S)[14], int h) {
                uint32_t a[2];
#pragma unroll
                for (int o = 0; o < 2; o++)
                    a[o] = hmax2_f16(hmax2_f16(hmax2_f16(hmax2_f16(S[o], S[2 + o]), S[4 + o]), hmax2_f16(hmax2_f16(S[6 + o], S[8 + o]), S[10 + o])), S[12 + o]);
                m[h] = hmax2_f16(prmt(a[0], a[1], 0x5410), prmt(a[0], a[1], 0x7632));
            };
            wgmma_wait<0>();
            reg_fence(sc0);
            reg_fence(sc1);
            if (lane == 0) mbar_arrive(bar + B_QKFREE);
            TR(12, k);
            ADEL(1);
            rowmax(sc0, 0);
            rowmax(sc1, 1);
#pragma unroll
            for (int i = 0; i < 2; i++) m[i] = hmax2_f16(m[i], __shfl_xor_sync(0xffffffffu, m[i], 1));
#pragma unroll
            for (int i = 0; i < 2; i++) m[i] = hmax2_f16(m[i], __shfl_xor_sync(0xffffffffu, m[i], 2));
#pragma unroll
            for (int i = 0; i < ASHFL; i++) m[i & 1] = hmax2_f16(m[i & 1], __shfl_xor_sync(0xffffffffu, m[i & 1], 1));
            auto probs = [&](const uint32_t (&S)[14], uint32_t mm, uint32_t (&pa)[4][4]) {
#pragma unroll
                for (int j = 0; j < 6; j++) {
                    pa[j >> 1][(j & 1) * 2]     = ex2_f16x2(hsub2_bc<0>(S[2 * j], mm));
                    pa[j >> 1][(j & 1) * 2 + 1] = ex2_f16x2(hsub2_bc<1>(S[2 * j + 1], mm));
                }
                pa[3][0] = ex2_f16lo(hsub2_bc<0>(S[12], mm)) & pmask;
                pa[3][1] = ex2_f16lo(hsub2_bc<1>(S[13], mm)) & pmask;
                pa[3][2] = 0u; pa[3][3] = 0u;
                reg_fence(pa);
            };
            uint32_t pa0[4][4], pa1[4][4];
            uint32_t o0[NOONES ? 12 : 14], o1[NOONES ? 12 : 14];
            auto rowsum = [&](const uint32_t (&pa)[4][4]) {
                uint32_t a[2];
#pragma unroll
                for (int o = 0; o < 2; o++)
                    a[o] = hadd2_f16(hadd2_f16(hadd2_f16(pa[0][o], pa[0][2 + o]), hadd2_f16(pa[1][o], pa[1][2 + o])),
                                     hadd2_f16(hadd2_f16(pa[2][o], pa[2][2 + o]), pa[3][o]));
                return hadd2_f16(prmt(a[0], a[1], 0x5410), prmt(a[0], a[1], 0x7632));
            };
            uint32_t ls[2];
            TR(13, k);
            TR(14, k);
            auto pstep = [&](const uint32_t (&S)[14], uint32_t mm, uint32_t (&pa)[4], int s) {
                if (s < 3) {
#pragma unroll
                    for (int j = 0; j < 2; j++) {
                        pa[2 * j]     = ex2_f16x2(hsub2_bc<0>(S[4 * s + 2 * j], mm));
                        pa[2 * j + 1] = ex2_f16x2(hsub2_bc<1>(S[4 * s + 2 * j + 1], mm));
                    }
                } else {
                    pa[0] = ex2_f16lo(hsub2_bc<0>(S[12], mm)) & pmask;
                    pa[1] = ex2_f16lo(hsub2_bc<1>(S[13], mm)) & pmask;
                    pa[2] = 0u; pa[3] = 0u;
                }
                reg_fence(pa);
            };
            pstep(sc0, m[0], pa0[3], 3); pstep(sc0, m[0], pa0[0], 0);
            wgmma_fence();
            mma_pv1f<2 * IT * V_STRIDE + 768, 3>(o0, pa0, descVw);
            mma_pv1n<2 * IT * V_STRIDE, 0>(o0, pa0, descVw);
            pstep(sc0, m[0], pa0[1], 1);
            wgmma_fence();
            mma_pv1n<2 * IT * V_STRIDE + 256, 1>(o0, pa0, descVw);
            pstep(sc0, m[0], pa0[2], 2);
            wgmma_fence();
            mma_pv1n<2 * IT * V_STRIDE + 512, 2>(o0, pa0, descVw);
            wgmma_commit();
            pstep(sc1, m[1], pa1[3], 3); pstep(sc1, m[1], pa1[0], 0);
            wgmma_fence();
            mma_pv1f<2 * IT * V_STRIDE + (NOONES ? 7 : 6) * GRP + 768, 3>(o1, pa1, descVw);
            mma_pv1n<2 * IT * V_STRIDE + (NOONES ? 7 : 6) * GRP, 0>(o1, pa1, descVw);
            pstep(sc1, m[1], pa1[1], 1);
            wgmma_fence();
            mma_pv1n<2 * IT * V_STRIDE + (NOONES ? 7 : 6) * GRP + 256, 1>(o1, pa1, descVw);
            pstep(sc1, m[1], pa1[2], 2);
            wgmma_fence();
            mma_pv1n<2 * IT * V_STRIDE + (NOONES ? 7 : 6) * GRP + 512, 2>(o1, pa1, descVw);
            wgmma_commit();
            uint32_t w[24];
            wgmma_wait<PVLATE == 2 ? 0 : 1>();
            reg_fence(o0);
            {
                const float il0 = rcp_ftz(f16lo(o0[12])), il1 = rcp_ftz(f16lo(o0[13]));
                const uint32_t l0 = pack_f16(il0, il0), l1 = pack_f16(il1, il1);
#pragma unroll
                for (int j = 0; j < 12; j++) w[j] = hmul2_f16(o0[j], (j & 1) ? l1 : l0) & ~(OMASK * 0x10001u);
            }
            wgmma_wait<0>();
            reg_fence(o1);
            TR(15, k);
            ADEL(2);
            asm volatile("{\n.reg .pred p;\nsetp.eq.u32 p, %0, 1;\n@p bar.sync 4, 128;\n@!p bar.sync 5, 128;\n}\n"
                         :: "r"(wg) : "memory");
            qok = mbar_test(bars + (tn & 3) * 8 + B_QKRAW, (tn >> 2) & 1);
            asm volatile("ld.volatile.shared.v2.b32 {%0, %1}, [%2];\n" : "=r"(mstate), "=r"(nwin) : "r"(bars + B_MSTATE) : "memory");
            {
                const float il2 = rcp_ftz(f16lo(o1[0])), il3 = rcp_ftz(f16lo(o1[1]));
                const uint32_t l2 = pack_f16(il2, il2), l3 = pack_f16(il3, il3);
#pragma unroll
                for (int j = 0; j < 12; j++) w[12 + j] = hmul2_f16(o1[j + 2], (j & 1) ? l3 : l2) & ~(OMASK * 0x10001u);
#pragma unroll
                for (int p = 0; p < 3; p++) stsm_x4(os[p] + 2 * IT * O_STRIDE, w[8 * p], w[8 * p + 2], w[8 * p + 4], w[8 * p + 6]);
#pragma unroll
                for (int p = 0; p < 3; p++) stsm_x4_if(warp < 3, os[p] + 2 * IT * O_STRIDE + 8 * 192, w[8 * p + 1], w[8 * p + 3], w[8 * p + 5], w[8 * p + 7]);
            }
            if (WFEN & 2) fence_async_smem();
            __syncwarp();
            if (lane == 0) mbar_arrive(bar + B_ODONE);
            TR(16, k);
        };
        for (int k = wg - 1;; k += 4) {
            window(std::integral_constant<int, 0>(), k);
            if (__any_sync(0xffffffffu, k + 2 >= nwin)) break;
            window(std::integral_constant<int, 1>(), k + 2);
            if (__any_sync(0xffffffffu, k + 4 >= nwin)) break;
        }
        (void)zero;
        asm volatile("setmaxnreg.inc.sync.aligned.u32 160;\n");
    }

    TR(27, wg);
    ST(2 + wg);
    uint32_t tag, seen;
    asm volatile("ld.relaxed.gpu.global.v2.u32 {%0, %1}, [%2];\n" : "=r"(tag), "=r"(seen) : "l"(g_guard) : "memory");
    if (attn || !MPRE) {
        __syncwarp();
        if (lane == 0) mbar_arrive(sbase + SM_PBAR + 96);
    }
    if (!attn) {
        uint4 wor[2][6];
        const int worow = OSTG ? ((tid >> 2) & ~30) | ((tid & 24)) | ((tid >> 4) & 6) : tid >> 2;
#pragma unroll
        for (int i = 0; i < 12; i++)
            ldg_nc_v4(reinterpret_cast<uint32_t (&)[4]>(wor[i / 6][i % 6]), P.wo + (worow + i / 6 * 96) * 192 + 32 * (i % 6) + 8 * c);
        auto prepare_wo = [&]() {
#pragma unroll
        for (int rh = 0; rh < 2; rh++) {
            const int row = (tid >> 2) + 96 * rh;
            const uint4 (&w)[6] = wor[rh];
            float s = 0.f;
#pragma unroll
            for (int a = 0; a < 6; a++)
                s += ((bf16lo(w[a].x) + bf16hi(w[a].x)) + (bf16lo(w[a].y) + bf16hi(w[a].y))) +
                     ((bf16lo(w[a].z) + bf16hi(w[a].z)) + (bf16lo(w[a].w) + bf16hi(w[a].w)));
            s += __shfl_xor_sync(0xffffffffu, s, 1);
            s += __shfl_xor_sync(0xffffffffu, s, 2);
            s *= (1.f / 192.f);
            const uint32_t sw = (row >> 1) & 3;
            const uint32_t d = sbase + SM_WO + row * 64 + ((c ^ sw) << 4), e = sbase + SM_WO + row * 64 + c * 4;
#pragma unroll
            for (int a = 0; a < 6; a++) {
                uint32_t h[4] = {pack_f16(bf16lo(w[a].x) - s, bf16hi(w[a].x) - s), pack_f16(bf16lo(w[a].y) - s, bf16hi(w[a].y) - s),
                                       pack_f16(bf16lo(w[a].z) - s, bf16hi(w[a].z) - s), pack_f16(bf16lo(w[a].w) - s, bf16hi(w[a].w) - s)};
#pragma unroll
                for (int i = 0; i < 4; i++) h[i] = (h[i] + (WMASK + 1) / 2 * 0x10001u) & ~(WMASK * 0x10001u);
                if (a < 2 * PSM) {
                    sts128(d + a * 12288, h[0], h[1], h[2], h[3]);
                } else {
#pragma unroll
                    for (int i = 0; i < 4; i++) sts32(e + a * 12288 + ((i ^ sw) << 4), h[i]);
                }
            }
        }
        fence_async_smem();
        asm volatile("bar.sync 6, 384;\n" ::: "memory");
        if (role == 2 * P.npair && tid == 0) {
            asm volatile("cp.async.bulk.global.shared::cta.bulk_group [%0], [%1], %2;\n"
                         :: "l"(g_wo), "r"(cl(sbase + SM_WO)), "n"(SM_STAGE) : "memory");
            asm volatile("cp.async.bulk.commit_group;\n" ::: "memory");
            if (WOE < 2) {
            asm volatile("cp.async.bulk.wait_group 0;\n" ::: "memory");
            asm volatile("fence.proxy.async.global;\n" ::: "memory");
            asm volatile("st.release.gpu.global.u32 [%0], %1;\n" :: "l"(g_guard + 3), "r"(tag | 255) : "memory");
            }
        }
        };
        {
            const uint32_t wstep = (gridDim.x - 2 * P.npair) * 12, wend = MEND * P.npair;
            const uint32_t mbuf = sbase + (WOE ? SM_STAGE : 0) + (tid >> 5) * MBUFS * M_BUF, mbar = sbase + SM_MBAR + (tid >> 5) * MBUFS * 8;
            uint32_t w = MPRE * P.npair + (role - 2 * P.npair) * 12 + (tid >> 5);
            auto load = [&](uint32_t w, uint32_t i) {
                if (w < wend) {
                    const uint32_t o = (w * 4802u) & ~(MALIGN - 1), n = MALIGN == 16 ? 4816 : ((w * 4802u & ~15u) + 4816 - o + MALIGN - 1) & ~(MALIGN - 1);
                    mbar_arrive_expect_tx(mbar + i * 8, n);
                    asm volatile("cp.async.bulk.shared::cluster.global.mbarrier::complete_tx::bytes.L2::cache_hint [%0], [%1], %3, [%2], %4;\n"
                                 :: "r"(cl(mbuf + i * M_BUF)), "l"(reinterpret_cast<const char*>(P.mask) + o),
                                    "r"(cl(mbar + i * 8)), "r"(n), "l"(EVICT_FIRST) : "memory");
                }
            };
            if (elect_one()) {
                if (MDELAY) __nanosleep(MDELAY);
#pragma unroll 1
                for (int i = 0; i < (MRAMP ? 1 : MBUFS); i++) load(w + i * wstep, i);
            }
            __syncwarp();
            if (WOE) { prepare_wo(); __syncwarp(); }
            uint32_t i = 0, ph = 0;
            const uint32_t wramp = w + (MRAMP - 1) * wstep;
#pragma unroll 1
            for (; w < wend; w += wstep) {
                const uint32_t b = mbuf + i * M_BUF + ((w * 4802u) & (MALIGN - 16));
                mbar_wait(mbar + i * 8, ph);
                uint32_t acc = lds16(b + (lane & 7) * 2 + (lane & 8) * 600);
                if ((lane & 15) - (w & 7) > 8u) acc = 0;
                uint32_t v[10][4];
#pragma unroll
                for (int j = 0; j < 10; j++) lds128(v[j], b + 16 * (j < 9 ? 1 + lane + 32 * j : min(289 + lane, 299)));
#pragma unroll
                for (int j = 0; j < 10; j++) acc |= v[j][0] | v[j][1] | v[j][2] | v[j][3];
                const uint32_t nz = __any_sync(0xffffffffu, (acc & 0x7FFF7FFFu) != 0) ? 1 : 0;
                if (elect_one()) {
                    if (MRAMP && w <= wramp) load(w + wstep, i ^ 1);
                    if (!MRAMP || w >= wramp) load(w + MBUFS * wstep, i);
                    const uint32_t k = w / (uint32_t)P.npair;
                    asm volatile("st.relaxed.gpu.global.u32 [%0], %1;\n" :: "l"(g_mz + (w - k * P.npair) * 128 + k), "r"((tag | 255) - nz) : "memory");
                }
                __syncwarp();
                if (++i == MBUFS) { i = 0; ph ^= 1; }
            }
            if (lane == 0) mbar_arrive(sbase + SM_PBAR + 96);
            if (!WOE) asm volatile("bar.sync 6, 384;\n" ::: "memory");
            if (WOE == 2 && role == 2 * P.npair && tid == 0) {
                asm volatile("cp.async.bulk.wait_group 0;\n" ::: "memory");
                asm volatile("fence.proxy.async.global;\n" ::: "memory");
                asm volatile("st.release.gpu.global.u32 [%0], %1;\n" :: "l"(g_guard + 3), "r"(tag | 255) : "memory");
            }
        }
        if (!WOE) prepare_wo();
        __syncwarp();
    } else {
        mbar_wait(bars + B_WRAW, 1);
    }
    tag |= 255;
    if (bad) g_guard[1] = tag;
    bad |= seen == tag;
    TR(27, 4 + wg);
    if (wg == 0) ST(5);
    {
        PROJ_SCHEDULE
        uint64_t descW = make_desc(sb0 + SM_WO, 12288, 512, 2);
        const uint64_t descA = make_desc(sb0 + SM_STAGE + wg * STAGE_BYTES, 16, 1024, 1);
        const uint32_t bar = sbase + SM_PBAR + wg * 8;
        const uint32_t yrel = sbase + SM_STAGE + wg * STAGE_BYTES + (warp * 16 + (lane & 15)) * 128 + (((lane & 7) ^ (lane >> 4)) << 4);
        uint32_t acch[48];
        uint32_t it = 0;
        for (int u = tile0 + wg * tstep; u < tend; u += 3 * tstep, it++) {
            const int tile = (NOLD && u < P.t1) ? u - told : u;
            descW += P.z1;
            mbar_wait(bar + (it & 1) * 24, (it >> 1) & 1);
            TR(28, it * 3 + wg);
            ST(6 + wg);
            if (it > 0 || wg > 0) asm volatile("bar.sync %0, 256;\n" :: "r"(8 + wg) : "memory");
            wgmma_fence();
            mma_projh<0, 0>(acch, descA + (uint64_t)((it & 1) * (3 * STAGE_BYTES >> 4)), descW);
            wgmma_commit();
            if (u + tstep < tend) asm volatile("bar.arrive %0, 256;\n" :: "r"(wg == 2 ? 8 : 9 + wg) : "memory");
            wgmma_wait<0>();
            reg_fence(acch);
            uint32_t a[4];
#pragma unroll
            for (int i = 0; i < 4; i++) a[i] = hmul2_f16(acch[i], acch[i]);
#pragma unroll
            for (int i = 4; i < 48; i++) a[i & 3] = hfma2_f16(acch[i], acch[i], a[i & 3]);
            float s0 = (f16lo(a[0]) + f16hi(a[0])) + (f16lo(a[2]) + f16hi(a[2])), s1 = (f16lo(a[1]) + f16hi(a[1])) + (f16lo(a[3]) + f16hi(a[3]));
            s0 += __shfl_xor_sync(0xffffffffu, s0, 1);
            s1 += __shfl_xor_sync(0xffffffffu, s1, 1);
            s0 += __shfl_xor_sync(0xffffffffu, s0, 2);
            s1 += __shfl_xor_sync(0xffffffffu, s1, 2);
            if (max(__float_as_uint(s0) - VAR_MIN, __float_as_uint(s1) - VAR_MIN) >= F32_INF - VAR_MIN) {
                const int rem = ((tile < TILES_A) ? NPIX - SEG_B - 64 * tile : SEG_B - 64 * (tile - TILES_A)) - warp * 16 - g;
                if ((__float_as_uint(s0) - VAR_MIN >= F32_INF - VAR_MIN && rem > 0) ||
                    (__float_as_uint(s1) - VAR_MIN >= F32_INF - VAR_MIN && rem > 8)) {
                    bad = true;
                    g_guard[1] = tag;
                }
            }
            const float rs0 = rsqrt_ftz(fmaf(s0, 1.f / 192.f, 1e-5f));
            const float rs1 = rsqrt_ftz(fmaf(s1, 1.f / 192.f, 1e-5f));
            const uint32_t rh[2] = {pack_f16(rs0, rs0), pack_f16(rs1, rs1)};
            auto Y = [&](int i) {
                const uint32_t t = hmul2_f16(acch[i], rh[i & 1]);
                return pack_bf16(f16lo(t), f16hi(t));
            };
            const uint32_t ya = yrel + (it & 1) * 3 * STAGE_BYTES;
            auto direct = [&]() {
                const int p0 = (tile < TILES_A) ? SEG_B + 64 * (tile & PWRAP) : 64 * (tile - TILES_A);
                const int lim = ((tile < TILES_A) ? NPIX : SEG_B) - p0;
                char* const po = reinterpret_cast<char*>(P.out) + (uint32_t)((p0 + warp * 16 + g) * 384 + c * 16);
                const bool v0 = warp * 16 + g < lim, v1 = warp * 16 + g + 8 < lim;
#pragma unroll
                for (int i = 2 * PSM; i < 6; i++) {
                    const int j = 8 * i;
                    stg128_if(v0, po + 64 * i, Y(j), Y(j + 2), Y(j + 4), Y(j + 6));
                    stg128_if(v1, po + 8 * 384 + 64 * i, Y(j + 1), Y(j + 3), Y(j + 5), Y(j + 7));
                }
            };
            if (PSM < 3 && PDF) direct();
#pragma unroll
            for (int p = 0; p < 4 * PSM; p++)
                stsm_x4((ya ^ (32 * (p & 3))) + (p >> 2) * 8192, Y(4 * p), Y(4 * p + 1), Y(4 * p + 2), Y(4 * p + 3));
            if (WFEN & 1) fence_async_smem();
            __syncwarp();
            if (lane == 0) mbar_arrive(bar + 104 + (it & 1) * 24);
            if (PSM < 3 && !PDF) direct();
            TR(29, it * 3 + wg);
            ST(16 + wg);
        }
        __syncwarp();
        if (lane == 0) mbar_arrive(sbase + SM_PBAR + 56);
    }

    {
        uint32_t any;
        asm volatile("{\n.reg .pred p, q;\nsetp.ne.u32 q, %1, 0;\nbarrier.cta.red.or.pred.aligned p, %2, 128, q;\nselp.u32 %0, 1, 0, p;\n}\n"
                     : "=r"(any) : "r"((uint32_t)bad), "r"(12 + wg) : "memory");
        if (!any) return;
    }
    redo(P, smem + wg * FB_BYTES, tag, 12 + wg);
}

}

typedef CUresult (*PFN_encodeTiled)(CUtensorMap*, CUtensorMapDataType, cuuint32_t, void*, const cuuint64_t*,
                                    const cuuint64_t*, const cuuint32_t*, const cuuint32_t*, CUtensorMapInterleave,
                                    CUtensorMapSwizzle, CUtensorMapL2promotion, CUtensorMapFloatOOBfill);

extern "C" void kernel_launch(void* const* d_in, const int* in_sizes, int n_in, void* d_out, int out_size) {
    swin::Params P;
    P.x           = (const __nv_bfloat16*)d_in[0];
    P.wqkv        = (const __nv_bfloat16*)d_in[1];
    P.wo          = (const __nv_bfloat16*)d_in[2];
    P.logit_scale = (const __nv_bfloat16*)d_in[3];
    P.cpb_w1      = (const __nv_bfloat16*)d_in[4];
    P.cpb_w2      = (const __nv_bfloat16*)d_in[5];
    P.rel_coords  = (const __nv_bfloat16*)d_in[6];
    P.rel_idx     = (const int*)d_in[7];
    P.mask        = (const __nv_bfloat16*)d_in[8];
    P.out         = (__nv_bfloat16*)d_out;
    P.z1 = 0;
    static PFN_encodeTiled encode = nullptr;
    if (!encode) {
        cudaFuncSetAttribute(swin::swin_window_attn_kernel, cudaFuncAttributeMaxDynamicSharedMemorySize, swin::SM_TOTAL);
        cudaDriverEntryPointQueryResult qr;
        cudaGetDriverEntryPoint("cuTensorMapEncodeTiled", (void**)&encode, cudaEnableDefault, &qr);
    }
    CUtensorMap xmap, xmap4, xmap3, omap, wmap, smap, omapb, xmapa, xmapb, smap3, wraw, smapw;
    const cuuint32_t estr[4] = {1, 1, 1, 1};
    auto make = [&](CUtensorMap* m, const void* base, int rank, const cuuint64_t* gdim, const cuuint64_t* gstr,
                    const cuuint32_t* box, CUtensorMapSwizzle swz = CU_TENSOR_MAP_SWIZZLE_128B) {
        CUresult r = encode(m, CU_TENSOR_MAP_DATA_TYPE_BFLOAT16, rank, const_cast<void*>(base), gdim, gstr, box, estr,
               CU_TENSOR_MAP_INTERLEAVE_NONE, swz, CU_TENSOR_MAP_L2_PROMOTION_L2_128B,
               CU_TENSOR_MAP_FLOAT_OOB_FILL_NONE);
        (void)r;
    };
    {
        const cuuint64_t gdim[3] = {192, swin::IMG, swin::IMG}, gstr[2] = {384, swin::IMG * 384};
        const cuuint32_t box[3] = {64, 7, 7}, box4[3] = {64, 4, 1}, box3[3] = {64, 3, 1};
        make(&xmap, P.x, 3, gdim, gstr, box);
        make(&xmap4, P.x, 3, gdim, gstr, box4);
        make(&xmap3, P.x, 3, gdim, gstr, box3);
        const cuuint32_t boxa[3] = {64, 7, 3}, boxb[3] = {64, 7, 4};
        make(&xmapa, P.x, 3, gdim, gstr, boxa);
        make(&xmapb, P.x, 3, gdim, gstr, boxb);
    }
    {
        const cuuint64_t gdim[2] = {192, (cuuint64_t)swin::NPIX}, gstr[1] = {384};
        const cuuint32_t box64[2] = {64, 64};
        make(&omap, d_out, 2, gdim, gstr, box64);
        const cuuint64_t gdimb[2] = {192, (cuuint64_t)swin::SEG_B};
        make(&omapb, d_out, 2, gdimb, gstr, box64);
    }
    {
        const cuuint64_t gdim[2] = {576, 192}, gstr[1] = {1152};
        const cuuint32_t box[2] = {32, 192}, box2[2] = {64, 192};
        make(&wmap, P.wqkv, 2, gdim, gstr, box, CU_TENSOR_MAP_SWIZZLE_64B);
        make(&wraw, P.wqkv, 2, gdim, gstr, box2);
    }
    {
        const cuuint64_t gdim[4] = {32, 6, swin::IMG, swin::IMG}, gstr[3] = {64, 384, swin::IMG * 384};
        const cuuint32_t box7[4] = {32, 3, 7, 7}, box3[4] = {32, 3, 7, 3}, boxw[4] = {32, 3, 4, 1};
        make(&smap, d_out, 4, gdim, gstr, box7, CU_TENSOR_MAP_SWIZZLE_64B);
        make(&smap3, d_out, 4, gdim, gstr, box3, CU_TENSOR_MAP_SWIZZLE_64B);
        const cuuint64_t gdimw[4] = {32, 6, 4, swin::IMG};
        make(&smapw, (char*)d_out - 384, 4, gdimw, gstr, boxw, CU_TENSOR_MAP_SWIZZLE_64B);
    }
    P.npair = NPAIR; P.need = swin::ROW_DONE;
    P.t1 = swin::TILES - (NTAIL - NOLD);
    P.spread = ((132 - 2 * NPAIR) * 65536 + 131) / 132;
    swin::swin_window_attn_kernel<<<132, swin::NTHREADS, swin::SM_TOTAL>>>(P, xmap, xmap4, xmap3, omap, wmap, smap, omapb, xmapa, xmapb, smap3, wraw, smapw);
}
```
